```python
import torch

def _softmax(x, axis=-1):
    return torch.softmax(x, dim=axis)

def _gelu(x):
    return torch.nn.functional.gelu(x, approximate='tanh')

def _silu(x):
    return torch.nn.functional.silu(x)

def _sigmoid(x):
    return torch.sigmoid(x)

def _layernorm(x, axis=-1, eps=1e-05):
    m = x.mean(dim=axis, keepdim=True)
    v = x.var(dim=axis, keepdim=True, unbiased=False)
    return (x - m) / torch.sqrt(v + eps)

def _scatter_add(tgt, idx, src, axis=0):
    return tgt.clone().index_add_(axis, idx, src)

def _segment_sum(src, seg, n):
    out = torch.zeros((n,) + src.shape[1:], dtype=src.dtype)
    return out.index_add_(0, seg, src)

def _pad(x, pw):
    flat = tuple((v for pair in reversed(pw) for v in pair))
    return torch.nn.functional.pad(x, flat)
kernel_name = 'adaLN_cond__sliding_block_cached__glu_gated_glu__decode'

def setup_inputs():

    _w = lambda a: (lambda t: t.to(torch.bfloat16) if t.is_floating_point() else t)(torch.as_tensor(a))

    def _A_setup():
        B, Sq, D = (8, 1, 512)
        Hq, Hkv, Sk, Dh = (32, 32, 4096, 128)
        assert Hq % Hkv == 0, (Hq, Hkv)
        return {'x': _w((lambda *s: torch.randn(*s, dtype=torch.bfloat16) * 0.05)(B, Sq, D)), 'k_cache': _w((lambda *s: torch.randn(*s, dtype=torch.bfloat16) * 3.2)(B, Hkv, Sk, Dh)), 'v_cache': _w((lambda *s: torch.randn(*s, dtype=torch.bfloat16) * 0.4)(B, Hkv, Sk, Dh)), 'wq': _w((lambda *s: torch.randn(*s, dtype=torch.bfloat16) * 3.2)(D, Hq * Dh) * D ** (-0.5)), 'wo': _w((lambda *s: torch.randn(*s, dtype=torch.bfloat16) * 0.4)(Hq * Dh, D) * (Hq * Dh) ** (-0.5))}
    _A_in = _A_setup()

    def _B_setup():
        B, S, D, F = (8, 1, 512, 1376)
        return {'x': _w((lambda *s: torch.randn(*s, dtype=torch.bfloat16) * 0.05)(B, S, D)), 'w_gate': _w((lambda *s: torch.randn(*s, dtype=torch.bfloat16) * 0.05)(D, F)), 'w_up': _w((lambda *s: torch.randn(*s, dtype=torch.bfloat16) * 0.05)(D, F)), 'w_down': _w((lambda *s: torch.randn(*s, dtype=torch.bfloat16) * 0.05)(F, D))}
    _B_in = _B_setup()
    return {'A_x': _A_in['x'], 'A_k_cache': _A_in['k_cache'], 'A_v_cache': _A_in['v_cache'], 'A_wq': _A_in['wq'], 'A_wo': _A_in['wo'], 'B_x': _B_in['x'], 'B_w_gate': _B_in['w_gate'], 'B_w_up': _B_in['w_up'], 'B_w_down': _B_in['w_down'], 'c': _w((lambda *s: torch.randn(*s, dtype=torch.bfloat16) * 0.1)(8, 512) * 8.0), 'w_mod': _w((lambda *s: torch.randn(*s, dtype=torch.bfloat16) * 0.1)(512, 6 * 512) * 512 ** (-0.5) * 8.0)}

def reference(A_x, A_k_cache, A_v_cache, A_wq, A_wo, B_x, B_w_gate, B_w_up, B_w_down, c, w_mod):

    def _A_ref(x, k_cache, v_cache, wq, wo):
        B, Sq, D = x.shape
        Hq, Dh = (32, 128)
        Hkv, Sk = (k_cache.shape[1], k_cache.shape[2])
        W = min(4096, max(256, Sk // 4))
        rep = Hq // Hkv
        q = (lambda x, *d: x.permute(*d))((x @ wq).reshape(B, Sq, Hq, Dh), 0, 2, 1, 3)
        k = (lambda x, n, axis: torch.repeat_interleave(x, n, dim=axis))(k_cache[:, :, Sk - W:, :], rep, axis=1)
        v = (lambda x, n, axis: torch.repeat_interleave(x, n, dim=axis))(v_cache[:, :, Sk - W:, :], rep, axis=1)
        scores = torch.einsum('bhqd,bhkd->bhqk', q, k) * Dh ** (-0.5)
        p = _softmax(scores, axis=-1)
        o = torch.einsum('bhqk,bhkd->bhqd', p, v)
        return (lambda x, *d: x.permute(*d))(o, 0, 2, 1, 3).reshape(B, Sq, Hq * Dh) @ wo

    def _B_ref(x, w_gate, w_up, w_down):
        g = torch.einsum('bsd,df->bsf', x, w_gate)
        u = torch.einsum('bsd,df->bsf', x, w_up)
        h = _sigmoid(g) * u
        return torch.einsum('bsf,fd->bsd', h, w_down)
    x = A_x
    mod = (_silu(c) @ w_mod).reshape(c.shape[0], 6, 1, -1)
    sa, ca, ga, sb, cb, gb = (mod[:, 0].clone(), mod[:, 1].clone(), mod[:, 2].clone(), mod[:, 3].clone(), mod[:, 4].clone(), mod[:, 5].clone())
    h = _layernorm(x, axis=-1) * (1 + ca) + sa
    x = x + ga * _A_ref(h, A_k_cache, A_v_cache, A_wq, A_wo)
    h = _layernorm(x, axis=-1) * (1 + cb) + sb
    x = x + gb * _B_ref(h, B_w_gate, B_w_up, B_w_down)
    return x
```

```cpp
#include <cuda_runtime.h>
#include <cuda_bf16.h>
#include <cuda.h>
#include <stdint.h>

namespace {

constexpr int NB = 8, DM = 512, NH = 32, DH = 128, SK = 4096, WIN = 1024, FF = 1376;
constexpr int NCTA = 128, NTHR = 288, NALL = 320;
constexpr int NT = 16;
constexpr int NF1 = 86, DN0 = 96;
constexpr unsigned SENT = 0xFFFFFFFFu;
constexpr int SPIN_MAX = 1 << 20;

#define PWIN0 12
#define PWIN 16
#define PSW 22
#define PNAP 30
#define NTRK 4
#define NPF 4
#define QN 6
#define TAU 169
#define ANCH0 250
#define LEAD 2100
#define PACE0 7000
#define PACE_NAP 300
#define WOA_ISSUE 3
#define WO_GAP 2
#define WOA_READ 8
#define MOD_T2 2000
#define XA_ 0
#define WP 4
#define W0 800
#define WS 220
#define PF2 1500
#define FFN_T2 2300
#define RM 0
#define RP 1
#define RD0 100
#define RDS 180
#define SD1 1100
#define HDW 0
#define XD0 100
#define HD0 1200
#define XC 2
#define NPRE 8
#define WLATE 0
#define VSPIN 0
#define FASTLN 0

constexpr int UNIT = 4096, REG = 8 * UNIT;
constexpr int SM_SCR = 6 * REG;
constexpr int SCR = 2048;
constexpr int SM_MN = SM_SCR + 8 * SCR;
constexpr int SM_SC = SM_MN + 8192;
constexpr int SM_BAR = SM_SC + 8192;
constexpr int SM_BM = SM_BAR + 512, SM_BT = SM_BM + 8, SM_BN = SM_BM + 16;
constexpr int SM_AN = SM_BM + 32, SM_SIDE = SM_BM + 36, SM_TAG = SM_BM + 40, SM_MASK = SM_BM + 44;
constexpr int SM_ST = SM_BAR + 576;
constexpr int SM_ML = SM_ST + 512;
constexpr int SM_PR = SM_ML + 64;
constexpr int SM_CK = SM_PR + 512;
constexpr int SM_TOTAL = SM_CK + 800;
constexpr int SC_M = 0, SC_Q = 256;
constexpr int SC_F1 = 0, SC_DN = 0, SC_RX = 1536;
constexpr int B_INIT = 0, B_ALL = 2, B_MOD = 3, B_WQ = 4, B_LAST = 5, B_RDY = 6, B_DN = 7, B_PRE = 8, B_FIN = 9, B_GO = 10, B_SIDE = 11, B_Q = 12;

constexpr unsigned HOME = 0xB3000;
constexpr int X_PART = 0;
constexpr int X_Q = 0x100000;
constexpr int X_M1 = 0x140000;
constexpr int X_X1 = 0x150000;
constexpr int X_HM = 0x160000;
constexpr int X_MOD = 0x170000;
constexpr int X_SIDE = 0x176000;
constexpr int X_EPOCH = 0x176400;
constexpr int X_READY = 0x176480;
constexpr int X_LAG = 0x178000;
constexpr int X_PRB = 0x180000;
constexpr int X_ALIGN = 0x200000;
__device__ uint4 g_raw[2 * X_ALIGN / 16];
__device__ __forceinline__ unsigned blk(unsigned base, unsigned k, unsigned s) { const unsigned o = base + k * 8192; return o + ((__popc(o & HOME) ^ s) & 1) * 4096; }

#define CKDECL
#define CKEND
#define CKP(i)
#define CKN(i, v)
#define CKA(i)
struct Params {
    CUtensorMap wm, wq, k, v, wn, wo, wg, wu, wd;
    const __nv_bfloat16* wdp;
    __nv_bfloat16* out;
};

__device__ __forceinline__ uint32_t smem_u32(const void* p) { return (uint32_t)__cvta_generic_to_shared(p); }
__device__ __forceinline__ void mbar_init(uint32_t a, uint32_t c) { asm volatile("mbarrier.init.shared::cta.b64 [%0], %1;" :: "r"(a), "r"(c) : "memory"); }
__device__ __forceinline__ void mbar_expect(uint32_t a, uint32_t b) { asm volatile("mbarrier.arrive.expect_tx.shared::cta.b64 _, [%0], %1;" :: "r"(a), "r"(b) : "memory"); }
__device__ __forceinline__ void mbar_wait(uint32_t a, uint32_t par) {
    uint32_t ok; int n = 0;
    do {
        asm volatile("{\n.reg .pred p;\nmbarrier.try_wait.parity.shared::cta.b64 p, [%1], %2, 2000;\nselp.u32 %0, 1, 0, p;\n}" : "=r"(ok) : "r"(a), "r"(par) : "memory");
        if (++n > SPIN_MAX) __trap();
    } while (!ok);
}
__device__ __forceinline__ bool mbar_test(uint32_t a, uint32_t par) {
    uint32_t ok; asm volatile("{\n.reg .pred p;\nmbarrier.test_wait.parity.shared::cta.b64 p, [%1], %2;\nselp.u32 %0, 1, 0, p;\n}" : "=r"(ok) : "r"(a), "r"(par) : "memory"); return ok;
}
__device__ __forceinline__ void tma2d(uint32_t dst, const CUtensorMap* m, int x, int y, uint32_t bar) {
    asm volatile("cp.async.bulk.tensor.2d.shared::cluster.global.mbarrier::complete_tx::bytes [%0], [%1, {%3, %4}], [%2];"
                 :: "r"(dst), "l"(m), "r"(bar), "r"(x), "r"(y) : "memory");
}
__device__ __forceinline__ void tma5d(uint32_t dst, const CUtensorMap* m, int x, int y, uint32_t bar) {
    asm volatile("cp.async.bulk.tensor.5d.shared::cluster.global.mbarrier::complete_tx::bytes [%0], [%1, {%3, 0, 0, 0, %4}], [%2];"
                 :: "r"(dst), "l"(m), "r"(bar), "r"(x), "r"(y) : "memory");
}
__device__ __forceinline__ void tma_kv(uint32_t dst, const CUtensorMap* m, int row, uint32_t bar, uint64_t pol) {
    asm volatile("cp.async.bulk.tensor.3d.shared::cluster.global.mbarrier::complete_tx::bytes.L2::cache_hint [%0], [%1, {0, %3, 0}], [%2], %4;"
                 :: "r"(dst), "l"(m), "r"(bar), "r"(row), "l"(pol) : "memory");
}
__device__ __forceinline__ void pf_bulk(const void* p, uint32_t n) { asm volatile("cp.async.bulk.prefetch.L2.global [%0], %1;" :: "l"(p), "r"(n) : "memory"); }
__device__ __forceinline__ void pf_line(const void* p) { asm volatile("prefetch.global.L2 [%0];" :: "l"(p) : "memory"); }
__device__ __forceinline__ void pf_map(const CUtensorMap* m) { asm volatile("prefetch.tensormap [%0];" :: "l"(m) : "memory"); }
__device__ __forceinline__ void ldsm(uint32_t (&r)[4], uint32_t a) {
    asm volatile("ldmatrix.sync.aligned.m8n8.x4.shared.b16 {%0,%1,%2,%3}, [%4];" : "=r"(r[0]), "=r"(r[1]), "=r"(r[2]), "=r"(r[3]) : "r"(a) : "memory");
}
__device__ __forceinline__ void ldsm_t(uint32_t (&r)[4], uint32_t a) {
    asm volatile("ldmatrix.sync.aligned.m8n8.x4.trans.shared.b16 {%0,%1,%2,%3}, [%4];" : "=r"(r[0]), "=r"(r[1]), "=r"(r[2]), "=r"(r[3]) : "r"(a) : "memory");
}
__device__ __forceinline__ void mma(float (&c)[4], uint32_t a0, uint32_t a1, uint32_t a2, uint32_t a3, uint32_t b0, uint32_t b1) {
    asm("mma.sync.aligned.m16n8k16.row.col.f32.bf16.bf16.f32 {%0,%1,%2,%3}, {%4,%5,%6,%7}, {%8,%9}, {%0,%1,%2,%3};"
        : "+f"(c[0]), "+f"(c[1]), "+f"(c[2]), "+f"(c[3]) : "r"(a0), "r"(a1), "r"(a2), "r"(a3), "r"(b0), "r"(b1));
}
__device__ __forceinline__ void mma(float (&c)[4], const uint32_t (&a)[4], uint32_t b0, uint32_t b1) { mma(c, a[0], a[1], a[2], a[3], b0, b1); }
__device__ __forceinline__ uint32_t movm(uint32_t a) { uint32_t r; asm volatile("movmatrix.sync.aligned.m8n8.trans.b16 %0, %1;" : "=r"(r) : "r"(a)); return r; }
__device__ __forceinline__ uint32_t pack2(float lo, float hi) { uint32_t r; asm("cvt.rn.bf16x2.f32 %0, %1, %2;" : "=r"(r) : "f"(hi), "f"(lo)); return r; }
__device__ __forceinline__ float blo(uint32_t w) { return __uint_as_float(w << 16); }
__device__ __forceinline__ float bhi(uint32_t w) { return __uint_as_float(w & 0xFFFF0000u); }
__device__ __forceinline__ float rbf(float x) { return blo(pack2(x, 0.f)); }
__device__ __forceinline__ uint32_t add2(uint32_t a, uint32_t b) { uint32_t r; asm("add.rn.bf16x2 %0, %1, %2;" : "=r"(r) : "r"(a), "r"(b)); return r; }
__device__ __forceinline__ uint32_t sub2(uint32_t a, uint32_t b) { uint32_t r; asm("sub.rn.bf16x2 %0, %1, %2;" : "=r"(r) : "r"(a), "r"(b)); return r; }
__device__ __forceinline__ uint32_t mul2(uint32_t a, uint32_t b) { uint32_t r; asm("mul.rn.bf16x2 %0, %1, %2;" : "=r"(r) : "r"(a), "r"(b)); return r; }
constexpr uint32_t ONE2 = 0x3F803F80u;
__device__ __forceinline__ float ex2(float x) { float y; asm("ex2.approx.ftz.f32 %0, %1;" : "=f"(y) : "f"(x)); return y; }
__device__ __forceinline__ uint4 ldg_rlx128(const void* p) {
    uint4 v; asm volatile("ld.relaxed.gpu.global.v4.u32 {%0,%1,%2,%3}, [%4];" : "=r"(v.x), "=r"(v.y), "=r"(v.z), "=r"(v.w) : "l"(p) : "memory"); return v;
}
__device__ __forceinline__ uint4 ldg_rlx2x64(const void* p) {
    unsigned long long a, b; asm volatile("ld.relaxed.gpu.global.v2.u64 {%0,%1}, [%2];" : "=l"(a), "=l"(b) : "l"(p) : "memory");
    return make_uint4((unsigned)a, (unsigned)(a >> 32), (unsigned)b, (unsigned)(b >> 32));
}
__device__ __forceinline__ uint2 ldg_rlx64(const void* p) {
    unsigned long long a; asm volatile("ld.relaxed.gpu.global.u64 %0, [%1];" : "=l"(a) : "l"(p) : "memory"); return make_uint2((unsigned)a, (unsigned)(a >> 32));
}
__device__ __forceinline__ unsigned ldg_acq32(const void* p) { unsigned v; asm volatile("ld.acquire.gpu.global.u32 %0, [%1];" : "=r"(v) : "l"(p) : "memory"); return v; }
__device__ __forceinline__ void red_add(void* p, unsigned v) { asm volatile("red.relaxed.gpu.global.add.u32 [%0], %1;" :: "l"(p), "r"(v) : "memory"); }
__device__ __forceinline__ unsigned now_ns() { unsigned t; asm volatile("mov.u32 %0, %%globaltimer_lo;" : "=r"(t)); return t; }
__device__ __forceinline__ void nap(unsigned ns) { asm volatile("nanosleep.u32 %0;" :: "r"(ns)); }
__device__ __forceinline__ unsigned ldg_rlx32(const void* p) { unsigned v; asm volatile("ld.relaxed.gpu.global.u32 %0, [%1];" : "=r"(v) : "l"(p) : "memory"); return v; }
__device__ __forceinline__ void stg_rlx32(void* p, unsigned v) { asm volatile("st.relaxed.gpu.global.u32 [%0], %1;" :: "l"(p), "r"(v) : "memory"); }
__device__ __forceinline__ void stg_rlx16(void* p, unsigned v) { asm volatile("st.relaxed.gpu.global.u16 [%0], %1;" :: "l"(p), "h"((unsigned short)v) : "memory"); }
__device__ __forceinline__ uint4 ldg_b128(const void* p) {
    unsigned long long a, b; asm volatile("{\n.reg .b128 x;\nld.relaxed.gpu.global.b128 x, [%2];\nmov.b128 {%0,%1}, x;\n}" : "=l"(a), "=l"(b) : "l"(p) : "memory");
    return make_uint4((unsigned)a, (unsigned)(a >> 32), (unsigned)b, (unsigned)(b >> 32));
}
__device__ __forceinline__ void stg_b128(void* p, uint4 v) {
    asm volatile("{\n.reg .b128 x;\nmov.b128 x, {%1,%2};\nst.relaxed.gpu.global.b128 [%0], x;\n}" :: "l"(p), "l"(v.x | ((unsigned long long)v.y << 32)), "l"(v.z | ((unsigned long long)v.w << 32)) : "memory");
}
__device__ __forceinline__ int rowoff(int b, int c) { return ((c >> 6) * 2 + ((c >> 2) & 1)) * 512 + b * 64 + (c & 3) * 16 + ((c >> 3) & 1) * 8 + ((c >> 5) & 1) * 4 + ((c >> 4) & 1) * 2; }
__device__ __forceinline__ void stg_rlx64(void* p, unsigned lo, unsigned hi) {
    unsigned long long a = lo | ((unsigned long long)hi << 32); asm volatile("st.relaxed.gpu.global.u64 [%0], %1;" :: "l"(p), "l"(a) : "memory");
}
__device__ __forceinline__ void stg_rlx128(void* p, uint4 v) { asm volatile("st.relaxed.gpu.global.v4.u32 [%0], {%1,%2,%3,%4};" :: "l"(p), "r"(v.x), "r"(v.y), "r"(v.z), "r"(v.w) : "memory"); }
__device__ __forceinline__ void sts32u(uint32_t a, unsigned x) { asm volatile("st.volatile.shared.u32 [%0], %1;" :: "r"(a), "r"(x) : "memory"); }
__device__ __forceinline__ unsigned lds32u(uint32_t a) { unsigned v; asm volatile("ld.volatile.shared.u32 %0, [%1];" : "=r"(v) : "r"(a) : "memory"); return v; }
__device__ __forceinline__ void spin(unsigned c0, unsigned d) { while ((unsigned)clock() - c0 < d) {} }
__device__ __forceinline__ void fence_gpu() { asm volatile("fence.acq_rel.gpu;" ::: "memory"); }
__device__ __forceinline__ bool valid4(const uint4& v) { return max(max(v.x, v.y), max(v.z, v.w)) != SENT; }
template <int ID, int N> __device__ __forceinline__ void bar_sync() { asm volatile("bar.sync %0, %1;" :: "n"(ID), "n"(N) : "memory"); }
template <int ID, int N> __device__ __forceinline__ void bar_arrive() { asm volatile("bar.arrive %0, %1;" :: "n"(ID), "n"(N) : "memory"); }
__device__ __forceinline__ void sts64(uint32_t a, float x, float y) { asm volatile("st.shared.v2.f32 [%0], {%1,%2};" :: "r"(a), "f"(x), "f"(y) : "memory"); }
__device__ __forceinline__ void sts128(uint32_t a, uint4 v) { asm volatile("st.shared.v4.u32 [%0], {%1,%2,%3,%4};" :: "r"(a), "r"(v.x), "r"(v.y), "r"(v.z), "r"(v.w) : "memory"); }
__device__ __forceinline__ void sts128f(uint32_t a, float x, float y, float z, float w) { asm volatile("st.shared.v4.f32 [%0], {%1,%2,%3,%4};" :: "r"(a), "f"(x), "f"(y), "f"(z), "f"(w) : "memory"); }
__device__ __forceinline__ void sts32(uint32_t a, float x) { asm volatile("st.shared.f32 [%0], %1;" :: "r"(a), "f"(x) : "memory"); }
__device__ __forceinline__ float2 lds64(uint32_t a) { float2 v; asm volatile("ld.shared.v2.f32 {%0,%1}, [%2];" : "=f"(v.x), "=f"(v.y) : "r"(a) : "memory"); return v; }
__device__ __forceinline__ float lds32(uint32_t a) { float v; asm volatile("ld.shared.f32 %0, [%1];" : "=f"(v) : "r"(a) : "memory"); return v; }
__device__ __forceinline__ float4 lds128(uint32_t a) { float4 v; asm volatile("ld.shared.v4.f32 {%0,%1,%2,%3}, [%4];" : "=f"(v.x), "=f"(v.y), "=f"(v.z), "=f"(v.w) : "r"(a) : "memory"); return v; }
__device__ __forceinline__ float2 sum8(uint32_t a) {
    float2 v[8];
#pragma unroll
    for (int i = 0; i < 8; i++) v[i] = lds64(a + i * SCR);
    return make_float2(((v[0].x + v[1].x) + (v[2].x + v[3].x)) + ((v[4].x + v[5].x) + (v[6].x + v[7].x)),
                       ((v[0].y + v[1].y) + (v[2].y + v[3].y)) + ((v[4].y + v[5].y) + (v[6].y + v[7].y)));
}
template <int STRIDE> __device__ __forceinline__ float4 sum8x4(uint32_t a) {
    float4 v[8];
#pragma unroll
    for (int i = 0; i < 8; i++) v[i] = lds128(a + i * STRIDE);
    return make_float4(((v[0].x + v[1].x) + (v[2].x + v[3].x)) + ((v[4].x + v[5].x) + (v[6].x + v[7].x)), ((v[0].y + v[1].y) + (v[2].y + v[3].y)) + ((v[4].y + v[5].y) + (v[6].y + v[7].y)),
                       ((v[0].z + v[1].z) + (v[2].z + v[3].z)) + ((v[4].z + v[5].z) + (v[6].z + v[7].z)), ((v[0].w + v[1].w) + (v[2].w + v[3].w)) + ((v[4].w + v[5].w) + (v[6].w + v[7].w)));
}
__device__ __forceinline__ float rcp(float x) { float y; asm("rcp.approx.ftz.f32 %0, %1;" : "=f"(y) : "f"(x)); return y; }
__device__ __forceinline__ float sigmoid_f(float x) { return rcp(1.0f + ex2(x * -1.4426950408889634f)); }
__device__ __forceinline__ uint32_t silu2(uint32_t c) { const float a = blo(c), b = bhi(c); return pack2(a * sigmoid_f(a), b * sigmoid_f(b)); }
__device__ __forceinline__ void ln_consts(float mean, float var, uint32_t& mu2, float& rs) {
    mu2 = pack2(mean, mean);
    float sd; asm("sqrt.approx.ftz.f32 %0, %1;" : "=f"(sd) : "f"(rbf(rbf(var) + 1e-5f)));
    rs = rcp(rbf(sd));
}
__device__ __forceinline__ uint32_t ln_norm(uint32_t x2, uint32_t mu2, float rs) { const uint32_t d = sub2(x2, mu2); return pack2(blo(d) * rs, bhi(d) * rs); }

__global__ void __launch_bounds__(NALL, 1) fused_kernel(const __nv_bfloat16* const px, const __nv_bfloat16* const pc, const __nv_bfloat16* const pk, const __nv_bfloat16* const pwm,
                                                        const __nv_bfloat16* const pwq, char* const X, const __grid_constant__ Params P) {
    extern __shared__ __align__(1024) unsigned char smem[];
    const uint32_t sb = smem_u32(smem);
    const int tid = threadIdx.x, w = tid >> 5, lane = tid & 31, g = lane >> 2, t = lane & 3;
    const int cta = blockIdx.x, head = cta >> 2, bat = (cta & 3) * 2 + (w >> 2);
    const uint32_t s0 = sb + w * UNIT, s2 = s0 + 4 * REG;
    const uint32_t bar0 = sb + SM_BAR + w * 64;
    const uint32_t barC = bar0 + 32;
    const uint32_t scr = sb + SM_SCR, myscr = scr + w * SCR;
    const unsigned t_start = now_ns();
    CKDECL;
    uint64_t pol;
    asm volatile("createpolicy.fractional.L2::evict_first.b64 %0, 1.0;" : "=l"(pol));
    auto ffn_terms = [&]() {
        const int e = tid - 256;
        bar_sync<B_PRE, NALL>();
        const float4 c = sum8x4<UNIT>(sb + REG + (e & 7) * 144 + (e >> 3) * 16), d = sum8x4<UNIT>(sb + REG + 1152 + (e & 7) * 144 + (e >> 3) * 16);
        sts128f(sb + SM_MN + e * 16, c.x, c.y, c.z, c.w); sts128f(sb + SM_MN + 1024 + e * 16, d.x, d.y, d.z, d.w);
        bar_arrive<B_FIN, NALL>();
    };
    auto reduce = [&](int task, uint32_t rx, unsigned c0, unsigned dly) {
        const char* const pp = X + blk(X_PART, task, lds32u(sb + SM_SIDE)) + lane * 16;
        const float4 gx = lds128(rx + (lane & 7) * 16);
        char* const xo = X + (lane >> 4) * 16384 + blk(X_X1, (task >> 3) & 1, lane >> 3) + (task & 7) * 512 + (task >> 4) * 64 + (lane & 7) * 8;
        uint4 v[8]; int n = 0;
        spin(c0, dly);
#pragma unroll
        for (int j = 0; j < 8; j++) v[j] = ldg_b128(pp + j * 512);
        while (true) {
            bool any = false;
#pragma unroll
            for (int j = 0; j < 8; j++) { const bool bad = v[j].x == SENT; any |= bad; if (bad) v[j] = ldg_b128(pp + j * 512); }
            if (!__any_sync(~0u, any)) break;
            if (++n > SPIN_MAX) __trap();
        }
        CKP(4); CKN(10, n + 1);
#define RSUM(f) (((__uint_as_float(v[0].f) + __uint_as_float(v[1].f)) + (__uint_as_float(v[2].f) + __uint_as_float(v[3].f))) + ((__uint_as_float(v[4].f) + __uint_as_float(v[5].f)) + (__uint_as_float(v[6].f) + __uint_as_float(v[7].f))))
        float a[4] = {RSUM(x), RSUM(y), RSUM(z), RSUM(w)};
#pragma unroll
        for (int i = 0; i < 4; i++) a[i] += __shfl_xor_sync(~0u, a[i], 8);
#pragma unroll
        for (int i = 0; i < 4; i++) a[i] += __shfl_xor_sync(~0u, a[i], 16);
        const unsigned x0 = add2(__float_as_uint(gx.z), mul2(__float_as_uint(gx.x), pack2(a[0], a[1]))), x1 = add2(__float_as_uint(gx.w), mul2(__float_as_uint(gx.y), pack2(a[2], a[3])));
        if (XC > 1 || lane < 16) stg_rlx64(xo, x0, x1);
        if (XC > 2) stg_rlx64(xo + 32768, x0, x1);
        CKP(5);
    };
    if (w == 9) {
#pragma unroll
        for (int i = 0; i < 2; i++) pf_line(pwm + (size_t)(cta * 4 + i * 2 + (lane >> 4)) * (6 * DM) + (lane & 15) * 64);
        const uint32_t sl = sb + SM_PR + lane * 16;
        char* const pl = X + blk(X_PRB, cta >> 1, lane & 1) + (lane >> 1) * 256 + (cta & 1) * 128;
        {
            char* const ps = X + X_PRB + (cta >> 1) * 8192 + (lane >> 1) * 256 + (cta & 1) * 128 + (lane & 1) * 16;
            sts32u(sl, 0);
            stg_rlx128(ps, make_uint4(1, 1, 1, 1)); stg_rlx128(ps + 4096, make_uint4(1, 1, 1, 1));
            __syncwarp();
        }
        unsigned v; asm volatile("atom.relaxed.gpu.global.add.u32 %0, [%1], 1;" : "=r"(v) : "l"(pl) : "memory");
        unsigned tag = ldg_rlx32(X + X_EPOCH);
#pragma unroll
        for (int i = 0; i < NPF; i++) pf_line(pk + (size_t)((((cta & 3) * 2 + (i & 1)) * NH + head) * SK + (SK - WIN) + (i >> 1) * 16) * DH + lane * 64);
        if (lane == 0) pf_bulk(pwq + (size_t)cta * QN * 1024, QN * 2048);
        CKA(0);
        if (lane == 0) sts32u(sb + SM_AN, t_start + ANCH0);
        if (lane < 8) sts32u(sb + SM_BAR + lane * 64 + 56, 0);
        {
            int d, n = 0;
#pragma unroll 1
            for (int r = 0; r < 4; r++) {
                if (v == SENT) __trap();
                asm volatile("cp.async.cg.shared.global [%0], [%1], 16;" :: "r"(sl), "l"(pl) : "memory");
                unsigned m;
                do {
                    m = __ballot_sync(~0u, lds32u(sl));
                    d = __popc(m & 0xAAAAAAAAu) - __popc(m & 0x55555555u);
                    if (++n > SPIN_MAX) __trap();
                } while (abs(d) < 6 && m != ~0u);
                if (abs(d) >= 6) break;
                asm volatile("cp.async.wait_all;" ::: "memory");
                sts32u(sl, 0);
                asm volatile("atom.relaxed.gpu.global.add.u32 %0, [%1], 1;" : "=r"(v) : "l"(pl) : "memory");
            }
            unsigned side = d > 0;
            tag++;
            if (lane == 0) { sts32u(sb + SM_SIDE, side); sts32u(sb + SM_TAG, tag); }
            bar_arrive<B_SIDE, NTHR>();
        }
        CKA(1);
        asm volatile("cp.async.wait_all;" ::: "memory");
        uint2* const g_lag = (uint2*)(X + X_LAG);
        while (now_ns() - t_start < PACE0) nap(200);
        for (int n = 0; n < SPIN_MAX; n++) {
            const unsigned mine = lane < 8 ? lds32u(sb + SM_BAR + lane * 64 + 56) : 30, t1 = now_ns();
            const unsigned lo = __reduce_min_sync(~0u, mine), sum = __reduce_add_sync(~0u, lane < 8 ? mine : 0);
            if (lo == 30) break;
            if (lo && lane == 0) stg_rlx64(g_lag + cta * 16, t1 - sum * TAU, tag);
            uint2 a = make_uint2(0, 0);
            if (cta == 0) {
                uint2 u[4];
#pragma unroll
                for (int i = 0; i < 4; i++) u[i] = ldg_rlx64(g_lag + (lane + 32 * i) * 16);
                const int s = __reduce_add_sync(~0u, (int)(u[0].x + u[1].x + u[2].x + u[3].x - 4 * t_start));
                if (__all_sync(~0u, (u[0].y == tag) & (u[1].y == tag) & (u[2].y == tag) & (u[3].y == tag)) && lane == 0) {
                    a = make_uint2(t_start + s / NCTA, tag);
                    stg_rlx64(g_lag + NCTA * 16, a.x, tag);
                }
            } else if (lane == 0) a = ldg_rlx64(g_lag + NCTA * 16);
            if (lane == 0 && a.y == tag) sts32u(sb + SM_AN, a.x - LEAD + (cta & 7) * (TAU / 8));
            __syncwarp();
            nap(PACE_NAP);
        }
        const unsigned side = lds32u(sb + SM_SIDE);
        const char* const sp = X + lane * 16 + (cta & (XC - 1)) * 16384 + blk(X_X1, (cta >> 3) & 1, side) + (cta & 7) * 512;
        bar_sync<B_RDY, NALL>();
        const unsigned c0 = clock() - lds32u(sb + SM_SIDE);
        reduce(cta, scr + SC_RX, c0, RD0 + 600);
        if (cta >= NF1 && cta < DN0) { CKEND; return; }
        if (RM) {
            int n = 0;
            spin(c0, SD1);
            while (__all_sync(~0u, ldg_rlx32(sp) == SENT)) if (++n > SPIN_MAX) __trap();
            CKN(11, n + 1);
        }
        spin(clock(), cta < NF1 ? XD0 : HD0);
        bar_arrive<B_GO, NTHR>();
        CKP(8);
        if (cta < NF1) ffn_terms();
        return;
    }
    if (w == 8) {
        const int row0 = ((cta & 3) * 2 * NH + head) * SK + (SK - WIN);
        auto kv_unit = [&](int u) {
            const uint32_t b = sb + SM_BAR + (u & 7) * 64 + (u >> 3) * 8;
            mbar_expect(b, UNIT);
            tma_kv(sb + (u >> 3) * REG + (u & 7) * UNIT, (u & 8) ? &P.v : &P.k, row0 + ((u >> 2) & 1) * NH * SK + (u & 3) * 16 + (u >> 4) * 64, b, pol);
        };
        if (lane == 0) {
            mbar_init(sb + SM_BM, 1);
#pragma unroll
            for (int i = 0; i < 8; i++) mbar_init(sb + SM_BAR + i * 64 + 48, 1);
            asm volatile("fence.mbarrier_init.release.cluster;" ::: "memory");
            CKA(0);
            mbar_expect(sb + SM_BM, 512 * 16);
            tma2d(sb + 4 * REG, &P.wm, cta * 8, 0, sb + SM_BM); tma2d(sb + 4 * REG + 256 * 16, &P.wm, cta * 8, 256, sb + SM_BM);
#pragma unroll 1
            for (int i = 0; i < 8; i++) { const uint32_t b = sb + SM_BAR + i * 64 + 48; mbar_expect(b, UNIT); tma2d(sb + 5 * REG + i * UNIT, &P.wq, cta * 32, i * 64, b); }
            CKA(1);
            mbar_init(sb + SM_BN, 1); mbar_init(sb + SM_BT, 1);
#pragma unroll
            for (int i = 0; i < 48; i++) mbar_init(sb + SM_BAR + (i & 7) * 64 + (i >> 3) * 8, 1);
            asm volatile("fence.mbarrier_init.release.cluster;" ::: "memory");
        }
        __syncwarp();
        bar_arrive<B_INIT, NTHR>();
        CKA(2);
        {
            uint32_t mine = lane >= NTRK ? 0 : lane < 8 ? sb + SM_BAR + lane * 64 + 48 : sb + SM_BM;
            int next = 0, lim = 32, n = 0;
            while (next < 48) {
                const bool idle = lane < (next < PSW ? PWIN0 : PWIN) && (mine == 0 || mbar_test(mine, 0));
                const unsigned m = __ballot_sync(~0u, idle);
                const int u = next + __popc(m & ((1u << lane) - 1));
                if (idle) {
                    mine = 0;
                    if (u < lim) { kv_unit(u); mine = sb + SM_BAR + (u & 7) * 64 + (u >> 3) * 8; }
                }
                next = min(next + __popc(m), lim);
                if (next == lim) {
                    if (lim == 32) { CKA(3); bar_sync<B_MOD, NTHR>(); } else if (lim == 40) { CKA(4); bar_sync<B_WQ, NTHR>(); CKA(5); }
                    lim += 8;
                }
                if (!m) nap(PNAP);
                if (++n > SPIN_MAX) __trap();
            }
        }
        if (lane < 5) pf_map(&P.wn + lane);
        CKA(6);
        float m[4][4] = {};
        auto late_mod = [&](uint32_t a, int h) {
            const int lrow = (lane & 7) + ((lane >> 4) << 3), lch = (lane >> 3) & 1;
            const uint32_t a0 = a + lrow * 32 + ((lch ^ ((lrow >> 2) & 1)) << 4);
            const uint32_t c0 = sb + SM_SC + h * 4096 + (lane & 7) * 128 + (((lane >> 3) ^ (lane & 7)) << 4);
#pragma unroll
            for (int j = 0; j < 8; j++) {
                uint32_t c[4], r[4], u[4];
                ldsm(c, (c0 + (j >> 1) * 1024) ^ ((j & 1) << 6)); ldsm_t(r, a0 + j * 1024); ldsm_t(u, a0 + j * 1024 + 512);
                mma(m[(j & 1) * 2], r, c[0], c[1]); mma(m[(j & 1) * 2 + 1], u, c[2], c[3]);
            }
        };
        if (cta < 96) {
#pragma unroll 1
            for (int h = 0; h < 2; h++) {
                if (lane == 0) { mbar_expect(sb + SM_BN, 8192); tma2d(sb + SM_MN, &P.wn, 2 * DM + cta * 16, h * 256, sb + SM_BN); }
                mbar_wait(sb + SM_BN, h);
                late_mod(sb + SM_MN, h);
                asm volatile("" :: "f"(m[0][0]), "f"(m[1][0]), "f"(m[2][0]), "f"(m[3][0]) : "memory");
                __syncwarp();
            }
#pragma unroll
            for (int e = 0; e < 4; e++) {
                float v = rbf((m[0][e] + m[1][e]) + (m[2][e] + m[3][e]));
                if (cta >= 64) v += 1.0f;
                stg_rlx16(X + X_MOD + (cta >> 5) * 8192 + rowoff(2 * t + (e & 1), (cta & 31) * 16 + g + (e >> 1) * 8), pack2(v, 0.f));
            }
        }
        CKA(7);
        {
            const unsigned side = lds32u(sb + SM_SIDE);
#pragma unroll
            for (int i = 0; i < 8; i++) stg_rlx128(X + blk(X_PART, cta, side) + i * 512 + lane * 16, make_uint4(SENT, SENT, SENT, SENT));
            if (lane == 0) stg_rlx32(X + X_SIDE + cta * 4, side);
        }
        bar_sync<B_Q, NTHR>();
        if (lane == 0) {
            CKA(8);
            const unsigned tag = lds32u(sb + SM_TAG);
            fence_gpu();
            red_add(X + X_READY, 1);
            int n = 0;
            while ((int)(ldg_acq32(X + X_READY) - tag * NCTA) < 0) { nap(1000); if (++n > SPIN_MAX) __trap(); }
            if (cta == 0) stg_rlx32(X + X_EPOCH, tag);
            CKA(9);
        }
        __syncwarp();
        {
            stg_rlx128(X + blk(X_Q, head >> 1, 0) + (head & 1) * 2048 + g * 256 + (cta & 3) * 64 + t * 16, make_uint4(0, 0, 0, 0));
            stg_rlx128(X + blk(X_Q, head >> 1, 1) + (head & 1) * 2048 + g * 256 + (cta & 3) * 64 + t * 16, make_uint4(0, 0, 0, 0));
            stg_rlx64(X + blk(X_M1, cta >> 5, lane >> 4) + (cta & 31) * 128 + (lane & 15) * 8, 0, 0);
            const int wt = (cta & 3) * 32 + lane;
            const unsigned mask = __ballot_sync(~0u, blk(X_PART, wt, ldg_rlx32(X + X_SIDE + (RM ? DN0 + (wt >> 2) : wt) * 4)) & 4096);
            if (lane == 0) sts32u(sb + SM_MASK, mask);
            if (RM ? cta >= DN0 : lane < 8) {
                const int task = RM ? (cta - DN0) * 4 + (lane >> 3) : cta;
                const int rb = task >> 4, c = ((task & 15) >> 1) * 64 + (task & 1) * 4 + ((lane & 7) >> 1) + (lane & 1) * 8;
                const uint2 ga = ldg_rlx64(X + X_MOD + rowoff(rb, c));
                const unsigned short* const xp = (const unsigned short*)px + rb * DM + c;
                sts128(scr + (lane >> 3) * SCR + SC_RX + (lane & 7) * 16, make_uint4(ga.x, ga.y, xp[0] | (xp[16] << 16), xp[32] | (xp[48] << 16)));
            }
            if (cta < NF1) {
#pragma unroll 1
                for (int i = 0; i < 4; i++) {
                    uint4 v[8];
#pragma unroll
                    for (int j = 0; j < 8; j++) v[j] = ldg_rlx128(X + X_MOD + 8192 + (i * 8 + j) * 512 + lane * 16);
#pragma unroll
                    for (int j = 0; j < 8; j++) sts128(sb + SM_MN + (i * 8 + j) * 512 + lane * 16, v[j]);
                }
            }
        }
        CKA(10);
        bar_arrive<B_RDY, NALL>();
        if (lane == 0) {
            auto until = [&](int x) { while ((int)(now_ns() - lds32u(sb + SM_AN) - 256 * TAU) < x) nap(20); };
            auto freed = [&](int i) { int n = 0; while (lds32u(sb + SM_BAR + i * 64 + 56) < 30) { nap(100); if (++n > SPIN_MAX) __trap(); } };
#pragma unroll 1
            for (int i = 0; i < 8; i++) freed(i);
            if (cta < NF1) {
#pragma unroll
                for (int i = 0; i < WP; i++) mbar_expect(sb + SM_BAR + i * 64 + 48, XA_ ? 0 : 8 / WP * UNIT);
#pragma unroll 1
                for (int i = 0; i < (XA_ ? 0 : WP); i++) {
                    const uint32_t b = sb + SM_BAR + i * 64 + 48;
                    until(W0 + i * WS);
                    tma5d(sb + 2 * REG + i * (16384 / WP), &P.wg, cta * 16, i * (16 / WP), b); tma5d(sb + 2 * REG + 16384 + i * (16384 / WP), &P.wu, cta * 16, i * (16 / WP), b);
                    CKP(i);
                }
            }
            until(PF2);
            pf_bulk(P.wdp + cta * (DM * FF / NCTA), DM * FF / NCTA * 2);
            CKP(9); CKN(8, lds32u(sb + SM_AN) + 256 * TAU);
        }
        if (cta >= DN0) {
            bar_sync<B_LAST, NTHR>();
            if (lane == 0) {
                auto until = [&](int x) { while ((int)(now_ns() - lds32u(sb + SM_AN) - 256 * TAU) < x) nap(20); };
                mbar_expect(sb + SM_BN, 16384);
                until(MOD_T2);
                tma2d(sb + 4 * REG - 16384, &P.wn, 2 * DM + cta * 16, 0, sb + SM_BN); tma2d(sb + 4 * REG - 8192, &P.wn, 2 * DM + cta * 16, 256, sb + SM_BN);
                CKP(12);
                mbar_expect(sb + SM_BT, 8 * 5632);
                until(FFN_T2);
#pragma unroll 1
                for (int i = 0; i < 8; i++) tma5d(sb + 2 * REG + i * 5632, &P.wd, (cta - DN0) * 16, i * 11, sb + SM_BT);
                CKP(13);
            }
        }
        __syncwarp();
        if (cta < NF1) ffn_terms();
        if (cta >= DN0) {
            mbar_wait(sb + SM_BN, 0);
            CKP(0);
            late_mod(sb + 4 * REG - 16384, 0); late_mod(sb + 4 * REG - 8192, 1);
#pragma unroll
            for (int e = 0; e < 2; e++)
                sts32u(sb + SM_MN + g * 32 + e * 16 + t * 4, movm(pack2((m[0][2 * e] + m[1][2 * e]) + (m[2][2 * e] + m[3][2 * e]), (m[0][2 * e + 1] + m[1][2 * e + 1]) + (m[2][2 * e + 1] + m[3][2 * e + 1]))));
            bar_arrive<B_DN, NTHR>();
            CKP(1);
        }
        return;
    }
    uint4 ca, cb, xa, xb, xc, xd;
    {
        const int e = ((lane >> 3) * DM + w * 64) / 8 + (lane & 7);
        ca = __ldg((const uint4*)pc + e); cb = __ldg((const uint4*)pc + e + 4 * DM / 8);
        xa = __ldg((const uint4*)px + w * DM / 8 + lane); xb = __ldg((const uint4*)px + w * DM / 8 + 32 + lane);
        xc = __ldg((const uint4*)px + e); xd = __ldg((const uint4*)px + e + 4 * DM / 8);
    }
    if (w >= 4) pf_map(&P.wm + (w & 3));
    char* const qout = X + blk(X_Q, head >> 1, tid >> 7) + (head & 1) * 2048 + ((tid >> 4) & 7) * 256 + (cta & 3) * 64 + (tid & 3) * 16 + ((tid >> 2) & 3) * 4;
    char* const mout = X + blk(X_M1, cta >> 5, w) + (cta & 31) * 128 + lane * 4;
    stg_rlx32(qout, 0);
    if (w < 2) stg_rlx32(mout, 0);
    uint32_t sc[8], xf[8];
    {
        const uint32_t a = (lane >> 3) * 128 + (((lane & 7) ^ (lane >> 3)) << 4), b = (lane & 7) * 128 + (((lane >> 3) ^ (lane & 7)) << 4);
        const uint32_t cs = sb + SM_SC + w * 1024;
        sts128(cs + a, make_uint4(silu2(ca.x), silu2(ca.y), silu2(ca.z), silu2(ca.w)));
        sts128(cs + 512 + (a ^ 64), make_uint4(silu2(cb.x), silu2(cb.y), silu2(cb.z), silu2(cb.w)));
        sts128(myscr + a, xc); sts128(myscr + 512 + (a ^ 64), xd);
        __syncwarp();
        ldsm(*(uint32_t(*)[4])&sc[0], cs + b); ldsm(*(uint32_t(*)[4])&sc[4], cs + (b ^ 64));
        ldsm(*(uint32_t(*)[4])&xf[0], myscr + b); ldsm(*(uint32_t(*)[4])&xf[4], myscr + (b ^ 64));
        __syncwarp();
    }
    CKA(0);
    {
        float v[16] = {blo(xa.x), bhi(xa.x), blo(xa.y), bhi(xa.y), blo(xa.z), bhi(xa.z), blo(xa.w), bhi(xa.w),
                       blo(xb.x), bhi(xb.x), blo(xb.y), bhi(xb.y), blo(xb.z), bhi(xb.z), blo(xb.w), bhi(xb.w)};
        float s = 0;
#pragma unroll
        for (int i = 0; i < 16; i++) s += v[i];
#pragma unroll
        for (int o = 16; o; o >>= 1) s += __shfl_xor_sync(~0u, s, o);
        s *= (1.0f / DM);
        float q2 = 0;
#pragma unroll
        for (int i = 0; i < 16; i++) q2 += (v[i] - s) * (v[i] - s);
#pragma unroll
        for (int o = 16; o; o >>= 1) q2 += __shfl_xor_sync(~0u, q2, o);
        uint32_t mu2; float rs; ln_consts(s, q2 * (1.0f / DM), mu2, rs);
        if (lane == 0) sts64(sb + SM_ST + w * 8, __uint_as_float(mu2), rs);
    }
    const int lrow = (lane & 7) + ((lane >> 4) << 3), lch = (lane >> 3) & 1;
    const uint32_t off64 = lrow * 64 + ((lch ^ ((lrow >> 1) & 3)) << 4);
    const uint32_t off128 = lrow * 128 + ((lch ^ (lane & 7)) << 4);
    bar_sync<B_INIT, NTHR>();
    mbar_wait(sb + SM_BM, 0);
    CKA(1);
    {
        float a[4] = {0, 0, 0, 0}, b[4] = {0, 0, 0, 0};
        uint32_t r[4], u[4];
        ldsm_t(r, sb + 4 * REG + (w * 64 + lane) * 16); ldsm_t(u, sb + 4 * REG + (w * 64 + 32 + lane) * 16);
        mma(a, sc[0], 0, sc[1], 0, r[0], r[1]); mma(b, sc[4], 0, sc[5], 0, u[0], u[1]);
        mma(a, sc[2], 0, sc[3], 0, r[2], r[3]); mma(b, sc[6], 0, sc[7], 0, u[2], u[3]);
        sts64(myscr + SC_M + lane * 8, a[0] + b[0], a[1] + b[1]);
    }
    bar_arrive<B_MOD, NTHR>();
    bar_sync<B_ALL, 256>();
    if (w < 2) {
        const float2 m = sum8(scr + SC_M + lane * 8);
        stg_rlx32(mout, ~pack2(m.x, m.y));
    }
    CKA(2);
    if (tid < 8 * XC) stg_rlx128(X + X_X1 + (cta * 8 * XC + tid) * 16, make_uint4(SENT, SENT, SENT, SENT));
    else if (tid >= 232) stg_rlx128(X + X_HM + (cta * 24 + tid - 232) * 16, make_uint4(SENT, SENT, SENT, SENT));
    {
        const float2 st = lds64(sb + SM_ST + g * 8);
#pragma unroll
        for (int i = 0; i < 8; i++) xf[i] = ln_norm(xf[i], __float_as_uint(st.x), st.y);
    }
    {
        unsigned sv[8], cv[8]; int n = 0;
        bar_sync<B_SIDE, NTHR>();
        const char* const mp = X + blk(X_M1, w >> 2, lds32u(sb + SM_SIDE)) + (w & 3) * 1024 + lane * 4;
        if (lane == 0) while (!ldg_rlx32(mp + 16384 + 7 * 128)) { nap(40); if (++n > SPIN_MAX) __trap(); }
        __syncwarp();
        CKA(3);
#pragma unroll
        for (int j = 0; j < 8; j++) { sv[j] = ldg_rlx32(mp + j * 128); cv[j] = ldg_rlx32(mp + 16384 + j * 128); }
        while (true) {
            unsigned m = ~0u;
#pragma unroll
            for (int j = 0; j < 8; j++) m = min(m, min(sv[j], cv[j]));
            if (__all_sync(~0u, m)) break;
#pragma unroll
            for (int j = 0; j < 8; j++) { if (!sv[j]) sv[j] = ldg_rlx32(mp + j * 128); if (!cv[j]) cv[j] = ldg_rlx32(mp + 16384 + j * 128); }
            if (++n > SPIN_MAX) __trap();
        }
        CKA(4);
#pragma unroll
        for (int j = 0; j < 8; j++) xf[j] = add2(mul2(xf[j], add2(~cv[j], ONE2)), ~sv[j]);
        mbar_wait(bar0 + 48, 0);
        CKA(5);
        float acc[4][4] = {};
#pragma unroll
        for (int j = 0; j < 4; j++) {
            uint32_t r[4], u[4];
            ldsm_t(r, s2 + REG + j * 1024 + off64); ldsm_t(u, s2 + REG + j * 1024 + (off64 ^ 32));
            mma(acc[0], xf[2 * j], 0, xf[2 * j + 1], 0, r[0], r[2]); mma(acc[1], xf[2 * j], 0, xf[2 * j + 1], 0, r[1], r[3]);
            mma(acc[2], xf[2 * j], 0, xf[2 * j + 1], 0, u[0], u[2]); mma(acc[3], xf[2 * j], 0, xf[2 * j + 1], 0, u[1], u[3]);
        }
#pragma unroll
        for (int n2 = 0; n2 < 4; n2++) sts64(myscr + SC_Q + g * 160 + n2 * 32 + t * 8, acc[n2][0], acc[n2][1]);
    }
    bar_arrive<B_WQ, NTHR>();
    bar_sync<B_ALL, 256>();
    {
        const float2 s = sum8(scr + SC_Q + ((tid >> 4) & 7) * 160 + (tid & 15) * 8);
        stg_rlx32(qout, ~pack2(s.x, s.y));
    }
    CKA(6);
    uint32_t q[16];
    {
        int n = 0;
        const char* const qp = X + blk(X_Q, head >> 1, lds32u(sb + SM_SIDE)) + (head & 1) * 2048 + bat * 256 + t * 16;
        uint4 v[4];
#pragma unroll
        for (int j = 0; j < 4; j++) v[j] = ldg_rlx128(qp + j * 64);
        while (true) {
            bool bad[4];
#pragma unroll
            for (int j = 0; j < 4; j++) bad[j] = !min(min(v[j].x, v[j].y), min(v[j].z, v[j].w));
            if (!__any_sync(~0u, bad[0] | bad[1] | bad[2] | bad[3])) break;
#pragma unroll
            for (int j = 0; j < 4; j++) if (bad[j]) v[j] = ldg_rlx128(qp + j * 64);
            if (++n > SPIN_MAX) __trap();
        }
#pragma unroll
        for (int j = 0; j < 4; j++) { q[4 * j] = ~v[j].x; q[4 * j + 1] = ~v[j].y; q[4 * j + 2] = ~v[j].z; q[4 * j + 3] = ~v[j].w; }
    }
    bar_arrive<B_Q, NTHR>();
    CKA(7);

    float o[2][4] = {};
    float mrun = -3.0e38f, lrun = 0.f;
    uint32_t wa[16][4], pb[2];
#pragma unroll
    for (int i = 0; i < 16; i++) wa[i][0] = wa[i][1] = wa[i][2] = wa[i][3] = 0;
    constexpr float LOG2E = 1.4426950408889634f, SCALE = 0.08838834764831845f;
    const uint32_t offk = (lane & 15) * 128 + (((lane >> 4) ^ (lane & 7)) << 4);
    auto scores = [&](uint32_t a0) {
        uint32_t kf[8][4];
#pragma unroll
        for (int j = 0; j < 8; j++) ldsm(kf[j], ((a0 + offk) ^ ((j & 3) << 5)) + (j >> 2) * 2048);
        float sa[4] = {0, 0, 0, 0}, sb2[4] = {0, 0, 0, 0};
#pragma unroll
        for (int j = 0; j < 8; j += 2) { mma(sa, kf[j], q[2 * j], q[2 * j + 1]); mma(sb2, kf[j + 1], q[2 * j + 2], q[2 * j + 3]); }
        uint32_t u = pack2(sa[0] + sb2[0], sa[2] + sb2[2]);
        u = pack2(blo(u) * SCALE, bhi(u) * SCALE);
        const float z0 = blo(u), z1 = bhi(u);
        float mx = fmaxf(z0, z1);
        mx = fmaxf(mx, __shfl_xor_sync(~0u, mx, 4)); mx = fmaxf(mx, __shfl_xor_sync(~0u, mx, 8)); mx = fmaxf(mx, __shfl_xor_sync(~0u, mx, 16));
        mx = fmaxf(mx, mrun);
        const float f = ex2((mrun - mx) * LOG2E), p0 = ex2((z0 - mx) * LOG2E), p1 = ex2((z1 - mx) * LOG2E);
        mrun = mx; lrun = lrun * f + (p0 + p1);
#pragma unroll
        for (int j = 0; j < 4; j++) { o[0][j] *= f; o[1][j] *= f; }
        pb[0] = movm(pack2(p0, p0)); pb[1] = movm(pack2(p1, p1));
    };
    const int kvrow = (bat * NH + head) * SK + (SK - WIN) + (w & 3) * 16;
    auto request = [&](int u) {
        sts32u(bar0 + 56, u - 1);
        while ((int)(now_ns() - lds32u(sb + SM_AN) - (u * 8 + w) * TAU) < 0) nap(20);
        const int sl = (~u & 2) + (u & 1);
        mbar_expect(bar0 + sl * 8, UNIT); tma_kv(s0 + sl * REG, &P.k + (u & 1), kvrow + (u >> 1) * 64, bar0 + sl * 8, pol);
    };
#pragma unroll 1
    for (int it = 0; it < NT - 1; it++) {
        const int si = it < 3 ? it : (it + 1) & 1;
        const uint32_t bar = bar0 + si * 16, a0 = s0 + si * 2 * REG;
        const uint32_t par = it < 3 ? 0 : ((it - 1) >> 1) & 1;
        const bool refill = lane == 0 && it >= 2;
        mbar_wait(bar, par);
        if (refill) {
            request(2 * it + 2);
            const int e = it - (it > WOA_READ ? WOA_READ + 1 : WOA_ISSUE);
            if (e == 0) mbar_expect(barC, 2 * UNIT);
            if (e == 0 || e == WO_GAP) tma2d(s2 + (e ? REG : 0), &P.wo, w * 64, head * 128 + (it > WOA_READ ? 64 : 0) + (e ? 32 : 0), barC);
        }
        __syncwarp();
        if (it == WOA_READ) {
            mbar_wait(barC, 1);
#pragma unroll
            for (int j = 0; j < 16; j++) ldsm_t(wa[j], s2 + (j >> 3) * REG + ((j >> 2) & 1) * 2048 + (off128 ^ ((j & 3) << 5)));
        }
        scores(a0);
        mbar_wait(bar + 8, par);
        if (refill) request(2 * it + 3);
        __syncwarp();
        uint32_t vf[8][4];
#pragma unroll
        for (int j = 0; j < 8; j++) ldsm_t(vf[j], ((a0 + off128) ^ ((j & 3) << 5)) + (j >> 2) * 2048 + REG);
#pragma unroll
        for (int j = 0; j < 8; j++) { const bool on = (g >> 1) == (j >> 1); mma(o[j & 1], vf[j], on ? pb[0] : 0, on ? pb[1] : 0); }
    }
    uint32_t wb[16][4];
    auto load_wb = [&](int j) { ldsm_t(wb[j], s2 + (j >> 3) * REG + ((j >> 2) & 1) * 2048 + (off128 ^ ((j & 3) << 5))); };
    {
        mbar_wait(bar0, 1);
        CKA(13);
        CKN(8, lds32u(sb + SM_AN) + 256 * TAU);
        if (cta >= DN0) bar_arrive<B_LAST, NTHR>();
        scores(s0);
        lrun += __shfl_xor_sync(~0u, lrun, 4); lrun += __shfl_xor_sync(~0u, lrun, 8); lrun += __shfl_xor_sync(~0u, lrun, 16);
        if (lane == 0) sts64(sb + SM_ML + w * 8, mrun, lrun);
        mbar_wait(barC, 0);
#pragma unroll
        for (int j = 0; j < NPRE; j++) load_wb(j);
        uint32_t pm[4][2];
#pragma unroll
        for (int j = 0; j < 4; j++) { pm[j][0] = (g >> 1) == j ? pb[0] : 0; pm[j][1] = (g >> 1) == j ? pb[1] : 0; }
        uint32_t va = s0 + REG + off128, ho = s0 + w * 16 + ((lane & 7) >> 1) * 64 + ((lane >> 3) & 1) * 32 + (lane & 1) * 16;
        asm volatile("" : "+r"(va), "+r"(ho), "+r"(pm[0][0]), "+r"(pm[0][1]), "+r"(pm[1][0]), "+r"(pm[1][1]), "+r"(pm[2][0]), "+r"(pm[2][1]), "+r"(pm[3][0]), "+r"(pm[3][1]));
        mbar_wait(bar0 + 8, 1);
        CKP(0);
        uint32_t vf[8][4];
        float o2[2][4] = {};
#pragma unroll
        for (int j = 0; j < 8; j++) ldsm_t(vf[j], (va ^ ((j & 3) << 5)) + (j >> 2) * 2048);
#pragma unroll
        for (int j = 0; j < 8; j++) mma((j & 2) ? o2[j & 1] : o[j & 1], vf[j], pm[j >> 1][0], pm[j >> 1][1]);
        asm volatile("stmatrix.sync.aligned.m8n8.x2.trans.shared.b16 [%0], {%1,%2};" :: "r"(ho), "r"(pack2(o[0][0] + o2[0][0], o[0][2] + o2[0][2])), "r"(pack2(o[1][0] + o2[1][0], o[1][2] + o2[1][2])) : "memory");
    }
    if (!WLATE)
#pragma unroll
        for (int j = NPRE; j < 16; j++) load_wb(j);
    CKP(1);
    bar_sync<B_RDY, NALL>();
    {
        float y[4][4] = {};
        uint32_t ob[4][4];
#pragma unroll
        for (int i2 = 0; i2 < 4; i2++) ldsm(ob[i2], sb + (lane & 7) * (UNIT + 16) + (i2 * 4 + (lane >> 3)) * 16);
        if (WLATE)
#pragma unroll
            for (int j = NPRE; j < 16; j++) load_wb(j);
        const float4 a = lds128(sb + SM_ML + (t >> 1) * 32), b = lds128(sb + SM_ML + (t >> 1) * 32 + 16);
        const int rd = (t >> 1) * 16 + w * 2 + (g >> 2);
        char* const pp = X + X_PART + ((cta & 3) * 32 + rd) * 8192 + ((lds32u(sb + SM_MASK) >> rd) & 1) * 4096 + head * 128 + (g & 3) * 32 + (t & 1) * 16;
#pragma unroll
        for (int j = 0; j < 8; j++)
#pragma unroll
            for (int i = 0; i < 4; i++) mma(y[i], j < 4 ? wa[j * 4 + i] : wb[(j - 4) * 4 + i], ob[j >> 1][2 * (j & 1)], ob[j >> 1][2 * (j & 1) + 1]);
        const float M = fmaxf(fmaxf(a.x, a.z), fmaxf(b.x, b.z));
        const float e0 = ex2((a.x - M) * LOG2E), e1 = ex2((a.z - M) * LOG2E), e2 = ex2((b.x - M) * LOG2E), e3 = ex2((b.z - M) * LOG2E);
        const float rL = rcp((e0 * a.y + e1 * a.w) + (e2 * b.y + e3 * b.w));
        const float f0 = ((t & 1) ? e2 : e0) * rL, f1 = ((t & 1) ? e3 : e1) * rL;
        uint32_t r[4];
#pragma unroll
        for (int i = 0; i < 4; i++) {
            const float lo = f0 * y[i][0] + f1 * y[i][1], hi = f0 * y[i][2] + f1 * y[i][3];
            r[i] = __float_as_uint(((t & 1) ? hi : lo) + __shfl_xor_sync(~0u, (t & 1) ? lo : hi, 1));
        }
        stg_b128(pp, make_uint4(min(r[0], SENT - 1), r[1], r[2], r[3]));
    }
    const unsigned c_st = clock();
    CKP(3);
    const unsigned side = lds32u(sb + SM_SIDE);
    const char* const x1p = X + (cta & (XC - 1)) * 16384;
    if (cta < NF1) {
        uint32_t wg[4][4], wu[4][4];
        const char* const xp = x1p + blk(X_X1, w >> 2, side) + (w & 3) * 1024 + lane * 16;
        float4 c1[2], sv[2];
#pragma unroll
        for (int h = 0; h < 2; h++) { sv[h] = lds128(sb + SM_MN + (w * 2 + h) * 512 + lane * 16); c1[h] = lds128(sb + SM_MN + 8192 + (w * 2 + h) * 512 + lane * 16); }
        mbar_wait(sb + SM_BAR + (w * WP >> 3) * 64 + 48, 1);
        CKP(13);
#pragma unroll
        for (int j = 0; j < 4; j++) {
            const uint32_t a = sb + 2 * REG + w * 2048 + (((lane & 7) >> 1) + (lane & 1) * 4 + j * 8 + (lane >> 4) * 32) * 32 + ((lch ^ (lane & 1)) << 4);
            ldsm_t(wg[j], a); ldsm_t(wu[j], a + 16384);
        }
        {
            float cg[4] = {}, cu[4] = {}, sg[4] = {}, su[4] = {};
#pragma unroll
            for (int j = 0; j < 4; j++) {
                const float4 a = c1[j & 1], b = sv[j & 1];
                const uint32_t a0 = __float_as_uint(j >> 1 ? a.z : a.x), a1 = __float_as_uint(j >> 1 ? a.w : a.y), b0 = __float_as_uint(j >> 1 ? b.z : b.x), b1 = __float_as_uint(j >> 1 ? b.w : b.y);
                mma(cg, wg[j], a0, a1); mma(cu, wu[j], a0, a1); mma(sg, wg[j], b0, b1); mma(su, wu[j], b0, b1);
            }
            const uint32_t d = s0 + REG + g * 144 + t * 32;
            sts128f(d, cg[0], cg[2], cu[0], cu[2]); sts128f(d + 16, cg[1], cg[3], cu[1], cu[3]);
            sts128f(d + 1152, sg[0], sg[2], su[0], su[2]); sts128f(d + 1168, sg[1], sg[3], su[1], su[3]);
            bar_arrive<B_PRE, NALL>();
        }
        char* ho = X + blk(X_HM, cta >> 4, (tid >> 6) & 1) + ((cta >> 1) & 7) * 512 + ((tid >> 3) & 7) * 64 + (tid & 3) * 16 + (cta & 1) * 8 + ((tid >> 2) & 1) * 4;
        asm volatile("" : "+l"(ho));
        CKP(2);
        bar_sync<B_GO, NTHR>();
        int n = 0;
        uint4 x0 = ldg_rlx2x64(xp), x1 = ldg_rlx2x64(xp + 512);
        CKP(6);
        while (true) {
            const bool b0 = max(x0.x, x0.z) == SENT, b1 = max(x1.x, x1.z) == SENT;
            if (b0) x0 = ldg_rlx2x64(xp);
            if (b1) x1 = ldg_rlx2x64(xp + 512);
            if (!__any_sync(~0u, b0 | b1)) break;
            if (++n > SPIN_MAX) __trap();
        }
        CKP(7); CKN(11, n + 1);
        {
            float sm[4] = {}, q0[4] = {}, q1[4] = {}, ag[2][4] = {}, au[2][4] = {};
#pragma unroll
            for (int j = 0; j < 4; j++) {
                const uint4 xv = (j & 1) ? x1 : x0; const float4 a = c1[j & 1];
                const uint32_t h0 = mul2(j >> 1 ? xv.z : xv.x, __float_as_uint(j >> 1 ? a.z : a.x)), h1 = mul2(j >> 1 ? xv.w : xv.y, __float_as_uint(j >> 1 ? a.w : a.y));
                mma(ag[j & 1], wg[j], h0, h1); mma(au[j & 1], wu[j], h0, h1);
            }
            mma(sm, x0.x, x0.y, x0.z, x0.w, ONE2, ONE2); mma(sm, x1.x, x1.y, x1.z, x1.w, ONE2, ONE2);
            mma(q0, x0.x, x0.z, x0.y, x0.w, x0.x, x0.y); mma(q1, x0.x, x0.z, x0.y, x0.w, x0.z, x0.w);
            mma(q0, x1.x, x1.z, x1.y, x1.w, x1.x, x1.y); mma(q1, x1.x, x1.z, x1.y, x1.w, x1.z, x1.w);
            const uint32_t d = myscr + SC_F1 + g * 144 + t * 32;
            sts128f(d, ag[0][0] + ag[1][0], ag[0][2] + ag[1][2], au[0][0] + au[1][0], au[0][2] + au[1][2]);
            sts128f(d + 16, ag[0][1] + ag[1][1], ag[0][3] + ag[1][3], au[0][1] + au[1][1], au[0][3] + au[1][3]);
            if (t == (g >> 1)) sts64(sb + SM_ST + g * 64 + w * 8, sm[0] + sm[2], (g & 1) ? q0[1] + q1[3] : q0[0] + q1[2]);
        }
        CKP(12);
        bar_sync<B_FIN, NALL>();
        if (tid < 128) {
            const int b = (tid >> 3) & 7, c = tid & 7;
            const float4 s0_ = lds128(sb + SM_ST + b * 64), s1_ = lds128(sb + SM_ST + b * 64 + 16), s2_ = lds128(sb + SM_ST + b * 64 + 32), s3_ = lds128(sb + SM_ST + b * 64 + 48);
            const float4 p = sum8x4<SCR>(scr + SC_F1 + c * 144 + b * 16), C = lds128(sb + SM_MN + (tid & 63) * 16), S = lds128(sb + SM_MN + 1024 + (tid & 63) * 16);
            const float mean = (((s0_.x + s0_.z) + (s1_.x + s1_.z)) + ((s2_.x + s2_.z) + (s3_.x + s3_.z))) * (1.0f / DM);
            const float sq = (((s0_.y + s0_.w) + (s1_.y + s1_.w)) + ((s2_.y + s2_.w) + (s3_.y + s3_.w))) * (1.0f / DM);
            uint32_t mu2; float rs;
            ln_consts(mean, fmaxf(sq - mean * mean, 0.f), mu2, rs);
            const float mu = blo(mu2);
            const float g0 = rs * (p.x - mu * C.x) + S.x, g1 = rs * (p.y - mu * C.y) + S.y, u0 = rs * (p.z - mu * C.z) + S.z, u1 = rs * (p.w - mu * C.w) + S.w;
            stg_rlx32(ho, pack2(rbf(sigmoid_f(rbf(g0))) * rbf(u0), rbf(sigmoid_f(rbf(g1))) * rbf(u1)));
        }
        CKP(9);
    } else if (cta >= DN0) {
        const int f = cta - DN0;
        uint32_t wd[12][4];
        const char* const hp = X + w * 512 + lane * 16;
        const char* const rp = x1p + blk(X_X1, f >> 4, side) + (rowoff(tid >> 3, f * 16 + (tid & 7) * 2) & 4092);
        unsigned* op = (unsigned*)P.out + (tid >> 3) * 256 + f * 8 + (tid & 7);
        asm volatile("" : "+l"(op));
        mbar_wait(sb + SM_BT, 0);
        CKP(13);
#pragma unroll
        for (int j = 0; j < 12; j++)
            if (j < 10 || w < 3) ldsm_t(wd[j], sb + 2 * REG + (w + (j >> 1) * 8) * 1024 + (j & 1) * 512 + (((lane & 7) >> 1) + (lane & 1) * 4 + (lane >> 4) * 8) * 32 + ((lch ^ (lane & 1)) << 4));
            else wd[j][0] = wd[j][1] = wd[j][2] = wd[j][3] = 0;
        CKP(2);
        bar_sync<B_GO, NTHR>();
        if (HDW) spin(clock() - lds32u(sb + SM_SIDE), w * HDW);
        uint4 hv[6]; int n = 0;
#pragma unroll
        for (int j = 0; j < 6; j++) hv[j] = (j < 5 || w < 3) ? ldg_rlx128(hp + blk(X_HM, j, side)) : make_uint4(0, 0, 0, 0);
        unsigned ra = 0, rb = 0;
        if (tid < 64) { ra = ldg_rlx32(rp); rb = ldg_rlx32(rp + 16); }
        CKP(6);
        while (true) {
            bool any = max(ra, rb) == SENT;
            if (any) { ra = ldg_rlx32(rp); rb = ldg_rlx32(rp + 16); }
#pragma unroll
            for (int j = 0; j < 6; j++) { const bool bad = !valid4(hv[j]); any |= bad; if (bad) hv[j] = ldg_rlx128(hp + blk(X_HM, j, side)); }
            if (!__any_sync(~0u, any)) break;
            if (++n > SPIN_MAX) __trap();
        }
        CKP(7); CKN(11, n + 1);
        float d[4][4] = {};
#pragma unroll
        for (int j = 0; j < 6; j++) { mma(d[(2 * j) & 3], wd[2 * j], hv[j].x, hv[j].y); mma(d[(2 * j + 1) & 3], wd[2 * j + 1], hv[j].z, hv[j].w); }
#pragma unroll
        for (int e = 0; e < 4; e++) sts32(myscr + SC_DN + (2 * t + (e & 1)) * 80 + (g + (e >> 1) * 8) * 4, (d[0][e] + d[1][e]) + (d[2][e] + d[3][e]));
        CKP(12);
        bar_sync<B_DN, NTHR>();
        if (tid < 64) {
            const unsigned gw = lds32u(sb + SM_MN + tid * 4);
            const float2 s = sum8(scr + SC_DN + (tid >> 3) * 80 + (tid & 7) * 8);
            *op = add2(__byte_perm(ra, rb, (f & 1) ? 0x7632 : 0x5410), mul2(gw, pack2(s.x, s.y)));
        }
        CKP(9);
    }
    CKEND;
}

typedef CUresult (*EncodeFn)(CUtensorMap*, CUtensorMapDataType, cuuint32_t, void*, const cuuint64_t*, const cuuint64_t*, const cuuint32_t*,
                             const cuuint32_t*, CUtensorMapInterleave, CUtensorMapSwizzle, CUtensorMapL2promotion, CUtensorMapFloatOOBfill);

void make2d(EncodeFn enc, CUtensorMap* m, const void* p, int rows, int cols, int brows, int bcols, CUtensorMapSwizzle sw) {
    cuuint64_t dims[2] = {(cuuint64_t)cols, (cuuint64_t)rows}, strides[1] = {(cuuint64_t)cols * 2};
    cuuint32_t box[2] = {(cuuint32_t)bcols, (cuuint32_t)brows}, es[2] = {1, 1};
    enc(m, CU_TENSOR_MAP_DATA_TYPE_BFLOAT16, 2, (void*)p, dims, strides, box, es, CU_TENSOR_MAP_INTERLEAVE_NONE, sw,
        CU_TENSOR_MAP_L2_PROMOTION_L2_128B, CU_TENSOR_MAP_FLOAT_OOB_FILL_NONE);
}
void make5d(EncodeFn enc, CUtensorMap* m, const void* p, int rows, int cols, int d, int nb) {
    const cuuint64_t rs = (cuuint64_t)cols * 2;
    cuuint64_t dims[5] = {(cuuint64_t)cols, 4, 2, (cuuint64_t)d / 4, (cuuint64_t)rows / (2 * d)}, strides[4] = {rs, rs * d, rs * 4, rs * 2 * d};
    cuuint32_t box[5] = {16, 4, 2, (cuuint32_t)d / 4, (cuuint32_t)nb}, es[5] = {1, 1, 1, 1, 1};
    enc(m, CU_TENSOR_MAP_DATA_TYPE_BFLOAT16, 5, (void*)p, dims, strides, box, es, CU_TENSOR_MAP_INTERLEAVE_NONE, CU_TENSOR_MAP_SWIZZLE_32B,
        CU_TENSOR_MAP_L2_PROMOTION_L2_128B, CU_TENSOR_MAP_FLOAT_OOB_FILL_NONE);
}
void makekv(EncodeFn enc, CUtensorMap* m, const void* p) {
    cuuint64_t dims[3] = {64, (cuuint64_t)NB * NH * SK, 2}, strides[2] = {256, 128};
    cuuint32_t box[3] = {64, 16, 2}, es[3] = {1, 1, 1};
    enc(m, CU_TENSOR_MAP_DATA_TYPE_BFLOAT16, 3, (void*)p, dims, strides, box, es, CU_TENSOR_MAP_INTERLEAVE_NONE, CU_TENSOR_MAP_SWIZZLE_128B,
        CU_TENSOR_MAP_L2_PROMOTION_NONE, CU_TENSOR_MAP_FLOAT_OOB_FILL_NONE);
}

}

extern "C" void kernel_launch(void* const* d_in, const int* in_sizes, int n_in, void* d_out, int out_size) {
    (void)in_sizes; (void)n_in; (void)out_size;
    static EncodeFn enc = nullptr;
    static void* raw = nullptr;
    if (!enc) {
        void* fn = nullptr; cudaDriverEntryPointQueryResult qr;
        cudaGetDriverEntryPoint("cuTensorMapEncodeTiled", &fn, cudaEnableDefault, &qr);
        enc = (EncodeFn)fn;
        cudaFuncSetAttribute(fused_kernel, cudaFuncAttributeMaxDynamicSharedMemorySize, SM_TOTAL);
        cudaGetSymbolAddress(&raw, g_raw);
    }
    Params P;
    makekv(enc, &P.k, d_in[1]);
    makekv(enc, &P.v, d_in[2]);
    make2d(enc, &P.wq, d_in[3], DM, NH * DH, 64, 32, CU_TENSOR_MAP_SWIZZLE_64B);
    make2d(enc, &P.wo, d_in[4], NH * DH, DM, 32, 64, CU_TENSOR_MAP_SWIZZLE_128B);
    make2d(enc, &P.wm, d_in[10], DM, 6 * DM, 256, 8, CU_TENSOR_MAP_SWIZZLE_NONE);
    make2d(enc, &P.wn, d_in[10], DM, 6 * DM, 256, 16, CU_TENSOR_MAP_SWIZZLE_32B);
    make5d(enc, &P.wg, d_in[6], DM, FF, 16, 16 / WP);
    make5d(enc, &P.wu, d_in[7], DM, FF, 16, 16 / WP);
    make5d(enc, &P.wd, d_in[8], FF, DM, 8, 11);
    P.out = (__nv_bfloat16*)d_out; P.wdp = (const __nv_bfloat16*)d_in[8];
    typedef const __nv_bfloat16* W;
    fused_kernel<<<NCTA, NALL, SM_TOTAL>>>((W)d_in[0], (W)d_in[9], (W)d_in[1], (W)d_in[10], (W)d_in[3], (char*)(((size_t)raw + X_ALIGN - 1) & ~(size_t)(X_ALIGN - 1)), P);
}
```

```cpp
#include <cuda_runtime.h>
#include <cuda_bf16.h>
#include <cuda.h>
#include <stdint.h>

namespace {

constexpr int NB = 8, DM = 512, NH = 32, DH = 128, SK = 4096, WIN = 1024, FF = 1376;
constexpr int NCTA = 128, NTHR = 288, NALL = 320;
constexpr int NT = 16;
constexpr int NF1 = 86, DN0 = 96;
constexpr unsigned SENT = 0xFFFFFFFFu;
constexpr int SPIN_MAX = 1 << 20;

#define PWIN0 12
#define PWIN 16
#define PSW 22
#define PNAP 30
#define NTRK 4
#define QN 6
#define TAU 169
#define ANCH0 250
#define LEAD 2100
#define PACE0 7000
#define PACE_NAP 300
#define WOA_ISSUE 3
#define WO_GAP 2
#define WOA_READ 8
#define MOD_T2 1800
#define XA_ 0
#define WP 4
#define RSPEC 1
#define FSPEC 0
#define DSPEC 0
#define GNAP 20
#define PFK 3
#define RMAP 1
#define XDW 30
#define HDW 30
#define RT0 1700
#define PRE_OUT 0
#define GREL 2
#define W0 900
#define WS 220
#define PF2 0
#define FFN_T2 1800
#define RD0 700
#define XD0 0
#define HD0 1000
#define XC 2
#define NPRE 9
#define WLATE 7
#define VSPIN 0

constexpr int UNIT = 4096, REG = 8 * UNIT;
constexpr int SM_SCR = 6 * REG;
constexpr int SCR = 2048;
constexpr int SM_MN = SM_SCR + 8 * SCR;
constexpr int SM_SC = SM_MN + 8192;
constexpr int SM_BAR = SM_SC + 8192;
constexpr int SM_BM = SM_BAR + 512, SM_BT = SM_BM + 8, SM_BN = SM_BM + 16, SM_BG = SM_BM + 24;
constexpr int SM_AN = SM_BM + 32, SM_SIDE = SM_BM + 36, SM_TAG = SM_BM + 40, SM_MASK = SM_BM + 44, SM_GO = SM_BM + 48;
constexpr int SM_ST = SM_BAR + 576;
constexpr int SM_ML = SM_ST + 512;
constexpr int SM_PR = SM_ML + 96;
constexpr int SM_CK = SM_PR + 512;
constexpr int SM_TOTAL = SM_CK + 800;
constexpr int SC_M = 0, SC_Q = 256;
constexpr int SC_F1 = 0, SC_DN = 0, SC_RX = 1536;
constexpr int B_INIT = 0, B_ALL = 2, B_MOD = 3, B_WQ = 4, B_LAST = 5, B_RDY = 6, B_DN = 7, B_PRE = 8, B_FIN = 9, B_GO = 10, B_SIDE = 11, B_Q = 12, B_ML = 13, B_CS = 14;

constexpr unsigned HOME = 0xB3000;
constexpr int X_PART = 0;
constexpr int X_Q = 0x100000;
constexpr int X_M1 = 0x140000;
constexpr int X_X1 = 0x150000;
constexpr int X_HM = 0x160000;
constexpr int X_MOD = 0x170000;
constexpr int X_SIDE = 0x176000;
constexpr int X_EPOCH = 0x176400;
constexpr int X_READY = 0x176480;
constexpr int X_LAG = 0x178000;
constexpr int X_PRB = 0x180000;
constexpr int X_ALIGN = 0x200000;
__device__ uint4 g_raw[2 * X_ALIGN / 16];
__device__ __forceinline__ unsigned blk(unsigned base, unsigned k, unsigned s) { const unsigned o = base + k * 8192; return o + ((__popc(o & HOME) ^ s) & 1) * 4096; }

#define CKDECL
#define CKEND
#define CKP(i)
#define CKN(i, v)
#define CKA(i)
struct Params {
    CUtensorMap wm, wq, k, v, wn, wo, wg, wu, wd;
    const __nv_bfloat16* wdp;
    __nv_bfloat16* out;
};

__device__ __forceinline__ uint32_t smem_u32(const void* p) { return (uint32_t)__cvta_generic_to_shared(p); }
__device__ __forceinline__ void mbar_init(uint32_t a, uint32_t c) { asm volatile("mbarrier.init.shared::cta.b64 [%0], %1;" :: "r"(a), "r"(c) : "memory"); }
__device__ __forceinline__ void mbar_expect(uint32_t a, uint32_t b) { asm volatile("mbarrier.arrive.expect_tx.shared::cta.b64 _, [%0], %1;" :: "r"(a), "r"(b) : "memory"); }
__device__ __forceinline__ void mbar_wait(uint32_t a, uint32_t par) {
    uint32_t ok; int n = 0;
    do {
        asm volatile("{\n.reg .pred p;\nmbarrier.try_wait.parity.shared::cta.b64 p, [%1], %2, 2000;\nselp.u32 %0, 1, 0, p;\n}" : "=r"(ok) : "r"(a), "r"(par) : "memory");
        if (++n > SPIN_MAX) __trap();
    } while (!ok);
}
__device__ __forceinline__ bool mbar_test(uint32_t a, uint32_t par) {
    uint32_t ok; asm volatile("{\n.reg .pred p;\nmbarrier.test_wait.parity.shared::cta.b64 p, [%1], %2;\nselp.u32 %0, 1, 0, p;\n}" : "=r"(ok) : "r"(a), "r"(par) : "memory"); return ok;
}
__device__ __forceinline__ void tma2d(uint32_t dst, const CUtensorMap* m, int x, int y, uint32_t bar) {
    asm volatile("cp.async.bulk.tensor.2d.shared::cluster.global.mbarrier::complete_tx::bytes [%0], [%1, {%3, %4}], [%2];"
                 :: "r"(dst), "l"(m), "r"(bar), "r"(x), "r"(y) : "memory");
}
__device__ __forceinline__ void tma5d(uint32_t dst, const CUtensorMap* m, int x, int y, uint32_t bar) {
    asm volatile("cp.async.bulk.tensor.5d.shared::cluster.global.mbarrier::complete_tx::bytes [%0], [%1, {%3, 0, 0, 0, %4}], [%2];"
                 :: "r"(dst), "l"(m), "r"(bar), "r"(x), "r"(y) : "memory");
}
__device__ __forceinline__ void tma_kv(uint32_t dst, const CUtensorMap* m, int row, uint32_t bar, uint64_t pol) {
    asm volatile("cp.async.bulk.tensor.3d.shared::cluster.global.mbarrier::complete_tx::bytes.L2::cache_hint [%0], [%1, {0, %3, 0}], [%2], %4;"
                 :: "r"(dst), "l"(m), "r"(bar), "r"(row), "l"(pol) : "memory");
}
__device__ __forceinline__ void pf_bulk(const void* p, uint32_t n) { asm volatile("cp.async.bulk.prefetch.L2.global [%0], %1;" :: "l"(p), "r"(n) : "memory"); }
__device__ __forceinline__ void pf_line(const void* p) { asm volatile("prefetch.global.L2 [%0];" :: "l"(p) : "memory"); }
__device__ __forceinline__ void pf_if(const void* p, unsigned i, unsigned n) { asm volatile("{\n.reg .pred p;\nsetp.lt.u32 p, %1, %2;\n@p prefetch.global.L2 [%0];\n}" :: "l"(p), "r"(i), "r"(n) : "memory"); }
__device__ __forceinline__ uint4 ldg_nc(const void* p) { uint4 v; asm volatile("ld.global.nc.v4.u32 {%0,%1,%2,%3}, [%4];" : "=r"(v.x), "=r"(v.y), "=r"(v.z), "=r"(v.w) : "l"(p)); return v; }
__device__ __forceinline__ bool elect() { uint32_t p; asm volatile("{\n.reg .pred p;\nelect.sync _|p, -1;\nselp.u32 %0, 1, 0, p;\n}" : "=r"(p)); return p; }
__device__ __forceinline__ void pf_map(const CUtensorMap* m) { asm volatile("prefetch.tensormap [%0];" :: "l"(m) : "memory"); }
__device__ __forceinline__ void ldsm(uint32_t (&r)[4], uint32_t a) {
    asm volatile("ldmatrix.sync.aligned.m8n8.x4.shared.b16 {%0,%1,%2,%3}, [%4];" : "=r"(r[0]), "=r"(r[1]), "=r"(r[2]), "=r"(r[3]) : "r"(a) : "memory");
}
__device__ __forceinline__ void ldsm_t(uint32_t (&r)[4], uint32_t a) {
    asm volatile("ldmatrix.sync.aligned.m8n8.x4.trans.shared.b16 {%0,%1,%2,%3}, [%4];" : "=r"(r[0]), "=r"(r[1]), "=r"(r[2]), "=r"(r[3]) : "r"(a) : "memory");
}
__device__ __forceinline__ void mma(float (&c)[4], uint32_t a0, uint32_t a1, uint32_t a2, uint32_t a3, uint32_t b0, uint32_t b1) {
    asm("mma.sync.aligned.m16n8k16.row.col.f32.bf16.bf16.f32 {%0,%1,%2,%3}, {%4,%5,%6,%7}, {%8,%9}, {%0,%1,%2,%3};"
        : "+f"(c[0]), "+f"(c[1]), "+f"(c[2]), "+f"(c[3]) : "r"(a0), "r"(a1), "r"(a2), "r"(a3), "r"(b0), "r"(b1));
}
__device__ __forceinline__ void mma(float (&c)[4], const uint32_t (&a)[4], uint32_t b0, uint32_t b1) { mma(c, a[0], a[1], a[2], a[3], b0, b1); }
__device__ __forceinline__ void mmav(float (&c)[4], const uint32_t (&a)[4], uint32_t b0, uint32_t b1) {
    asm volatile("mma.sync.aligned.m16n8k16.row.col.f32.bf16.bf16.f32 {%0,%1,%2,%3}, {%4,%5,%6,%7}, {%8,%9}, {%0,%1,%2,%3};"
        : "+f"(c[0]), "+f"(c[1]), "+f"(c[2]), "+f"(c[3]) : "r"(a[0]), "r"(a[1]), "r"(a[2]), "r"(a[3]), "r"(b0), "r"(b1));
}
__device__ __forceinline__ uint32_t pin(uint32_t v) { asm volatile("shfl.sync.bfly.b32 %0, %0, 0, 31, -1;" : "+r"(v)); return v; }
template <class T> __device__ __forceinline__ T* pin(T* p) { const size_t a = (size_t)p; return (T*)(pin((uint32_t)a) | (size_t)pin((uint32_t)(a >> 32)) << 32); }
__device__ __forceinline__ uint32_t movm(uint32_t a) { uint32_t r; asm volatile("movmatrix.sync.aligned.m8n8.trans.b16 %0, %1;" : "=r"(r) : "r"(a)); return r; }
__device__ __forceinline__ uint32_t pack2(float lo, float hi) { uint32_t r; asm("cvt.rn.bf16x2.f32 %0, %1, %2;" : "=r"(r) : "f"(hi), "f"(lo)); return r; }
__device__ __forceinline__ float blo(uint32_t w) { return __uint_as_float(w << 16); }
__device__ __forceinline__ float bhi(uint32_t w) { return __uint_as_float(w & 0xFFFF0000u); }
__device__ __forceinline__ float rbf(float x) { return blo(pack2(x, 0.f)); }
__device__ __forceinline__ uint32_t add2(uint32_t a, uint32_t b) { uint32_t r; asm("add.rn.bf16x2 %0, %1, %2;" : "=r"(r) : "r"(a), "r"(b)); return r; }
__device__ __forceinline__ uint32_t sub2(uint32_t a, uint32_t b) { uint32_t r; asm("sub.rn.bf16x2 %0, %1, %2;" : "=r"(r) : "r"(a), "r"(b)); return r; }
__device__ __forceinline__ uint32_t mul2(uint32_t a, uint32_t b) { uint32_t r; asm("mul.rn.bf16x2 %0, %1, %2;" : "=r"(r) : "r"(a), "r"(b)); return r; }
constexpr uint32_t ONE2 = 0x3F803F80u;
__device__ __forceinline__ float ex2(float x) { float y; asm("ex2.approx.ftz.f32 %0, %1;" : "=f"(y) : "f"(x)); return y; }
__device__ __forceinline__ uint4 ldg_rlx128(const void* p) {
    uint4 v; asm volatile("ld.relaxed.gpu.global.v4.u32 {%0,%1,%2,%3}, [%4];" : "=r"(v.x), "=r"(v.y), "=r"(v.z), "=r"(v.w) : "l"(p) : "memory"); return v;
}
__device__ __forceinline__ uint4 ldg_rlx2x64(const void* p) {
    unsigned long long a, b; asm volatile("ld.relaxed.gpu.global.v2.u64 {%0,%1}, [%2];" : "=l"(a), "=l"(b) : "l"(p) : "memory");
    return make_uint4((unsigned)a, (unsigned)(a >> 32), (unsigned)b, (unsigned)(b >> 32));
}
__device__ __forceinline__ uint2 ldg_rlx64(const void* p) {
    unsigned long long a; asm volatile("ld.relaxed.gpu.global.u64 %0, [%1];" : "=l"(a) : "l"(p) : "memory"); return make_uint2((unsigned)a, (unsigned)(a >> 32));
}
__device__ __forceinline__ unsigned ldg_acq32(const void* p) { unsigned v; asm volatile("ld.acquire.gpu.global.u32 %0, [%1];" : "=r"(v) : "l"(p) : "memory"); return v; }
__device__ __forceinline__ void red_add(void* p, unsigned v) { asm volatile("red.relaxed.gpu.global.add.u32 [%0], %1;" :: "l"(p), "r"(v) : "memory"); }
__device__ __forceinline__ unsigned now_ns() { unsigned t; asm volatile("mov.u32 %0, %%globaltimer_lo;" : "=r"(t)); return t; }
__device__ __forceinline__ void nap(unsigned ns) { asm volatile("nanosleep.u32 %0;" :: "r"(ns)); }
__device__ __forceinline__ unsigned ldg_rlx32(const void* p) { unsigned v; asm volatile("ld.relaxed.gpu.global.u32 %0, [%1];" : "=r"(v) : "l"(p) : "memory"); return v; }
__device__ __forceinline__ void stg_rlx32(void* p, unsigned v) { asm volatile("st.relaxed.gpu.global.u32 [%0], %1;" :: "l"(p), "r"(v) : "memory"); }
__device__ __forceinline__ void stg_rlx16(void* p, unsigned v) { asm volatile("st.relaxed.gpu.global.u16 [%0], %1;" :: "l"(p), "h"((unsigned short)v) : "memory"); }
__device__ __forceinline__ uint4 ldg_b128(const void* p) {
    unsigned long long a, b; asm volatile("{\n.reg .b128 x;\nld.relaxed.gpu.global.b128 x, [%2];\nmov.b128 {%0,%1}, x;\n}" : "=l"(a), "=l"(b) : "l"(p) : "memory");
    return make_uint4((unsigned)a, (unsigned)(a >> 32), (unsigned)b, (unsigned)(b >> 32));
}
__device__ __forceinline__ void stg_b128(void* p, uint4 v) {
    asm volatile("{\n.reg .b128 x;\nmov.b128 x, {%1,%2};\nst.relaxed.gpu.global.b128 [%0], x;\n}" :: "l"(p), "l"(v.x | ((unsigned long long)v.y << 32)), "l"(v.z | ((unsigned long long)v.w << 32)) : "memory");
}
__device__ __forceinline__ int rowoff(int b, int c) { return ((c >> 6) * 2 + ((c >> 2) & 1)) * 512 + b * 64 + (c & 3) * 16 + ((c >> 3) & 1) * 8 + ((c >> 5) & 1) * 4 + ((c >> 4) & 1) * 2; }
__device__ __forceinline__ void stg_rlx64(void* p, unsigned lo, unsigned hi) {
    unsigned long long a = lo | ((unsigned long long)hi << 32); asm volatile("st.relaxed.gpu.global.u64 [%0], %1;" :: "l"(p), "l"(a) : "memory");
}
__device__ __forceinline__ void stg_rlx128(void* p, uint4 v) { asm volatile("st.relaxed.gpu.global.v4.u32 [%0], {%1,%2,%3,%4};" :: "l"(p), "r"(v.x), "r"(v.y), "r"(v.z), "r"(v.w) : "memory"); }
__device__ __forceinline__ void sts32u(uint32_t a, unsigned x) { asm volatile("st.volatile.shared.u32 [%0], %1;" :: "r"(a), "r"(x) : "memory"); }
__device__ __forceinline__ unsigned lds32u(uint32_t a) { unsigned v; asm volatile("ld.volatile.shared.u32 %0, [%1];" : "=r"(v) : "r"(a) : "memory"); return v; }
__device__ __forceinline__ void spin(unsigned c0, unsigned d) { if (d) while ((unsigned)clock() - c0 < d) {} }
__device__ __forceinline__ void fence_gpu() { asm volatile("fence.acq_rel.gpu;" ::: "memory"); }
__device__ __forceinline__ bool valid4(const uint4& v) { return max(max(v.x, v.y), max(v.z, v.w)) != SENT; }
template <int ID, int N> __device__ __forceinline__ void bar_sync() { asm volatile("bar.sync %0, %1;" :: "n"(ID), "n"(N) : "memory"); }
template <int ID, int N> __device__ __forceinline__ void bar_arrive() { asm volatile("bar.arrive %0, %1;" :: "n"(ID), "n"(N) : "memory"); }
__device__ __forceinline__ void sts64(uint32_t a, float x, float y) { asm volatile("st.shared.v2.f32 [%0], {%1,%2};" :: "r"(a), "f"(x), "f"(y) : "memory"); }
__device__ __forceinline__ void sts128(uint32_t a, uint4 v) { asm volatile("st.volatile.shared.v4.u32 [%0], {%1,%2,%3,%4};" :: "r"(a), "r"(v.x), "r"(v.y), "r"(v.z), "r"(v.w) : "memory"); }
__device__ __forceinline__ void sts128f(uint32_t a, float x, float y, float z, float w) { asm volatile("st.volatile.shared.v4.f32 [%0], {%1,%2,%3,%4};" :: "r"(a), "f"(x), "f"(y), "f"(z), "f"(w) : "memory"); }
__device__ __forceinline__ void sts32(uint32_t a, float x) { asm volatile("st.shared.f32 [%0], %1;" :: "r"(a), "f"(x) : "memory"); }
__device__ __forceinline__ float2 lds64(uint32_t a) { float2 v; asm volatile("ld.shared.v2.f32 {%0,%1}, [%2];" : "=f"(v.x), "=f"(v.y) : "r"(a) : "memory"); return v; }
__device__ __forceinline__ float lds32(uint32_t a) { float v; asm volatile("ld.shared.f32 %0, [%1];" : "=f"(v) : "r"(a) : "memory"); return v; }
__device__ __forceinline__ float4 lds128(uint32_t a) { float4 v; asm volatile("ld.shared.v4.f32 {%0,%1,%2,%3}, [%4];" : "=f"(v.x), "=f"(v.y), "=f"(v.z), "=f"(v.w) : "r"(a) : "memory"); return v; }
__device__ __forceinline__ float2 sum8(uint32_t a) {
    float2 v[8];
#pragma unroll
    for (int i = 0; i < 8; i++) v[i] = lds64(a + i * SCR);
    return make_float2(((v[0].x + v[1].x) + (v[2].x + v[3].x)) + ((v[4].x + v[5].x) + (v[6].x + v[7].x)),
                       ((v[0].y + v[1].y) + (v[2].y + v[3].y)) + ((v[4].y + v[5].y) + (v[6].y + v[7].y)));
}
template <int STRIDE> __device__ __forceinline__ float4 sum8x4(uint32_t a) {
    float4 v[8];
#pragma unroll
    for (int i = 0; i < 8; i++) v[i] = lds128(a + i * STRIDE);
    return make_float4(((v[0].x + v[1].x) + (v[2].x + v[3].x)) + ((v[4].x + v[5].x) + (v[6].x + v[7].x)), ((v[0].y + v[1].y) + (v[2].y + v[3].y)) + ((v[4].y + v[5].y) + (v[6].y + v[7].y)),
                       ((v[0].z + v[1].z) + (v[2].z + v[3].z)) + ((v[4].z + v[5].z) + (v[6].z + v[7].z)), ((v[0].w + v[1].w) + (v[2].w + v[3].w)) + ((v[4].w + v[5].w) + (v[6].w + v[7].w)));
}
__device__ __forceinline__ float rcp(float x) { float y; asm("rcp.approx.ftz.f32 %0, %1;" : "=f"(y) : "f"(x)); return y; }
__device__ __forceinline__ float sigmoid_f(float x) { return rcp(1.0f + ex2(x * -1.4426950408889634f)); }
__device__ __forceinline__ uint32_t silu2(uint32_t c) { const float a = blo(c), b = bhi(c); return pack2(a * sigmoid_f(a), b * sigmoid_f(b)); }
__device__ __forceinline__ void ln_consts(float mean, float var, uint32_t& mu2, float& rs) {
    mu2 = pack2(mean, mean);
    float sd; asm("sqrt.approx.ftz.f32 %0, %1;" : "=f"(sd) : "f"(rbf(rbf(var) + 1e-5f)));
    rs = rcp(rbf(sd));
}
__device__ __forceinline__ uint32_t ln_norm(uint32_t x2, uint32_t mu2, float rs) { const uint32_t d = sub2(x2, mu2); return pack2(blo(d) * rs, bhi(d) * rs); }

__global__ void __launch_bounds__(NALL, 1) fused_kernel(const __nv_bfloat16* const px, const __nv_bfloat16* const pc, const __nv_bfloat16* const pk, const __nv_bfloat16* const pwm,
                                                        const __nv_bfloat16* const pwq, char* const X, const __grid_constant__ Params P) {
    extern __shared__ __align__(1024) unsigned char smem[];
    const uint32_t sb = smem_u32(smem);
    const int tid = threadIdx.x, w = tid >> 5, lane = tid & 31, g = lane >> 2, t = lane & 3;
    const int cta = blockIdx.x, head = cta >> 2, bat = (cta & 3) * 2 + (w >> 2);
    const uint32_t s0 = sb + w * UNIT, s2 = s0 + 4 * REG;
    const uint32_t bar0 = sb + SM_BAR + w * 64;
    const uint32_t barC = bar0 + 32;
    const uint32_t scr = sb + SM_SCR, myscr = scr + w * SCR;
    pf_if((const char*)pwm + ((cta * 4 + (tid >> 4)) * (6 * DM * 2) + (tid & 15) * 128), w, 2);
    pf_if((const char*)pk + (unsigned)(((((cta & 3) * 2 + (w & 1)) * NH + head) * SK + (SK - WIN - 16) + (w >> 1) * 16) * (DH * 2) + lane * 128), w - 2, PFK);
    const int rid = !RMAP ? cta : !(cta & 1) ? cta >> 1 : (cta >> 2) + (cta & 2 ? 64 : 96);
    const unsigned t_start = now_ns();
    CKDECL;
    uint64_t pol;
    asm volatile("createpolicy.fractional.L2::evict_first.b64 %0, 1.0;" : "=l"(pol));
    auto ffn_finish = [&]() {
        const int b = (tid - 256) >> 3, c = tid & 7;
        char* const ho = pin(X + X_HM + (rid >> 4) * 8192 + ((rid >> 1) & 7) * 512 + b * 64 + (c & 3) * 16 + (rid & 1) * 8 + (c >> 2) * 4);
        const uint32_t pi = pin(scr + SC_F1 + c * 144 + b * 16), si = pin(sb + SM_ST + b * 64);
        bar_sync<B_PRE, NALL>();
        const float4 C = sum8x4<UNIT>(sb + REG + c * 144 + b * 16), S = sum8x4<UNIT>(sb + REG + 1152 + c * 144 + b * 16);
        sts128f(sb + SM_PR + lane * 16, C.x, C.y, C.z, C.w); sts128f(sb + SM_PR + lane * 16, S.x, S.y, S.z, S.w);
        sts128(sb + SM_PR + lane * 16, make_uint4(pi, si, (uint32_t)(size_t)ho, (uint32_t)((size_t)ho >> 32)));
        bar_sync<B_FIN, NALL>();
        const float4 s0_ = lds128(si), s1_ = lds128(si + 16), s2_ = lds128(si + 32), s3_ = lds128(si + 48);
        const float4 p = sum8x4<SCR>(pi);
        const float mean = (((s0_.x + s0_.z) + (s1_.x + s1_.z)) + ((s2_.x + s2_.z) + (s3_.x + s3_.z))) * (1.0f / DM);
        const float sq = (((s0_.y + s0_.w) + (s1_.y + s1_.w)) + ((s2_.y + s2_.w) + (s3_.y + s3_.w))) * (1.0f / DM);
        float rs; asm("rsqrt.approx.ftz.f32 %0, %1;" : "=f"(rs) : "f"(fmaxf(sq - mean * mean, 0.f) + 1e-5f));
        const float g0 = rs * (p.x - mean * C.x) + S.x, g1 = rs * (p.y - mean * C.y) + S.y, u0 = rs * (p.z - mean * C.z) + S.z, u1 = rs * (p.w - mean * C.w) + S.w;
        const unsigned hw = pack2(sigmoid_f(g0) * u0, sigmoid_f(g1) * u1);
        stg_rlx32(ho, hw); stg_rlx32(ho + 4096, hw);
        CKP(9);
    };
    auto go_first = [&](uint32_t wbar, uint32_t par) {
        for (int n = 0;; n++) {
            if (mbar_test(wbar, par)) return false;
            if (mbar_test(sb + SM_BG, 0)) return true;
            if (n > SPIN_MAX * 4) __trap();
            nap(GNAP);
        }
    };
    auto reduce = [&](int task, uint32_t rx, unsigned c0, unsigned dly) {
        const char* const pp = pin(X + blk(X_PART, task, lds32u(sb + SM_SIDE)) + lane * 16);
        const float4 gx = lds128(rx + (lane & 7) * 16);
        char* const xo = pin(X + (lane >> 4) * 16384 + blk(X_X1, (task >> 3) & 1, lane >> 3) + (task & 7) * 512 + (task >> 4) * 64 + (lane & 7) * 8);
        uint4 v[8]; int n = 0;
        float a[4];
        spin(c0, dly);
#pragma unroll
        for (int j = 0; j < 8; j++) v[j] = ldg_b128(pp + j * 512);
        while (true) {
#define RSUM(f) (((__uint_as_float(v[0].f) + __uint_as_float(v[1].f)) + (__uint_as_float(v[2].f) + __uint_as_float(v[3].f))) + ((__uint_as_float(v[4].f) + __uint_as_float(v[5].f)) + (__uint_as_float(v[6].f) + __uint_as_float(v[7].f))))
            const bool ok = __all_sync(~0u, max(max(max(v[0].x, v[1].x), max(v[2].x, v[3].x)), max(max(v[4].x, v[5].x), max(v[6].x, v[7].x))) != SENT);
            a[0] = RSUM(x); a[1] = RSUM(y); a[2] = RSUM(z); a[3] = RSUM(w);
            asm volatile("" : "+f"(a[0]), "+f"(a[1]), "+f"(a[2]), "+f"(a[3]));
            if (ok) break;
#pragma unroll
            for (int j = 0; j < 8; j++) if (v[j].x == SENT) v[j] = ldg_b128(pp + j * 512);
            if (++n > SPIN_MAX) __trap();
        }
        CKP(4); CKN(10, n + 1);
#pragma unroll
        for (int i = 0; i < 4; i++) a[i] += __shfl_xor_sync(~0u, a[i], 8);
#pragma unroll
        for (int i = 0; i < 4; i++) a[i] += __shfl_xor_sync(~0u, a[i], 16);
        const unsigned x0 = add2(__float_as_uint(gx.z), mul2(__float_as_uint(gx.x), pack2(a[0], a[1]))), x1 = add2(__float_as_uint(gx.w), mul2(__float_as_uint(gx.y), pack2(a[2], a[3])));
        if (XC > 1 || lane < 16) stg_rlx64(xo, x0, x1);
        if (XC > 2) stg_rlx64(xo + 32768, x0, x1);
        CKP(5);
    };
    if (w == 9) {
        const uint32_t sl = sb + SM_PR + lane * 16;
        char* const pl = X + blk(X_PRB, cta >> 1, lane & 1) + (lane >> 1) * 256 + (cta & 1) * 128;
        {
            char* const ps = X + X_PRB + (cta >> 1) * 8192 + (lane >> 1) * 256 + (cta & 1) * 128 + (lane & 1) * 16;
            sts32u(sl, 0);
            stg_rlx128(ps, make_uint4(1, 1, 1, 1)); stg_rlx128(ps + 4096, make_uint4(1, 1, 1, 1));
            __syncwarp();
        }
        unsigned v; asm volatile("atom.relaxed.gpu.global.add.u32 %0, [%1], 1;" : "=r"(v) : "l"(pl) : "memory");
        unsigned tag = ldg_rlx32(X + X_EPOCH);
        if (lane == 0) pf_bulk(pwq + (size_t)cta * QN * 1024, QN * 2048);
        CKA(0);
        if (lane == 0) sts32u(sb + SM_AN, t_start + ANCH0 - 74);
        if (lane < 8) sts32u(sb + SM_BAR + lane * 64 + 56, 0);
        {
            int d, n = 0;
#pragma unroll 1
            for (int r = 0; r < 4; r++) {
                if (v == SENT) __trap();
                asm volatile("cp.async.cg.shared.global [%0], [%1], 16;" :: "r"(sl), "l"(pl) : "memory");
                unsigned m;
                do {
                    m = __ballot_sync(~0u, lds32u(sl));
                    d = __popc(m & 0xAAAAAAAAu) - __popc(m & 0x55555555u);
                    if (++n > SPIN_MAX) __trap();
                } while (abs(d) < 6 && m != ~0u);
                if (abs(d) >= 6) break;
                asm volatile("cp.async.wait_all;" ::: "memory");
                sts32u(sl, 0);
                asm volatile("atom.relaxed.gpu.global.add.u32 %0, [%1], 1;" : "=r"(v) : "l"(pl) : "memory");
            }
            unsigned side = d > 0;
            tag++;
            if (lane == 0) { sts32u(sb + SM_SIDE, side); sts32u(sb + SM_TAG, tag); }
            bar_arrive<B_SIDE, NTHR>();
        }
        CKA(1);
        asm volatile("cp.async.wait_all;" ::: "memory");
        uint2* const g_lag = (uint2*)(X + X_LAG);
        while (now_ns() - t_start < PACE0) nap(200);
        for (int n = 0; n < SPIN_MAX; n++) {
            const unsigned mine = lane < 8 ? lds32u(sb + SM_BAR + lane * 64 + 56) : 30, t1 = now_ns();
            const unsigned lo = __reduce_min_sync(~0u, mine), sum = __reduce_add_sync(~0u, lane < 8 ? mine : 0);
            if (lo == 30) break;
            if (lo && lane == 0) stg_rlx64(g_lag + cta * 16, t1 - sum * TAU, tag);
            uint2 a = make_uint2(0, 0);
            if (cta == 0) {
                uint2 u[4];
#pragma unroll
                for (int i = 0; i < 4; i++) u[i] = ldg_rlx64(g_lag + (lane + 32 * i) * 16);
                const int s = __reduce_add_sync(~0u, (int)(u[0].x + u[1].x + u[2].x + u[3].x - 4 * t_start));
                if (__all_sync(~0u, (u[0].y == tag) & (u[1].y == tag) & (u[2].y == tag) & (u[3].y == tag)) && lane == 0) {
                    a = make_uint2(t_start + s / NCTA, tag);
                    stg_rlx64(g_lag + NCTA * 16, a.x, tag);
                }
            } else if (lane == 0) a = ldg_rlx64(g_lag + NCTA * 16);
            if (lane == 0 && a.y == tag) sts32u(sb + SM_AN, a.x - LEAD);
            __syncwarp();
            nap(PACE_NAP);
        }
        const unsigned side = lds32u(sb + SM_SIDE);
        {
            bar_sync<B_ML, NTHR>();
            const float2 ml = lds64(sb + SM_ML + (lane & 7) * 8);
            float M = fmaxf(ml.x, __shfl_xor_sync(~0u, ml.x, 1)); M = fmaxf(M, __shfl_xor_sync(~0u, M, 2));
            const float e = ex2((ml.x - M) * 1.4426950408889634f);
            float L = e * ml.y; L += __shfl_xor_sync(~0u, L, 1); L += __shfl_xor_sync(~0u, L, 2);
            if (lane < 8) sts32(sb + SM_ML + 64 + lane * 4, e * rcp(L));
        }
        bar_arrive<B_RDY, NALL>();
        bar_sync<B_CS, 64>();
        { const unsigned t = lds32u(sb + SM_AN) + 256 * TAU + RT0 + (cta & 7) * (TAU / 8); while ((int)(now_ns() - t) < 0) nap(20); }
        const unsigned c0 = clock() - RD0;
        reduce(cta, scr + SC_RX, c0, RD0);
        if (rid >= NF1 && rid < DN0) { CKEND; return; }
        const unsigned c1 = clock();
        if (rid >= DN0) {
            const int f = rid - DN0;
            const char* const rp = X + (rid & (XC - 1)) * 16384 + blk(X_X1, f >> 4, side) + (rowoff(g, f * 16 + t * 4) & 4092);
            unsigned r[4]; int n = 0;
            spin(c1, HD0 - 450);
            do {
#pragma unroll
                for (int i = 0; i < 4; i++) r[i] = ldg_rlx32(rp + i * 16);
                if (++n > SPIN_MAX) __trap();
            } while (max(max(r[0], r[1]), max(r[2], r[3])) == SENT);
            const unsigned sel = (f & 1) ? 0x7632 : 0x5410;
            sts64(sb + SM_MN + 256 + lane * 8, __uint_as_float(__byte_perm(r[0], r[1], sel)), __uint_as_float(__byte_perm(r[2], r[3], sel)));
            __syncwarp();
        }
        spin(c1, rid < NF1 ? XD0 : HD0);
        if (lane == 0) { if (GREL == 1) sts32u(sb + SM_GO, clock()); asm volatile("mbarrier.arrive.shared::cta.b64 _, [%0];" :: "r"(sb + SM_BG) : "memory"); }
        CKP(8);
        if (rid < NF1) ffn_finish();
        return;
    }
    if (w == 8) {
        const int row0 = ((cta & 3) * 2 * NH + head) * SK + (SK - WIN);
        auto kv_unit = [&](int u) {
            const uint32_t b = sb + SM_BAR + (u & 7) * 64 + (u >> 3) * 8;
            mbar_expect(b, UNIT);
            tma_kv(sb + (u >> 3) * REG + (u & 7) * UNIT, (u & 8) ? &P.v : &P.k, row0 + ((u >> 2) & 1) * NH * SK + (u & 3) * 16 + (u >> 4) * 64, b, pol);
        };
        if (elect()) {
            mbar_init(sb + SM_BM, 1);
#pragma unroll
            for (int i = 0; i < 8; i++) mbar_init(sb + SM_BAR + i * 64 + 48, 1);
            asm volatile("fence.mbarrier_init.release.cluster;" ::: "memory");
            CKA(0);
            mbar_expect(sb + SM_BM, 512 * 16);
            tma2d(sb + 4 * REG, &P.wm, cta * 8, 0, sb + SM_BM); tma2d(sb + 4 * REG + 256 * 16, &P.wm, cta * 8, 256, sb + SM_BM);
#pragma unroll
            for (int i = 0; i < 8; i++) { const uint32_t b = sb + SM_BAR + i * 64 + 48; mbar_expect(b, UNIT); tma2d(sb + 5 * REG + i * UNIT, &P.wq, cta * 32, i * 64, b); }
            CKA(1);
            mbar_init(sb + SM_BN, 1); mbar_init(sb + SM_BT, 1); mbar_init(sb + SM_BG, 1);
#pragma unroll
            for (int i = 0; i < 48; i++) mbar_init(sb + SM_BAR + (i & 7) * 64 + (i >> 3) * 8, 1);
            asm volatile("fence.mbarrier_init.release.cluster;" ::: "memory");
        }
        __syncwarp();
        bar_arrive<B_INIT, NTHR>();
        CKA(2);
        {
            uint32_t mine = lane >= NTRK ? 0 : lane < 8 ? sb + SM_BAR + lane * 64 + 48 : sb + SM_BM;
            int next = 0, lim = 32, n = 0;
            while (next < 48) {
                const bool idle = lane < (next < PSW ? PWIN0 : PWIN) && (mine == 0 || mbar_test(mine, 0));
                const unsigned m = __ballot_sync(~0u, idle);
                const int u = next + __popc(m & ((1u << lane) - 1));
                if (idle) {
                    mine = 0;
                    if (u < lim) { kv_unit(u); mine = sb + SM_BAR + (u & 7) * 64 + (u >> 3) * 8; }
                }
                next = min(next + __popc(m), lim);
                if (next == lim) {
                    if (lim == 32) { CKA(3); bar_sync<B_MOD, NTHR>(); } else if (lim == 40) { CKA(4); bar_sync<B_WQ, NTHR>(); CKA(5); }
                    lim += 8;
                }
                if (!m) nap(PNAP);
                if (++n > SPIN_MAX) __trap();
            }
        }
        if (lane < 5) pf_map(&P.wn + lane);
        CKA(6);
        float m[4][4] = {};
        auto late_mod = [&](uint32_t a, int h) {
            const int lrow = (lane & 7) + ((lane >> 4) << 3), lch = (lane >> 3) & 1;
            const uint32_t a0 = a + lrow * 32 + ((lch ^ ((lrow >> 2) & 1)) << 4);
            const uint32_t c0 = sb + SM_SC + h * 4096 + (lane & 7) * 128 + (((lane >> 3) ^ (lane & 7)) << 4);
#pragma unroll
            for (int j = 0; j < 8; j++) {
                uint32_t c[4], r[4], u[4];
                ldsm(c, (c0 + (j >> 1) * 1024) ^ ((j & 1) << 6)); ldsm_t(r, a0 + j * 1024); ldsm_t(u, a0 + j * 1024 + 512);
                mma(m[(j & 1) * 2], r, c[0], c[1]); mma(m[(j & 1) * 2 + 1], u, c[2], c[3]);
            }
        };
        if (rid < 96) {
#pragma unroll 1
            for (int h = 0; h < 2; h++) {
                if (lane == 0) { mbar_expect(sb + SM_BN, 8192); tma2d(sb + SM_MN, &P.wn, 2 * DM + rid * 16, h * 256, sb + SM_BN); }
                mbar_wait(sb + SM_BN, h);
                late_mod(sb + SM_MN, h);
                asm volatile("" :: "f"(m[0][0]), "f"(m[1][0]), "f"(m[2][0]), "f"(m[3][0]) : "memory");
                __syncwarp();
            }
#pragma unroll
            for (int e = 0; e < 4; e++) {
                float v = rbf((m[0][e] + m[1][e]) + (m[2][e] + m[3][e]));
                if (rid >= 64) v += 1.0f;
                stg_rlx16(X + X_MOD + (rid >> 5) * 8192 + rowoff(2 * t + (e & 1), (rid & 31) * 16 + g + (e >> 1) * 8), pack2(v, 0.f));
            }
        }
        CKA(7);
        {
            const unsigned side = lds32u(sb + SM_SIDE);
#pragma unroll
            for (int i = 0; i < 8; i++) stg_rlx128(X + blk(X_PART, cta, side) + i * 512 + lane * 16, make_uint4(SENT, SENT, SENT, SENT));
            if (lane == 0) stg_rlx32(X + X_SIDE + cta * 4, side);
        }
        bar_sync<B_Q, NTHR>();
        if (lane == 0) {
            CKA(8);
            const unsigned tag = lds32u(sb + SM_TAG);
            fence_gpu();
            red_add(X + X_READY, 1);
            int n = 0;
            while ((int)(ldg_acq32(X + X_READY) - tag * NCTA) < 0) { nap(1000); if (++n > SPIN_MAX) __trap(); }
            if (cta == 0) stg_rlx32(X + X_EPOCH, tag);
            CKA(9);
        }
        __syncwarp();
        {
            stg_rlx128(X + blk(X_Q, head >> 1, 0) + (head & 1) * 2048 + g * 256 + (cta & 3) * 64 + t * 16, make_uint4(0, 0, 0, 0));
            stg_rlx128(X + blk(X_Q, head >> 1, 1) + (head & 1) * 2048 + g * 256 + (cta & 3) * 64 + t * 16, make_uint4(0, 0, 0, 0));
            stg_rlx64(X + blk(X_M1, cta >> 5, lane >> 4) + (cta & 31) * 128 + (lane & 15) * 8, 0, 0);
            const int wt = (cta & 3) * 32 + lane;
            const unsigned mask = __ballot_sync(~0u, blk(X_PART, wt, ldg_rlx32(X + X_SIDE + wt * 4)) & 4096);
            if (lane == 0) sts32u(sb + SM_MASK, mask);
            if (lane < 8) {
                const int task = cta;
                const int rb = task >> 4, c = ((task & 15) >> 1) * 64 + (task & 1) * 4 + ((lane & 7) >> 1) + (lane & 1) * 8;
                const uint2 ga = ldg_rlx64(X + X_MOD + rowoff(rb, c));
                const unsigned short* const xp = (const unsigned short*)px + rb * DM + c;
                sts128(scr + (lane >> 3) * SCR + SC_RX + (lane & 7) * 16, make_uint4(ga.x, ga.y, xp[0] | (xp[16] << 16), xp[32] | (xp[48] << 16)));
            }
            if (rid < NF1) {
#pragma unroll 1
                for (int i = 0; i < 4; i++) {
                    uint4 v[8];
#pragma unroll
                    for (int j = 0; j < 8; j++) v[j] = ldg_rlx128(X + X_MOD + 8192 + (i * 8 + j) * 512 + lane * 16);
#pragma unroll
                    for (int j = 0; j < 8; j++) sts128(sb + SM_MN + (i * 8 + j) * 512 + lane * 16, v[j]);
                }
            }
        }
        CKA(10);
        bar_arrive<B_RDY, NALL>();
        if (RT0) bar_arrive<B_CS, 64>();
        unsigned t_ref = 0;
        auto until = [&](int x) { while ((int)(now_ns() - t_ref) < x) nap(20); };
        if (elect()) {
#pragma unroll 1
            for (int i = 0; i < 8; i++) { int n = 0; while (lds32u(sb + SM_BAR + i * 64 + 56) < 30) { nap(100); if (++n > SPIN_MAX) __trap(); } }
            t_ref = lds32u(sb + SM_AN) + 256 * TAU + (cta & 7) * (TAU / 8);
            if (rid < NF1) {
#pragma unroll
                for (int i = 0; i < WP; i++) mbar_expect(sb + SM_BAR + i * 64 + 48, XA_ ? 0 : 8 / WP * UNIT);
#pragma unroll 1
                for (int i = 0; i < (XA_ ? 0 : WP); i++) {
                    const uint32_t b = sb + SM_BAR + i * 64 + 48;
                    until(W0 + i * WS);
                    tma5d(sb + 2 * REG + i * (16384 / WP), &P.wg, rid * 16, i * (16 / WP), b); tma5d(sb + 2 * REG + 16384 + i * (16384 / WP), &P.wu, rid * 16, i * (16 / WP), b);
                    CKP(i);
                }
            } else if (rid >= DN0) {
                mbar_expect(sb + SM_BN, XA_ ? 0 : 16384); mbar_expect(sb + SM_BT, XA_ ? 0 : FF * 32);
            }
            until(PF2);
            if (PF2 > 0) pf_bulk(P.wdp + cta * (DM * FF / NCTA), DM * FF / NCTA * 2);
            CKP(7); CKN(8, t_ref);
        }
        if (rid >= DN0) {
            bar_sync<B_LAST, NTHR>();
            if (elect()) {
                until(FFN_T2);
                tma5d(sb + 2 * REG + 16384, &P.wd, (rid - DN0) * 16, 0, sb + SM_BT); tma5d(sb + 2 * REG + 16384 + 43 * 512, &P.wd, (rid - DN0) * 16, 43, sb + SM_BT);
                CKP(13);
                until(MOD_T2);
                tma2d(sb + 2 * REG, &P.wn, 2 * DM + rid * 16, 0, sb + SM_BN); tma2d(sb + 2 * REG + 8192, &P.wn, 2 * DM + rid * 16, 256, sb + SM_BN);
                CKP(12);
            }
        }
        __syncwarp();
        if (rid < NF1) ffn_finish();
        if (rid >= DN0) {
            mbar_wait(sb + SM_BN, 0);
            CKP(0);
            late_mod(sb + 2 * REG, 0); late_mod(sb + 2 * REG + 8192, 1);
#pragma unroll
            for (int e = 0; e < 2; e++)
                sts32u(sb + SM_MN + g * 32 + e * 16 + t * 4, movm(pack2((m[0][2 * e] + m[1][2 * e]) + (m[2][2 * e] + m[3][2 * e]), (m[0][2 * e + 1] + m[1][2 * e + 1]) + (m[2][2 * e + 1] + m[3][2 * e + 1]))));
            bar_arrive<B_DN, NTHR>();
            CKP(1);
        }
        return;
    }
    const unsigned ce = (lane >> 3) * (DM * 2) + w * 128 + (lane & 7) * 16;
    const uint4 ca = ldg_nc((const char*)pc + ce), cb = ldg_nc((const char*)pc + ce + 4 * DM * 2);
    const uint4 xa = ldg_nc((const char*)px + w * (DM * 2) + lane * 16), xb = ldg_nc((const char*)px + w * (DM * 2) + lane * 16 + 512);
    const uint4 xc = ldg_nc((const char*)px + ce), xd = ldg_nc((const char*)px + ce + 4 * DM * 2);
    CKA(12);
    if (w >= 4) pf_map(&P.wm + (w & 3));
    char* const qout = X + blk(X_Q, head >> 1, tid >> 7) + (head & 1) * 2048 + ((tid >> 4) & 7) * 256 + (cta & 3) * 64 + (tid & 3) * 16 + ((tid >> 2) & 3) * 4;
    char* const mout = X + blk(X_M1, cta >> 5, w) + (cta & 31) * 128 + lane * 4;
    stg_rlx32(qout, 0);
    if (w < 2) stg_rlx32(mout, 0);
    uint32_t sc[8], xf[8];
    {
        const uint32_t a = (lane >> 3) * 128 + (((lane & 7) ^ (lane >> 3)) << 4), b = (lane & 7) * 128 + (((lane >> 3) ^ (lane & 7)) << 4);
        const uint32_t cs = sb + SM_SC + w * 1024;
        sts128(cs + a, make_uint4(silu2(ca.x), silu2(ca.y), silu2(ca.z), silu2(ca.w)));
        sts128(cs + 512 + (a ^ 64), make_uint4(silu2(cb.x), silu2(cb.y), silu2(cb.z), silu2(cb.w)));
        sts128(myscr + a, xc); sts128(myscr + 512 + (a ^ 64), xd);
        __syncwarp();
        ldsm(*(uint32_t(*)[4])&sc[0], cs + b); ldsm(*(uint32_t(*)[4])&sc[4], cs + (b ^ 64));
        ldsm(*(uint32_t(*)[4])&xf[0], myscr + b); ldsm(*(uint32_t(*)[4])&xf[4], myscr + (b ^ 64));
        __syncwarp();
    }
    CKA(0);
    {
        float v[16] = {blo(xa.x), bhi(xa.x), blo(xa.y), bhi(xa.y), blo(xa.z), bhi(xa.z), blo(xa.w), bhi(xa.w),
                       blo(xb.x), bhi(xb.x), blo(xb.y), bhi(xb.y), blo(xb.z), bhi(xb.z), blo(xb.w), bhi(xb.w)};
        float s = 0;
#pragma unroll
        for (int i = 0; i < 16; i++) s += v[i];
#pragma unroll
        for (int o = 16; o; o >>= 1) s += __shfl_xor_sync(~0u, s, o);
        s *= (1.0f / DM);
        float q2 = 0;
#pragma unroll
        for (int i = 0; i < 16; i++) q2 += (v[i] - s) * (v[i] - s);
#pragma unroll
        for (int o = 16; o; o >>= 1) q2 += __shfl_xor_sync(~0u, q2, o);
        uint32_t mu2; float rs; ln_consts(s, q2 * (1.0f / DM), mu2, rs);
        if (lane == 0) sts64(sb + SM_ST + w * 8, __uint_as_float(mu2), rs);
    }
    const int lrow = (lane & 7) + ((lane >> 4) << 3), lch = (lane >> 3) & 1;
    const uint32_t off64 = lrow * 64 + ((lch ^ ((lrow >> 1) & 3)) << 4);
    const uint32_t off128 = lrow * 128 + ((lch ^ (lane & 7)) << 4);
    bar_sync<B_INIT, NTHR>();
    mbar_wait(sb + SM_BM, 0);
    CKA(1);
    {
        float a[4] = {0, 0, 0, 0}, b[4] = {0, 0, 0, 0};
        uint32_t r[4], u[4];
        ldsm_t(r, sb + 4 * REG + (w * 64 + lane) * 16); ldsm_t(u, sb + 4 * REG + (w * 64 + 32 + lane) * 16);
        mma(a, sc[0], 0, sc[1], 0, r[0], r[1]); mma(b, sc[4], 0, sc[5], 0, u[0], u[1]);
        mma(a, sc[2], 0, sc[3], 0, r[2], r[3]); mma(b, sc[6], 0, sc[7], 0, u[2], u[3]);
        sts64(myscr + SC_M + lane * 8, a[0] + b[0], a[1] + b[1]);
    }
    bar_arrive<B_MOD, NTHR>();
    bar_sync<B_ALL, 256>();
    if (w < 2) {
        const float2 m = sum8(scr + SC_M + lane * 8);
        stg_rlx32(mout, ~pack2(m.x, m.y));
    }
    CKA(2);
    if (tid < 8 * XC) stg_rlx128(X + X_X1 + (cta * 8 * XC + tid) * 16, make_uint4(SENT, SENT, SENT, SENT));
    else if (tid >= 232) stg_rlx128(X + X_HM + (cta * 24 + tid - 232) * 16, make_uint4(SENT, SENT, SENT, SENT));
    {
        const float2 st = lds64(sb + SM_ST + g * 8);
#pragma unroll
        for (int i = 0; i < 8; i++) xf[i] = ln_norm(xf[i], __float_as_uint(st.x), st.y);
    }
    {
        unsigned sv[8], cv[8]; int n = 0;
        bar_sync<B_SIDE, NTHR>();
        const char* const mp = X + blk(X_M1, w >> 2, lds32u(sb + SM_SIDE)) + (w & 3) * 1024 + lane * 4;
        if (lane == 0) while (!ldg_rlx32(mp + 16384 + 7 * 128)) { nap(40); if (++n > SPIN_MAX) __trap(); }
        __syncwarp();
        CKA(3);
#pragma unroll
        for (int j = 0; j < 8; j++) { sv[j] = ldg_rlx32(mp + j * 128); cv[j] = ldg_rlx32(mp + 16384 + j * 128); }
        while (true) {
            unsigned m = ~0u;
#pragma unroll
            for (int j = 0; j < 8; j++) m = min(m, min(sv[j], cv[j]));
            if (__all_sync(~0u, m)) break;
#pragma unroll
            for (int j = 0; j < 8; j++) { if (!sv[j]) sv[j] = ldg_rlx32(mp + j * 128); if (!cv[j]) cv[j] = ldg_rlx32(mp + 16384 + j * 128); }
            if (++n > SPIN_MAX) __trap();
        }
        CKA(4);
#pragma unroll
        for (int j = 0; j < 8; j++) xf[j] = add2(mul2(xf[j], add2(~cv[j], ONE2)), ~sv[j]);
        mbar_wait(bar0 + 48, 0);
        CKA(5);
        float acc[4][4] = {};
#pragma unroll
        for (int j = 0; j < 4; j++) {
            uint32_t r[4], u[4];
            ldsm_t(r, s2 + REG + j * 1024 + off64); ldsm_t(u, s2 + REG + j * 1024 + (off64 ^ 32));
            mma(acc[0], xf[2 * j], 0, xf[2 * j + 1], 0, r[0], r[2]); mma(acc[1], xf[2 * j], 0, xf[2 * j + 1], 0, r[1], r[3]);
            mma(acc[2], xf[2 * j], 0, xf[2 * j + 1], 0, u[0], u[2]); mma(acc[3], xf[2 * j], 0, xf[2 * j + 1], 0, u[1], u[3]);
        }
#pragma unroll
        for (int n2 = 0; n2 < 4; n2++) sts64(myscr + SC_Q + g * 160 + n2 * 32 + t * 8, acc[n2][0], acc[n2][1]);
    }
    bar_arrive<B_WQ, NTHR>();
    bar_sync<B_ALL, 256>();
    {
        const float2 s = sum8(scr + SC_Q + ((tid >> 4) & 7) * 160 + (tid & 15) * 8);
        stg_rlx32(qout, ~pack2(s.x, s.y));
    }
    CKA(6);
    uint32_t q[16];
    {
        int n = 0;
        const char* const qp = X + blk(X_Q, head >> 1, lds32u(sb + SM_SIDE)) + (head & 1) * 2048 + bat * 256 + t * 16;
        uint4 v[4];
#pragma unroll
        for (int j = 0; j < 4; j++) v[j] = ldg_rlx128(qp + j * 64);
        while (true) {
            bool bad[4];
#pragma unroll
            for (int j = 0; j < 4; j++) bad[j] = !min(min(v[j].x, v[j].y), min(v[j].z, v[j].w));
            if (!__any_sync(~0u, bad[0] | bad[1] | bad[2] | bad[3])) break;
#pragma unroll
            for (int j = 0; j < 4; j++) if (bad[j]) v[j] = ldg_rlx128(qp + j * 64);
            if (++n > SPIN_MAX) __trap();
        }
#pragma unroll
        for (int j = 0; j < 4; j++) { q[4 * j] = ~v[j].x; q[4 * j + 1] = ~v[j].y; q[4 * j + 2] = ~v[j].z; q[4 * j + 3] = ~v[j].w; }
    }
    bar_arrive<B_Q, NTHR>();
    CKA(7);

    float o[2][4] = {};
    float mrun = -3.0e38f, lrun = 0.f;
    uint32_t wa[16][4], pb[2];
#pragma unroll
    for (int i = 0; i < 16; i++) wa[i][0] = wa[i][1] = wa[i][2] = wa[i][3] = 0;
    constexpr float LOG2E = 1.4426950408889634f, SCALE = 0.08838834764831845f;
    const uint32_t offk = (lane & 15) * 128 + (((lane >> 4) ^ (lane & 7)) << 4);
    float p0, p1;
    auto scores = [&](uint32_t a0) {
        uint32_t kf[8][4];
#pragma unroll
        for (int j = 0; j < 8; j++) ldsm(kf[j], ((a0 + offk) ^ ((j & 3) << 5)) + (j >> 2) * 2048);
        float sa[4] = {0, 0, 0, 0}, sb2[4] = {0, 0, 0, 0};
#pragma unroll
        for (int j = 0; j < 8; j += 2) { mma(sa, kf[j], q[2 * j], q[2 * j + 1]); mma(sb2, kf[j + 1], q[2 * j + 2], q[2 * j + 3]); }
        uint32_t u = pack2(sa[0] + sb2[0], sa[2] + sb2[2]);
        u = pack2(blo(u) * SCALE, bhi(u) * SCALE);
        const float z0 = blo(u), z1 = bhi(u);
        float mx = fmaxf(z0, z1);
        mx = fmaxf(mx, __shfl_xor_sync(~0u, mx, 4)); mx = fmaxf(mx, __shfl_xor_sync(~0u, mx, 8)); mx = fmaxf(mx, __shfl_xor_sync(~0u, mx, 16));
        mx = fmaxf(mx, mrun);
        const float f = ex2((mrun - mx) * LOG2E);
        p0 = ex2((z0 - mx) * LOG2E); p1 = ex2((z1 - mx) * LOG2E);
        mrun = mx; lrun = lrun * f + (p0 + p1);
#pragma unroll
        for (int j = 0; j < 4; j++) { o[0][j] *= f; o[1][j] *= f; }
    };
    const int kvrow = (bat * NH + head) * SK + (SK - WIN) + (w & 3) * 16;
    const int wofs = (w * 8 + (cta & 7)) * TAU / 8;
    auto request = [&](int u) {
        sts32u(bar0 + 56, u - 1);
        while ((int)(now_ns() - lds32u(sb + SM_AN) - u * 8 * TAU - wofs) < 0) nap(20);
        const int sl = (~u & 2) + (u & 1);
        mbar_expect(bar0 + sl * 8, UNIT); tma_kv(s0 + sl * REG, &P.k + (u & 1), kvrow + (u >> 1) * 64, bar0 + sl * 8, pol);
    };
#pragma unroll 1
    for (int it = 0; it < NT - 1; it++) {
        const int si = it < 3 ? it : (it + 1) & 1;
        const uint32_t bar = bar0 + si * 16, a0 = s0 + si * 2 * REG;
        const uint32_t par = it < 3 ? 0 : ((it - 1) >> 1) & 1;
        const bool refill = lane == 0 && it >= 2;
        mbar_wait(bar, par);
        if (refill) {
            request(2 * it + 2);
            const int e = it - (it > WOA_READ ? WOA_READ + 1 : WOA_ISSUE);
            if (e == 0) mbar_expect(barC, 2 * UNIT);
            if (e == 0 || e == WO_GAP) tma2d(s2 + (e ? REG : 0), &P.wo, w * 64, head * 128 + (it > WOA_READ ? 64 : 0) + (e ? 32 : 0), barC);
        }
        __syncwarp();
        if (it == WOA_READ) {
            mbar_wait(barC, 1);
#pragma unroll
            for (int j = 0; j < 16; j++) ldsm_t(wa[j], s2 + (j >> 3) * REG + ((j >> 2) & 1) * 2048 + (off128 ^ ((j & 3) << 5)));
        }
        scores(a0);
        pb[0] = movm(pack2(p0, p0)); pb[1] = movm(pack2(p1, p1));
        mbar_wait(bar + 8, par);
        if (refill) request(2 * it + 3);
        __syncwarp();
        uint32_t vf[8][4];
#pragma unroll
        for (int j = 0; j < 8; j++) ldsm_t(vf[j], ((a0 + off128) ^ ((j & 3) << 5)) + (j >> 2) * 2048 + REG);
#pragma unroll
        for (int j = 0; j < 8; j++) { const bool on = (g >> 1) == (j >> 1); mma(o[j & 1], vf[j], on ? pb[0] : 0, on ? pb[1] : 0); }
    }
    {
        uint32_t wb[16][4];
        mbar_wait(bar0, 1);
        CKA(13);
        CKP(8);
        if (rid >= DN0) bar_arrive<B_LAST, NTHR>();
        scores(s0);
        lrun += __shfl_xor_sync(~0u, lrun, 4); lrun += __shfl_xor_sync(~0u, lrun, 8); lrun += __shfl_xor_sync(~0u, lrun, 16);
        if (lane == 0) sts64(sb + SM_ML + w * 8, mrun, lrun);
        bar_arrive<B_ML, NTHR>();
        pb[0] = movm(pack2(p0, p0)); pb[1] = movm(pack2(p1, p1));
        const uint32_t va = pin(s0 + REG + off128);
        auto load_wb = [&](int j) { ldsm_t(wb[j], (va ^ ((j & 3) << 5)) + (3 + (j >> 3)) * REG + ((j >> 2) & 1) * 2048); };
        mbar_wait(barC, 0);
#pragma unroll
        for (int j = 0; j < NPRE; j++) load_wb(j);
        const uint32_t ho = pin(s0 + w * 16 + ((lane & 7) >> 1) * 64 + ((lane >> 3) & 1) * 32 + (lane & 1) * 16), oa = pin(sb + (lane & 7) * (UNIT + 16) + (lane >> 3) * 16);
        const uint32_t rd = pin((t >> 1) * 16 + w * 2 + (g >> 2));
        char* const pp = pin(X + X_PART + ((cta & 3) * 32 + rd) * 8192 + head * 128 + (g & 3) * 32 + (t & 1) * 16);
        const uint32_t ln = pin(lane);
        mbar_wait(bar0 + 8, 1);
        CKP(0);
        {
            uint32_t vf[8][4];
            float o2[2][4] = {};
#pragma unroll
            for (int j = 0; j < 8; j++) ldsm_t(vf[j], (va ^ ((j & 3) << 5)) + (j >> 2) * 2048);
#pragma unroll
            for (int j = 0; j < 8; j++) { const bool on = (ln >> 3) == (j >> 1); mma((j & 2) ? o2[j & 1] : o[j & 1], vf[j], on ? pb[0] : 0, on ? pb[1] : 0); }
            asm volatile("stmatrix.sync.aligned.m8n8.x2.trans.shared.b16 [%0], {%1,%2};" :: "r"(ho), "r"(pack2(o[0][0] + o2[0][0], o[0][2] + o2[0][2])), "r"(pack2(o[1][0] + o2[1][0], o[1][2] + o2[1][2])) : "memory");
        }
#pragma unroll
        for (int j = NPRE; j < 16 - WLATE; j++) load_wb(j);
        CKP(1);
        bar_sync<B_RDY, NALL>();
        float y[4][4] = {};
        uint32_t ob[4][4];
#pragma unroll
        for (int i2 = 0; i2 < 4; i2++) ldsm(ob[i2], oa + i2 * 64);
        const float2 f = lds64(sb + SM_ML + 64 + (ln & 3) * 8);
        const unsigned half = (lds32u(sb + SM_MASK) >> rd & 1) * 4096;
#pragma unroll
        for (int j = 16 - WLATE; j < 16; j++) load_wb(j);
#pragma unroll
        for (int j = 0; j < 8; j++)
#pragma unroll
            for (int i = 0; i < 4; i++) mma(y[i], j < 4 ? wa[j * 4 + i] : wb[(j - 4) * 4 + i], ob[j >> 1][2 * (j & 1)], ob[j >> 1][2 * (j & 1) + 1]);
        uint32_t r[4];
#pragma unroll
        for (int i = 0; i < 4; i++) {
            const float lo = f.x * y[i][0] + f.y * y[i][1], hi = f.x * y[i][2] + f.y * y[i][3];
            r[i] = __float_as_uint(((ln & 1) ? hi : lo) + __shfl_xor_sync(~0u, (ln & 1) ? lo : hi, 1));
        }
        asm("min.u32 %0, %0, 0xFFFFFFFE;" : "+r"(r[0]));
        stg_b128(pp + half, make_uint4(r[0], r[1], r[2], r[3]));
    }
    CKP(3);
    const unsigned side = lds32u(sb + SM_SIDE);
    const char* const x1p = X + (rid & (XC - 1)) * 16384;
    if (rid < NF1) {
        uint32_t wg[4][4], wu[4][4];
        const char* const xp = pin(x1p + blk(X_X1, w >> 2, side) + (w & 3) * 1024 + lane * 16);
        float4 c1[2], sv[2];
#pragma unroll
        for (int h = 0; h < 2; h++) { sv[h] = lds128(sb + SM_MN + (w * 2 + h) * 512 + lane * 16); c1[h] = lds128(sb + SM_MN + 8192 + (w * 2 + h) * 512 + lane * 16); }
        const uint32_t po = pin(myscr + SC_F1 + g * 144 + t * 32), so = pin(t == (g >> 1) ? sb + SM_ST + g * 64 + w * 8 : myscr + 1792 + lane * 8), odd = pin(g & 1);
        const uint32_t wbar = sb + SM_BAR + (w * WP >> 3) * 64 + 48;
        uint4 x0, x1;
        const bool early = go_first(wbar, 1);
        if (early) { spin(GREL == 1 ? lds32u(sb + SM_GO) : clock(), (GREL == 2 ? 7 - w : w) * XDW); x0 = ldg_rlx2x64(xp); x1 = ldg_rlx2x64(xp + 512); CKP(6); mbar_wait(wbar, 1); }
        CKP(13);
#pragma unroll
        for (int j = 0; j < 4; j++) {
            const uint32_t a = sb + 2 * REG + w * 2048 + (((lane & 7) >> 1) + (lane & 1) * 4 + j * 8 + (lane >> 4) * 32) * 32 + ((lch ^ (lane & 1)) << 4);
            ldsm_t(wg[j], a); ldsm_t(wu[j], a + 16384);
        }
        {
            float cg[4] = {}, cu[4] = {}, sg[4] = {}, su[4] = {};
#pragma unroll
            for (int j = 0; j < 4; j++) {
                const float4 a = c1[j & 1], b = sv[j & 1];
                const uint32_t a0 = __float_as_uint(j >> 1 ? a.z : a.x), a1 = __float_as_uint(j >> 1 ? a.w : a.y), b0 = __float_as_uint(j >> 1 ? b.z : b.x), b1 = __float_as_uint(j >> 1 ? b.w : b.y);
                mma(cg, wg[j], a0, a1); mma(cu, wu[j], a0, a1); mma(sg, wg[j], b0, b1); mma(su, wu[j], b0, b1);
            }
            const uint32_t d = s0 + REG + g * 144 + t * 32;
            sts128f(d, cg[0], cg[2], cu[0], cu[2]); sts128f(d + 16, cg[1], cg[3], cu[1], cu[3]);
            sts128f(d + 1152, sg[0], sg[2], su[0], su[2]); sts128f(d + 1168, sg[1], sg[3], su[1], su[3]);
            bar_arrive<B_PRE, NALL>();
        }
        CKP(2);
        if (!early) { mbar_wait(sb + SM_BG, 0); spin(GREL == 1 ? lds32u(sb + SM_GO) : clock(), (GREL == 2 ? 7 - w : w) * XDW); x0 = ldg_rlx2x64(xp); x1 = ldg_rlx2x64(xp + 512); CKP(6); }
        int n = 0;
        float sm[4], q0[4], q1[4], ag[2][4], au[2][4];
        while (true) {
            const bool b0 = max(x0.x, x0.z) == SENT, b1 = max(x1.x, x1.z) == SENT;
            const bool ok = !__any_sync(~0u, b0 | b1);
            if (ok)
            {
#pragma unroll
                for (int i = 0; i < 4; i++) sm[i] = q0[i] = q1[i] = ag[0][i] = ag[1][i] = au[0][i] = au[1][i] = 0.f;
                const uint32_t a0[4] = {x0.x, x0.y, x0.z, x0.w}, a1[4] = {x1.x, x1.y, x1.z, x1.w};
                mmav(sm, a0, ONE2, ONE2); mmav(q0, a0, x0.x, x0.z); mmav(q1, a0, x0.y, x0.w);
#pragma unroll
                for (int j = 0; j < 4; j++) {
                    const uint4 xv = (j & 1) ? x1 : x0; const float4 a = c1[j & 1];
                    const uint32_t h0 = mul2(j >> 1 ? xv.z : xv.x, __float_as_uint(j >> 1 ? a.z : a.x)), h1 = mul2(j >> 1 ? xv.w : xv.y, __float_as_uint(j >> 1 ? a.w : a.y));
                    mmav(ag[j & 1], wg[j], h0, h1); mmav(au[j & 1], wu[j], h0, h1);
                    if (j == 0) { mmav(sm, a1, ONE2, ONE2); mmav(q0, a1, x1.x, x1.z); mmav(q1, a1, x1.y, x1.w); }
                }
            }
            if (ok) break;
            if (b0) x0 = ldg_rlx2x64(xp);
            if (b1) x1 = ldg_rlx2x64(xp + 512);
            if (++n > SPIN_MAX) __trap();
        }
        CKP(7); CKN(11, n + 1);
        sts64(so, sm[0] + sm[2], odd ? q0[1] + q1[3] : q0[0] + q1[2]);
        sts128f(po, ag[0][0] + ag[1][0], ag[0][2] + ag[1][2], au[0][0] + au[1][0], au[0][2] + au[1][2]);
        sts128f(po + 16, ag[0][1] + ag[1][1], ag[0][3] + ag[1][3], au[0][1] + au[1][1], au[0][3] + au[1][3]);
        CKP(12);
        bar_arrive<B_FIN, NALL>();
    } else if (rid >= DN0) {
        const int f = rid - DN0;
        uint32_t wd[12][4];
        const char* const hp0 = pin(X + blk(X_HM, 0, side) + w * 512 + lane * 16);
        const char* const hp1 = pin(X + blk(X_HM, 1, side) + w * 512 + lane * 16);
        auto hm = [&](int j) { return ldg_rlx128((j & 1 ? hp1 : hp0) + (j >> 1) * 16384); };
        unsigned* const op = pin((unsigned*)P.out + (tid >> 3) * 256 + f * 8 + (tid & 7));
        const uint32_t po = pin(myscr + SC_DN + t * 160 + g * 4), pi = pin(scr + SC_DN + (tid >> 3) * 80 + (tid & 7) * 8), gi = pin(sb + SM_MN + tid * 4), first = pin(w < 2);
        uint4 hv[6]; int n = 0;
        auto first_poll = [&]() {
            spin(GREL == 1 ? lds32u(sb + SM_GO) : clock(), w * HDW);
#pragma unroll
            for (int j = 0; j < 6; j++) hv[j] = (j < 5 || w < 3) ? hm(j) : make_uint4(0, 0, 0, 0);
            CKP(6);
        };
        const bool early = go_first(sb + SM_BT, 0);
        if (early) { first_poll(); mbar_wait(sb + SM_BT, 0); }
        CKP(13);
#pragma unroll
        for (int j = 0; j < 12; j++)
            if (j < 10 || w < 3) ldsm_t(wd[j], sb + 2 * REG + 16384 + (w + (j >> 1) * 8) * 1024 + (j & 1) * 512 + (((lane & 7) >> 1) + (lane & 1) * 4 + (lane >> 4) * 8) * 32 + ((lch ^ (lane & 1)) << 4));
            else wd[j][0] = wd[j][1] = wd[j][2] = wd[j][3] = 0;
        CKP(2);
        if (!early) { mbar_wait(sb + SM_BG, 0); first_poll(); }
        float d[4][4];
        while (true) {
            unsigned m[6];
#pragma unroll
            for (int j = 0; j < 6; j++) m[j] = max(max(hv[j].x, hv[j].y), max(hv[j].z, hv[j].w));
            const bool ok = __all_sync(~0u, max(max(max(m[0], m[1]), m[2]), max(max(m[3], m[4]), m[5])) != SENT);
            if (ok)
            {
#pragma unroll
                for (int i = 0; i < 4; i++) d[0][i] = d[1][i] = d[2][i] = d[3][i] = 0.f;
#pragma unroll
                for (int j = 0; j < 6; j++) {
                    mmav(d[(2 * j) & 3], wd[2 * j], hv[j].x, hv[j].y); mmav(d[(2 * j + 1) & 3], wd[2 * j + 1], hv[j].z, hv[j].w);
                }
            }
            if (ok) break;
#pragma unroll
            for (int j = 0; j < 6; j++) if (m[j] == SENT) hv[j] = hm(j);
            if (++n > SPIN_MAX) __trap();
        }
        CKP(7); CKN(11, n + 1);
#pragma unroll
        for (int e = 0; e < 4; e++) sts32(po + (e & 1) * 80 + (e >> 1) * 32, (d[0][e] + d[1][e]) + (d[2][e] + d[3][e]));
        CKP(12);
        if (!first) bar_arrive<B_DN, NTHR>();
        else {
            bar_sync<B_DN, NTHR>();
            const float2 s = sum8(pi);
            const unsigned gw = lds32u(gi), res = lds32u(gi + 256);
            asm volatile("st.global.u32 [%0], %1;" :: "l"(op), "r"(add2(res, mul2(gw, pack2(s.x, s.y)))) : "memory");
        }
        CKP(9);
    }
    CKEND;
}

typedef CUresult (*EncodeFn)(CUtensorMap*, CUtensorMapDataType, cuuint32_t, void*, const cuuint64_t*, const cuuint64_t*, const cuuint32_t*,
                             const cuuint32_t*, CUtensorMapInterleave, CUtensorMapSwizzle, CUtensorMapL2promotion, CUtensorMapFloatOOBfill);

void make2d(EncodeFn enc, CUtensorMap* m, const void* p, int rows, int cols, int brows, int bcols, CUtensorMapSwizzle sw) {
    cuuint64_t dims[2] = {(cuuint64_t)cols, (cuuint64_t)rows}, strides[1] = {(cuuint64_t)cols * 2};
    cuuint32_t box[2] = {(cuuint32_t)bcols, (cuuint32_t)brows}, es[2] = {1, 1};
    enc(m, CU_TENSOR_MAP_DATA_TYPE_BFLOAT16, 2, (void*)p, dims, strides, box, es, CU_TENSOR_MAP_INTERLEAVE_NONE, sw,
        CU_TENSOR_MAP_L2_PROMOTION_L2_128B, CU_TENSOR_MAP_FLOAT_OOB_FILL_NONE);
}
void make5d(EncodeFn enc, CUtensorMap* m, const void* p, int rows, int cols, int d, int nb) {
    const cuuint64_t rs = (cuuint64_t)cols * 2;
    cuuint64_t dims[5] = {(cuuint64_t)cols, 4, 2, (cuuint64_t)d / 4, (cuuint64_t)rows / (2 * d)}, strides[4] = {rs, rs * d, rs * 4, rs * 2 * d};
    cuuint32_t box[5] = {16, 4, 2, (cuuint32_t)d / 4, (cuuint32_t)nb}, es[5] = {1, 1, 1, 1, 1};
    enc(m, CU_TENSOR_MAP_DATA_TYPE_BFLOAT16, 5, (void*)p, dims, strides, box, es, CU_TENSOR_MAP_INTERLEAVE_NONE, CU_TENSOR_MAP_SWIZZLE_32B,
        CU_TENSOR_MAP_L2_PROMOTION_L2_128B, CU_TENSOR_MAP_FLOAT_OOB_FILL_NONE);
}
void makekv(EncodeFn enc, CUtensorMap* m, const void* p) {
    cuuint64_t dims[3] = {64, (cuuint64_t)NB * NH * SK, 2}, strides[2] = {256, 128};
    cuuint32_t box[3] = {64, 16, 2}, es[3] = {1, 1, 1};
    enc(m, CU_TENSOR_MAP_DATA_TYPE_BFLOAT16, 3, (void*)p, dims, strides, box, es, CU_TENSOR_MAP_INTERLEAVE_NONE, CU_TENSOR_MAP_SWIZZLE_128B,
        CU_TENSOR_MAP_L2_PROMOTION_NONE, CU_TENSOR_MAP_FLOAT_OOB_FILL_NONE);
}

}

extern "C" void kernel_launch(void* const* d_in, const int* in_sizes, int n_in, void* d_out, int out_size) {
    (void)in_sizes; (void)n_in; (void)out_size;
    static EncodeFn enc = nullptr;
    static void* raw = nullptr;
    if (!enc) {
        void* fn = nullptr; cudaDriverEntryPointQueryResult qr;
        cudaGetDriverEntryPoint("cuTensorMapEncodeTiled", &fn, cudaEnableDefault, &qr);
        enc = (EncodeFn)fn;
        cudaFuncSetAttribute(fused_kernel, cudaFuncAttributeMaxDynamicSharedMemorySize, SM_TOTAL);
        cudaGetSymbolAddress(&raw, g_raw);
    }
    Params P;
    makekv(enc, &P.k, d_in[1]);
    makekv(enc, &P.v, d_in[2]);
    make2d(enc, &P.wq, d_in[3], DM, NH * DH, 64, 32, CU_TENSOR_MAP_SWIZZLE_64B);
    make2d(enc, &P.wo, d_in[4], NH * DH, DM, 32, 64, CU_TENSOR_MAP_SWIZZLE_128B);
    make2d(enc, &P.wm, d_in[10], DM, 6 * DM, 256, 8, CU_TENSOR_MAP_SWIZZLE_NONE);
    make2d(enc, &P.wn, d_in[10], DM, 6 * DM, 256, 16, CU_TENSOR_MAP_SWIZZLE_32B);
    make5d(enc, &P.wg, d_in[6], DM, FF, 16, 16 / WP);
    make5d(enc, &P.wu, d_in[7], DM, FF, 16, 16 / WP);
    make5d(enc, &P.wd, d_in[8], FF, DM, 8, 43);
    P.out = (__nv_bfloat16*)d_out; P.wdp = (const __nv_bfloat16*)d_in[8];
    typedef const __nv_bfloat16* W;
    fused_kernel<<<NCTA, NALL, SM_TOTAL>>>((W)d_in[0], (W)d_in[9], (W)d_in[1], (W)d_in[10], (W)d_in[3], (char*)(((size_t)raw + X_ALIGN - 1) & ~(size_t)(X_ALIGN - 1)), P);
}
```

```cpp
#include <cuda_runtime.h>
#include <cuda_bf16.h>
#include <cuda.h>
#include <stdint.h>

namespace {

constexpr int NB = 8, DM = 512, NH = 32, DH = 128, SK = 4096, WIN = 1024, FF = 1376;
constexpr int NCTA = 128, NTHR = 288, NALL = 320;
constexpr int NT = 16;
constexpr int NF1 = 86, DN0 = 96;
constexpr unsigned SENT = 0xFFFFFFFFu;
constexpr int SPIN_MAX = 1 << 20;

constexpr int PWIN0 = 12;
constexpr int PWIN = 16;
constexpr int PSW = 22;
constexpr int NTRK = 4;
constexpr int PFK = 3;
constexpr int QN = 6;
constexpr int TAU = 166;
constexpr int ANCH0 = 176;
constexpr int LEAD = 1650;
constexpr int PACE0 = 7000;
constexpr int PNAP = 200;
constexpr int WOA_ISSUE = 3;
constexpr int WO_GAP = 2;
constexpr int WOA_READ = 8;
constexpr int NPRE = 9;
constexpr int W0 = 900;
constexpr int WS = 180;
constexpr int WD0 = 1700;
constexpr int RT0 = 1650;
constexpr int HD0 = 1000;
constexpr int XDW = 30;
constexpr int HDW = 30;
constexpr int XC = 2;

constexpr int UNIT = 4096, REG = 8 * UNIT;
constexpr int SM_SCR = 6 * REG;
constexpr int SCR = 2048;
constexpr int SM_MN = SM_SCR + 8 * SCR;
constexpr int SM_SC = SM_MN + 8192;
constexpr int SM_BAR = SM_SC + 8192;
constexpr int SM_BM = SM_BAR + 512, SM_BT = SM_BM + 8, SM_BN = SM_BM + 16, SM_BG = SM_BM + 24;
constexpr int SM_AN = SM_BM + 32, SM_SIDE = SM_BM + 36, SM_TAG = SM_BM + 40, SM_MASK = SM_BM + 44;
constexpr int SM_ST = SM_BAR + 576;
constexpr int SM_ML = SM_ST + 512;
constexpr int SM_PR = SM_ML + 96;
constexpr int SM_TOTAL = SM_PR + 512;
constexpr int SC_M = 0, SC_Q = 256;
constexpr int SC_F1 = 0, SC_DN = 0, SC_RX = 1536;
constexpr int B_INIT = 0, B_ALL = 2, B_MOD = 3, B_WQ = 4, B_LAST = 5, B_RDY = 6, B_DN = 7, B_PRE = 8, B_FIN = 9, B_STG = 10, B_SIDE = 11, B_Q = 12, B_ML = 13;

constexpr unsigned HOME = 0xB3000;
constexpr int X_PART = 0;
constexpr int X_Q = 0x100000;
constexpr int X_M1 = 0x140000;
constexpr int X_X1 = 0x150000;
constexpr int X_HM = 0x160000;
constexpr int X_MOD = 0x170000;
constexpr int X_SIDE = 0x176000;
constexpr int X_EPOCH = 0x176400;
constexpr int X_READY = 0x176480;
constexpr int X_LAG = 0x178000;
constexpr int X_ANC = 0x158000;
constexpr int X_PRB = 0x180000;
constexpr int X_ALIGN = 0x200000;
static_assert(XC == 2, "one store writes all copies of x1");
__device__ uint4 g_raw[2 * X_ALIGN / 16];
__device__ __forceinline__ unsigned blk(unsigned base, unsigned k, unsigned s) { const unsigned o = base + k * 8192; return o + ((__popc(o & HOME) ^ s) & 1) * 4096; }

struct Params {
    CUtensorMap wm, wq, k, v, wn, wo, wg, wu, wd;
    __nv_bfloat16* out;
};

__device__ __forceinline__ uint32_t smem_u32(const void* p) { return (uint32_t)__cvta_generic_to_shared(p); }
__device__ __forceinline__ void mbar_init(uint32_t a, uint32_t c) { asm volatile("mbarrier.init.shared::cta.b64 [%0], %1;" :: "r"(a), "r"(c) : "memory"); }
__device__ __forceinline__ void mbar_expect(uint32_t a, uint32_t b) { asm volatile("mbarrier.arrive.expect_tx.shared::cta.b64 _, [%0], %1;" :: "r"(a), "r"(b) : "memory"); }
__device__ __forceinline__ void mbar_wait(uint32_t a, uint32_t par) {
    uint32_t ok; int n = 0;
    do {
        asm volatile("{\n.reg .pred p;\nmbarrier.try_wait.parity.shared::cta.b64 p, [%1], %2, 2000;\nselp.u32 %0, 1, 0, p;\n}" : "=r"(ok) : "r"(a), "r"(par) : "memory");
        if (++n > SPIN_MAX) __trap();
    } while (!ok);
}
__device__ __forceinline__ bool mbar_test(uint32_t a, uint32_t par) {
    uint32_t ok; asm volatile("{\n.reg .pred p;\nmbarrier.test_wait.parity.shared::cta.b64 p, [%1], %2;\nselp.u32 %0, 1, 0, p;\n}" : "=r"(ok) : "r"(a), "r"(par) : "memory"); return ok;
}
__device__ __forceinline__ void tma2d(uint32_t dst, const CUtensorMap* m, int x, int y, uint32_t bar) {
    asm volatile("cp.async.bulk.tensor.2d.shared::cluster.global.mbarrier::complete_tx::bytes [%0], [%1, {%3, %4}], [%2];"
                 :: "r"(dst), "l"(m), "r"(bar), "r"(x), "r"(y) : "memory");
}
__device__ __forceinline__ void tma5d(uint32_t dst, const CUtensorMap* m, int x, int y, uint32_t bar) {
    asm volatile("cp.async.bulk.tensor.5d.shared::cluster.global.mbarrier::complete_tx::bytes [%0], [%1, {%3, 0, 0, 0, %4}], [%2];"
                 :: "r"(dst), "l"(m), "r"(bar), "r"(x), "r"(y) : "memory");
}
__device__ __forceinline__ void tma_kv(uint32_t dst, const CUtensorMap* m, int row, uint32_t bar, uint64_t pol) {
    asm volatile("cp.async.bulk.tensor.3d.shared::cluster.global.mbarrier::complete_tx::bytes.L2::cache_hint [%0], [%1, {0, %3, 0}], [%2], %4;"
                 :: "r"(dst), "l"(m), "r"(bar), "r"(row), "l"(pol) : "memory");
}
__device__ __forceinline__ void pf_bulk(const void* p, uint32_t n) { asm volatile("cp.async.bulk.prefetch.L2.global [%0], %1;" :: "l"(p), "r"(n) : "memory"); }
__device__ __forceinline__ void pf_line(const void* p) { asm volatile("prefetch.global.L2 [%0];" :: "l"(p) : "memory"); }
__device__ __forceinline__ void pf_if(const void* p, unsigned i, unsigned n) { asm volatile("{\n.reg .pred p;\nsetp.lt.u32 p, %1, %2;\n@p prefetch.global.L2 [%0];\n}" :: "l"(p), "r"(i), "r"(n) : "memory"); }
__device__ __forceinline__ uint4 ldg_nc(const void* p) { uint4 v; asm volatile("ld.global.nc.v4.u32 {%0,%1,%2,%3}, [%4];" : "=r"(v.x), "=r"(v.y), "=r"(v.z), "=r"(v.w) : "l"(p)); return v; }
__device__ __forceinline__ bool elect() { uint32_t p; asm volatile("{\n.reg .pred p;\nelect.sync _|p, -1;\nselp.u32 %0, 1, 0, p;\n}" : "=r"(p)); return p; }
__device__ __forceinline__ void pf_map(const CUtensorMap* m) { asm volatile("prefetch.tensormap [%0];" :: "l"(m) : "memory"); }
__device__ __forceinline__ void ldsm(uint32_t (&r)[4], uint32_t a) {
    asm volatile("ldmatrix.sync.aligned.m8n8.x4.shared.b16 {%0,%1,%2,%3}, [%4];" : "=r"(r[0]), "=r"(r[1]), "=r"(r[2]), "=r"(r[3]) : "r"(a) : "memory");
}
__device__ __forceinline__ void ldsm_t(uint32_t (&r)[4], uint32_t a) {
    asm volatile("ldmatrix.sync.aligned.m8n8.x4.trans.shared.b16 {%0,%1,%2,%3}, [%4];" : "=r"(r[0]), "=r"(r[1]), "=r"(r[2]), "=r"(r[3]) : "r"(a) : "memory");
}
__device__ __forceinline__ void mma(float (&c)[4], uint32_t a0, uint32_t a1, uint32_t a2, uint32_t a3, uint32_t b0, uint32_t b1) {
    asm("mma.sync.aligned.m16n8k16.row.col.f32.bf16.bf16.f32 {%0,%1,%2,%3}, {%4,%5,%6,%7}, {%8,%9}, {%0,%1,%2,%3};"
        : "+f"(c[0]), "+f"(c[1]), "+f"(c[2]), "+f"(c[3]) : "r"(a0), "r"(a1), "r"(a2), "r"(a3), "r"(b0), "r"(b1));
}
__device__ __forceinline__ void mma(float (&c)[4], const uint32_t (&a)[4], uint32_t b0, uint32_t b1) { mma(c, a[0], a[1], a[2], a[3], b0, b1); }
__device__ __forceinline__ void mmav(float (&c)[4], const uint32_t (&a)[4], uint32_t b0, uint32_t b1) {
    asm volatile("mma.sync.aligned.m16n8k16.row.col.f32.bf16.bf16.f32 {%0,%1,%2,%3}, {%4,%5,%6,%7}, {%8,%9}, {%0,%1,%2,%3};"
        : "+f"(c[0]), "+f"(c[1]), "+f"(c[2]), "+f"(c[3]) : "r"(a[0]), "r"(a[1]), "r"(a[2]), "r"(a[3]), "r"(b0), "r"(b1));
}
__device__ __forceinline__ uint32_t pin(uint32_t v) { asm volatile("shfl.sync.bfly.b32 %0, %0, 0, 31, -1;" : "+r"(v)); return v; }
template <class T> __device__ __forceinline__ T* pin(T* p) { const size_t a = (size_t)p; return (T*)(pin((uint32_t)a) | (size_t)pin((uint32_t)(a >> 32)) << 32); }
__device__ __forceinline__ uint32_t movm(uint32_t a) { uint32_t r; asm volatile("movmatrix.sync.aligned.m8n8.trans.b16 %0, %1;" : "=r"(r) : "r"(a)); return r; }
__device__ __forceinline__ uint32_t pack2(float lo, float hi) { uint32_t r; asm("cvt.rn.bf16x2.f32 %0, %1, %2;" : "=r"(r) : "f"(hi), "f"(lo)); return r; }
__device__ __forceinline__ float blo(uint32_t w) { return __uint_as_float(w << 16); }
__device__ __forceinline__ float bhi(uint32_t w) { return __uint_as_float(w & 0xFFFF0000u); }
__device__ __forceinline__ float rbf(float x) { return blo(pack2(x, 0.f)); }
__device__ __forceinline__ uint32_t add2(uint32_t a, uint32_t b) { uint32_t r; asm("add.rn.bf16x2 %0, %1, %2;" : "=r"(r) : "r"(a), "r"(b)); return r; }
__device__ __forceinline__ uint32_t sub2(uint32_t a, uint32_t b) { uint32_t r; asm("sub.rn.bf16x2 %0, %1, %2;" : "=r"(r) : "r"(a), "r"(b)); return r; }
__device__ __forceinline__ uint32_t mul2(uint32_t a, uint32_t b) { uint32_t r; asm("mul.rn.bf16x2 %0, %1, %2;" : "=r"(r) : "r"(a), "r"(b)); return r; }
constexpr uint32_t ONE2 = 0x3F803F80u;
__device__ __forceinline__ float ex2(float x) { float y; asm("ex2.approx.ftz.f32 %0, %1;" : "=f"(y) : "f"(x)); return y; }
__device__ __forceinline__ uint4 ldg_rlx128(const void* p) {
    uint4 v; asm volatile("ld.relaxed.gpu.global.v4.u32 {%0,%1,%2,%3}, [%4];" : "=r"(v.x), "=r"(v.y), "=r"(v.z), "=r"(v.w) : "l"(p) : "memory"); return v;
}
__device__ __forceinline__ uint4 ldg_rlx2x64(const void* p) {
    unsigned long long a, b; asm volatile("ld.relaxed.gpu.global.v2.u64 {%0,%1}, [%2];" : "=l"(a), "=l"(b) : "l"(p) : "memory");
    return make_uint4((unsigned)a, (unsigned)(a >> 32), (unsigned)b, (unsigned)(b >> 32));
}
__device__ __forceinline__ uint2 ldg_rlx64(const void* p) {
    unsigned long long a; asm volatile("ld.relaxed.gpu.global.u64 %0, [%1];" : "=l"(a) : "l"(p) : "memory"); return make_uint2((unsigned)a, (unsigned)(a >> 32));
}
__device__ __forceinline__ unsigned ldg_acq32(const void* p) { unsigned v; asm volatile("ld.acquire.gpu.global.u32 %0, [%1];" : "=r"(v) : "l"(p) : "memory"); return v; }
__device__ __forceinline__ void red_add(void* p, unsigned v) { asm volatile("red.relaxed.gpu.global.add.u32 [%0], %1;" :: "l"(p), "r"(v) : "memory"); }
__device__ __forceinline__ unsigned now_ns() { unsigned t; asm volatile("mov.u32 %0, %%globaltimer_lo;" : "=r"(t)); return t; }
__device__ __forceinline__ void nap(unsigned ns) { asm volatile("nanosleep.u32 %0;" :: "r"(ns)); }
__device__ __forceinline__ unsigned ldg_rlx32(const void* p) { unsigned v; asm volatile("ld.relaxed.gpu.global.u32 %0, [%1];" : "=r"(v) : "l"(p) : "memory"); return v; }
__device__ __forceinline__ void stg_rlx32(void* p, unsigned v) { asm volatile("st.relaxed.gpu.global.u32 [%0], %1;" :: "l"(p), "r"(v) : "memory"); }
__device__ __forceinline__ void stg_rlx16(void* p, unsigned v) { asm volatile("st.relaxed.gpu.global.u16 [%0], %1;" :: "l"(p), "h"((unsigned short)v) : "memory"); }
__device__ __forceinline__ uint4 ldg_b128(const void* p) {
    unsigned long long a, b; asm volatile("{\n.reg .b128 x;\nld.relaxed.gpu.global.b128 x, [%2];\nmov.b128 {%0,%1}, x;\n}" : "=l"(a), "=l"(b) : "l"(p) : "memory");
    return make_uint4((unsigned)a, (unsigned)(a >> 32), (unsigned)b, (unsigned)(b >> 32));
}
__device__ __forceinline__ void stg_b128(void* p, uint4 v) {
    asm volatile("{\n.reg .b128 x;\nmov.b128 x, {%1,%2};\nst.relaxed.gpu.global.b128 [%0], x;\n}" :: "l"(p), "l"(v.x | ((unsigned long long)v.y << 32)), "l"(v.z | ((unsigned long long)v.w << 32)) : "memory");
}
__device__ __forceinline__ int rowoff(int b, int c) { return ((c >> 6) * 2 + ((c >> 2) & 1)) * 512 + b * 64 + (c & 3) * 16 + ((c >> 3) & 1) * 8 + ((c >> 5) & 1) * 4 + ((c >> 4) & 1) * 2; }
__device__ __forceinline__ void stg_rlx64(void* p, unsigned lo, unsigned hi) {
    unsigned long long a = lo | ((unsigned long long)hi << 32); asm volatile("st.relaxed.gpu.global.u64 [%0], %1;" :: "l"(p), "l"(a) : "memory");
}
__device__ __forceinline__ void stg_rlx128(void* p, uint4 v) { asm volatile("st.relaxed.gpu.global.v4.u32 [%0], {%1,%2,%3,%4};" :: "l"(p), "r"(v.x), "r"(v.y), "r"(v.z), "r"(v.w) : "memory"); }
__device__ __forceinline__ void sts32u(uint32_t a, unsigned x) { asm volatile("st.volatile.shared.u32 [%0], %1;" :: "r"(a), "r"(x) : "memory"); }
__device__ __forceinline__ unsigned lds32u(uint32_t a) { unsigned v; asm volatile("ld.volatile.shared.u32 %0, [%1];" : "=r"(v) : "r"(a) : "memory"); return v; }
__device__ __forceinline__ void spin(unsigned c0, unsigned d) { if (d) while ((unsigned)clock() - c0 < d) {} }
__device__ __forceinline__ void fence_gpu() { asm volatile("fence.acq_rel.gpu;" ::: "memory"); }
__device__ __forceinline__ bool valid4(const uint4& v) { return max(max(v.x, v.y), max(v.z, v.w)) != SENT; }
template <int ID, int N> __device__ __forceinline__ void bar_sync() { asm volatile("bar.sync %0, %1;" :: "n"(ID), "n"(N) : "memory"); }
template <int ID, int N> __device__ __forceinline__ void bar_arrive() { asm volatile("bar.arrive %0, %1;" :: "n"(ID), "n"(N) : "memory"); }
__device__ __forceinline__ void sts64(uint32_t a, float x, float y) { asm volatile("st.shared.v2.f32 [%0], {%1,%2};" :: "r"(a), "f"(x), "f"(y) : "memory"); }
__device__ __forceinline__ void sts128(uint32_t a, uint4 v) { asm volatile("st.volatile.shared.v4.u32 [%0], {%1,%2,%3,%4};" :: "r"(a), "r"(v.x), "r"(v.y), "r"(v.z), "r"(v.w) : "memory"); }
__device__ __forceinline__ void sts128f(uint32_t a, float x, float y, float z, float w) { asm volatile("st.volatile.shared.v4.f32 [%0], {%1,%2,%3,%4};" :: "r"(a), "f"(x), "f"(y), "f"(z), "f"(w) : "memory"); }
__device__ __forceinline__ void sts32(uint32_t a, float x) { asm volatile("st.shared.f32 [%0], %1;" :: "r"(a), "f"(x) : "memory"); }
__device__ __forceinline__ float2 lds64(uint32_t a) { float2 v; asm volatile("ld.shared.v2.f32 {%0,%1}, [%2];" : "=f"(v.x), "=f"(v.y) : "r"(a) : "memory"); return v; }
__device__ __forceinline__ float lds32(uint32_t a) { float v; asm volatile("ld.shared.f32 %0, [%1];" : "=f"(v) : "r"(a) : "memory"); return v; }
__device__ __forceinline__ float4 lds128(uint32_t a) { float4 v; asm volatile("ld.shared.v4.f32 {%0,%1,%2,%3}, [%4];" : "=f"(v.x), "=f"(v.y), "=f"(v.z), "=f"(v.w) : "r"(a) : "memory"); return v; }
__device__ __forceinline__ float2 sum8(uint32_t a) {
    float2 v[8];
#pragma unroll
    for (int i = 0; i < 8; i++) v[i] = lds64(a + i * SCR);
    return make_float2(((v[0].x + v[1].x) + (v[2].x + v[3].x)) + ((v[4].x + v[5].x) + (v[6].x + v[7].x)),
                       ((v[0].y + v[1].y) + (v[2].y + v[3].y)) + ((v[4].y + v[5].y) + (v[6].y + v[7].y)));
}
template <int STRIDE> __device__ __forceinline__ float4 sum8x4(uint32_t a) {
    float4 v[8];
#pragma unroll
    for (int i = 0; i < 8; i++) v[i] = lds128(a + i * STRIDE);
    return make_float4(((v[0].x + v[1].x) + (v[2].x + v[3].x)) + ((v[4].x + v[5].x) + (v[6].x + v[7].x)), ((v[0].y + v[1].y) + (v[2].y + v[3].y)) + ((v[4].y + v[5].y) + (v[6].y + v[7].y)),
                       ((v[0].z + v[1].z) + (v[2].z + v[3].z)) + ((v[4].z + v[5].z) + (v[6].z + v[7].z)), ((v[0].w + v[1].w) + (v[2].w + v[3].w)) + ((v[4].w + v[5].w) + (v[6].w + v[7].w)));
}
__device__ __forceinline__ float rcp(float x) { float y; asm("rcp.approx.ftz.f32 %0, %1;" : "=f"(y) : "f"(x)); return y; }
__device__ __forceinline__ float sigmoid_f(float x) { return rcp(1.0f + ex2(x * -1.4426950408889634f)); }
__device__ __forceinline__ uint32_t silu2(uint32_t c) { const float a = blo(c), b = bhi(c); return pack2(a * sigmoid_f(a), b * sigmoid_f(b)); }
__device__ __forceinline__ void ln_consts(float mean, float var, uint32_t& mu2, float& rs) {
    mu2 = pack2(mean, mean);
    float sd; asm("sqrt.approx.ftz.f32 %0, %1;" : "=f"(sd) : "f"(rbf(rbf(var) + 1e-5f)));
    rs = rcp(rbf(sd));
}
__device__ __forceinline__ uint32_t ln_norm(uint32_t x2, uint32_t mu2, float rs) { const uint32_t d = sub2(x2, mu2); return pack2(blo(d) * rs, bhi(d) * rs); }

__global__ void __launch_bounds__(NALL, 1) fused_kernel(const __nv_bfloat16* const px, const __nv_bfloat16* const pc, const __nv_bfloat16* const pk, const __nv_bfloat16* const pwm,
                                                        const __nv_bfloat16* const pwq, char* const X, const __grid_constant__ Params P) {
    extern __shared__ __align__(1024) unsigned char smem[];
    const uint32_t sb = smem_u32(smem);
    const int tid = threadIdx.x, w = tid >> 5, lane = tid & 31, g = lane >> 2, t = lane & 3;
    const int cta = blockIdx.x, head = cta >> 2, bat = (cta & 3) * 2 + (w >> 2);
    const uint32_t s0 = sb + w * UNIT, s2 = s0 + 4 * REG;
    const uint32_t bar0 = sb + SM_BAR + w * 64;
    const uint32_t barC = bar0 + 32;
    const uint32_t scr = sb + SM_SCR, myscr = scr + w * SCR;
    pf_if((const char*)pwm + ((cta * 4 + (tid >> 4)) * (6 * DM * 2) + (tid & 15) * 128), w, 2);
    pf_if((const char*)pk + (unsigned)(((((cta & 3) * 2 + (w & 1)) * NH + head) * SK + (SK - WIN - 16) + (w >> 1) * 16) * (DH * 2) + lane * 128), w - 2, PFK);
    const int rid = !(cta & 1) ? cta >> 1 : (cta >> 2) + (cta & 2 ? 64 : 96);
    const unsigned t_start = now_ns();
    uint64_t pol;
    asm volatile("createpolicy.fractional.L2::evict_first.b64 %0, 1.0;" : "=l"(pol));
    auto go_first = [&](uint32_t wbar, uint32_t par) {
        for (int n = 0;; n++) {
            if (mbar_test(wbar, par)) return false;
            if (mbar_test(sb + SM_BG, 0)) return true;
            if (n > SPIN_MAX * 4) __trap();
            nap(20);
        }
    };
    if (w == 9) {
        const uint32_t sl = sb + SM_PR + lane * 16;
        char* const pl = X + blk(X_PRB, cta >> 1, lane & 1) + (lane >> 1) * 256 + (cta & 1) * 128;
        {
            char* const ps = X + X_PRB + (cta >> 1) * 8192 + g * 256 + (cta & 1) * 128 + t * 16;
            sts32u(sl, 0);
#pragma unroll
            for (int i = 0; i < 4; i++) stg_rlx128(ps + i * 2048, make_uint4(1, 1, 1, 1));
            __syncwarp();
        }
        unsigned v; asm volatile("atom.relaxed.gpu.global.add.u32 %0, [%1], 1;" : "=r"(v) : "l"(pl) : "memory");
        unsigned tag = ldg_rlx32(X + X_EPOCH);
        if (lane == 0) pf_bulk(pwq + (size_t)cta * QN * 1024, QN * 2048);
        if (lane == 0) sts32u(sb + SM_AN, t_start + ANCH0);
        if (lane < 8) sts32u(sb + SM_BAR + lane * 64 + 56, 0);
        unsigned side;
        {
            int d, n = 0;
#pragma unroll 1
            for (int r = 0; r < 4; r++) {
                if (v == SENT) __trap();
                asm volatile("cp.async.cg.shared.global [%0], [%1], 16;" :: "r"(sl), "l"(pl) : "memory");
                unsigned m;
                do {
                    m = __ballot_sync(~0u, lds32u(sl));
                    d = __popc(m & 0xAAAAAAAAu) - __popc(m & 0x55555555u);
                    if (++n > SPIN_MAX) __trap();
                } while (abs(d) < 6 && m != ~0u);
                if (abs(d) >= 6) break;
                asm volatile("cp.async.wait_all;" ::: "memory");
                sts32u(sl, 0);
                asm volatile("atom.relaxed.gpu.global.add.u32 %0, [%1], 1;" : "=r"(v) : "l"(pl) : "memory");
            }
            side = d > 0;
            tag++;
            if (lane == 0) { sts32u(sb + SM_SIDE, side); sts32u(sb + SM_TAG, tag); }
            bar_arrive<B_SIDE, NTHR>();
        }
        asm volatile("cp.async.wait_all;" ::: "memory");
        while (now_ns() - t_start < PACE0) nap(200);
        for (int n = 0; n < SPIN_MAX; n++) {
            const uint32_t wb = sb + SM_BAR + (lane & 7) * 64;
            const unsigned seen = lds32u(wb + 56), u = seen + ((lane >> 3) & 1), t1 = now_ns();
            const unsigned more = mbar_test(wb + (u < 6 ? u : (~u & 2) + (u & 1)) * 8, u < 6 ? 0 : ((u - 2) >> 2) & 1);
            const unsigned lo = __reduce_min_sync(~0u, seen), sum = __reduce_add_sync(~0u, lane < 8 ? seen + more : lane < 16 ? more : 0);
            if (lo == 30) break;
            if (lo && lane < 2) stg_rlx64(X + X_LAG + (cta >> 5) * 8192 + lane * 4096 + (cta & 31) * 128, t1 - sum * TAU, tag);
            uint2 a = make_uint2(0, 0);
            if (cta == 0) {
                uint2 u[4];
#pragma unroll
                for (int i = 0; i < 4; i++) u[i] = ldg_rlx64(X + blk(X_LAG, i, side) + lane * 128);
                const int s = __reduce_add_sync(~0u, (int)(u[0].x + u[1].x + u[2].x + u[3].x - 4 * t_start));
                if (__all_sync(~0u, (u[0].y == tag) & (u[1].y == tag) & (u[2].y == tag) & (u[3].y == tag)) && lane < 2) {
                    a = make_uint2(t_start + s / NCTA, tag);
                    stg_rlx64(X + X_ANC + lane * 4096, a.x, tag);
                }
            } else if (lane == 0) a = ldg_rlx64(X + blk(X_ANC, 0, side));
            if (lane == 0 && a.y == tag) sts32u(sb + SM_AN, a.x - LEAD);
            __syncwarp();
            nap(PNAP);
        }
        {
            bar_sync<B_ML, NTHR>();
            const float2 ml = lds64(sb + SM_ML + (lane & 7) * 8);
            float M = fmaxf(ml.x, __shfl_xor_sync(~0u, ml.x, 1)); M = fmaxf(M, __shfl_xor_sync(~0u, M, 2));
            const float e = ex2((ml.x - M) * 1.4426950408889634f);
            float L = e * ml.y; L += __shfl_xor_sync(~0u, L, 1); L += __shfl_xor_sync(~0u, L, 2);
            if (lane < 8) sts32(sb + SM_ML + 64 + lane * 4, e * rcp(L));
        }
        bar_arrive<B_RDY, NALL>();
        bar_sync<B_STG, 64>();
        {
            const char* const pp = pin(X + blk(X_PART, cta, side) + lane * 16);
            char* const xo = pin(X + (lane >> 4) * 16384 + blk(X_X1, (cta >> 3) & 1, lane >> 3) + (cta & 7) * 512 + (cta >> 4) * 64 + (lane & 7) * 8);
            const float4 gx = lds128(scr + SC_RX + (lane & 7) * 16);
            const unsigned t0 = lds32u(sb + SM_AN) + 256 * TAU + RT0 + (cta & 7) * (TAU / 8);
            while ((int)(now_ns() - t0) < 0) nap(20);
            uint4 v[8]; int n = 0;
            float a[4];
#pragma unroll
            for (int j = 0; j < 8; j++) v[j] = ldg_b128(pp + j * 512);
            while (true) {
#define RSUM(f) (((__uint_as_float(v[0].f) + __uint_as_float(v[1].f)) + (__uint_as_float(v[2].f) + __uint_as_float(v[3].f))) + ((__uint_as_float(v[4].f) + __uint_as_float(v[5].f)) + (__uint_as_float(v[6].f) + __uint_as_float(v[7].f))))
                const bool ok = __all_sync(~0u, max(max(max(v[0].x, v[1].x), max(v[2].x, v[3].x)), max(max(v[4].x, v[5].x), max(v[6].x, v[7].x))) != SENT);
                a[0] = RSUM(x); a[1] = RSUM(y); a[2] = RSUM(z); a[3] = RSUM(w);
                asm volatile("" : "+f"(a[0]), "+f"(a[1]), "+f"(a[2]), "+f"(a[3]));
                if (ok) break;
#pragma unroll
                for (int j = 0; j < 8; j++) if (v[j].x == SENT) v[j] = ldg_b128(pp + j * 512);
                if (++n > SPIN_MAX) __trap();
            }
#pragma unroll
            for (int i = 0; i < 4; i++) a[i] += __shfl_xor_sync(~0u, a[i], 8);
#pragma unroll
            for (int i = 0; i < 4; i++) a[i] += __shfl_xor_sync(~0u, a[i], 16);
            stg_rlx64(xo, add2(__float_as_uint(gx.z), mul2(__float_as_uint(gx.x), pack2(a[0], a[1]))), add2(__float_as_uint(gx.w), mul2(__float_as_uint(gx.y), pack2(a[2], a[3]))));
        }
        if (rid >= DN0) {
            const unsigned c1 = clock();
            const int f = rid - DN0;
            const char* const rp = X + (rid & (XC - 1)) * 16384 + blk(X_X1, f >> 4, side) + (rowoff(g, f * 16 + t * 4) & 4092);
            unsigned r[4]; int n = 0;
            spin(c1, HD0 - 450);
            do {
#pragma unroll
                for (int i = 0; i < 4; i++) r[i] = ldg_rlx32(rp + i * 16);
                if (++n > SPIN_MAX) __trap();
            } while (max(max(r[0], r[1]), max(r[2], r[3])) == SENT);
            const unsigned sel = (f & 1) ? 0x7632 : 0x5410;
            sts64(sb + SM_MN + 256 + lane * 8, __uint_as_float(__byte_perm(r[0], r[1], sel)), __uint_as_float(__byte_perm(r[2], r[3], sel)));
            __syncwarp();
            spin(c1, HD0);
        }
        if (lane == 0) asm volatile("mbarrier.arrive.shared::cta.b64 _, [%0];" :: "r"(sb + SM_BG) : "memory");
    } else if (w == 8) {
        const int row0 = ((cta & 3) * 2 * NH + head) * SK + (SK - WIN);
        auto kv_unit = [&](int u) {
            const uint32_t b = sb + SM_BAR + (u & 7) * 64 + (u >> 3) * 8;
            mbar_expect(b, UNIT);
            tma_kv(sb + (u >> 3) * REG + (u & 7) * UNIT, (u & 8) ? &P.v : &P.k, row0 + ((u >> 2) & 1) * NH * SK + (u & 3) * 16 + (u >> 4) * 64, b, pol);
        };
        if (elect()) {
            mbar_init(sb + SM_BM, 1);
#pragma unroll
            for (int i = 0; i < 8; i++) mbar_init(sb + SM_BAR + i * 64 + 48, 1);
            asm volatile("fence.mbarrier_init.release.cluster;" ::: "memory");
            mbar_expect(sb + SM_BM, 512 * 16);
            tma2d(sb + 4 * REG, &P.wm, cta * 8, 0, sb + SM_BM); tma2d(sb + 4 * REG + 256 * 16, &P.wm, cta * 8, 256, sb + SM_BM);
#pragma unroll
            for (int i = 0; i < 8; i++) { const uint32_t b = sb + SM_BAR + i * 64 + 48; mbar_expect(b, UNIT); tma2d(sb + 5 * REG + i * UNIT, &P.wq, cta * 32, i * 64, b); }
            mbar_init(sb + SM_BN, 1); mbar_init(sb + SM_BT, 1); mbar_init(sb + SM_BG, 1);
#pragma unroll
            for (int i = 0; i < 48; i++) mbar_init(sb + SM_BAR + (i & 7) * 64 + (i >> 3) * 8, 1);
            asm volatile("fence.mbarrier_init.release.cluster;" ::: "memory");
        }
        __syncwarp();
        bar_arrive<B_INIT, NTHR>();
        {
            uint32_t mine = lane >= NTRK ? 0 : lane < 8 ? sb + SM_BAR + lane * 64 + 48 : sb + SM_BM;
            int next = 0, lim = 32, n = 0;
            while (next < 48) {
                const bool idle = lane < (next < PSW ? PWIN0 : PWIN) && (mine == 0 || mbar_test(mine, 0));
                const unsigned m = __ballot_sync(~0u, idle);
                const int u = next + __popc(m & ((1u << lane) - 1));
                if (idle) {
                    mine = 0;
                    if (u < lim) { kv_unit(u); mine = sb + SM_BAR + (u & 7) * 64 + (u >> 3) * 8; }
                }
                next = min(next + __popc(m), lim);
                if (next == lim) {
                    if (lim == 32) { bar_sync<B_MOD, NTHR>(); } else if (lim == 40) { bar_sync<B_WQ, NTHR>(); }
                    lim += 8;
                }
                if (!m) nap(30);
                if (++n > SPIN_MAX) __trap();
            }
        }
        if (lane < 5) pf_map(&P.wn + lane);
        float m[4][4] = {};
        auto late_mod = [&](uint32_t a, int h) {
            const int lrow = (lane & 7) + ((lane >> 4) << 3), lch = (lane >> 3) & 1;
            const uint32_t a0 = a + lrow * 32 + ((lch ^ ((lrow >> 2) & 1)) << 4);
            const uint32_t c0 = sb + SM_SC + h * 4096 + (lane & 7) * 128 + (((lane >> 3) ^ (lane & 7)) << 4);
#pragma unroll
            for (int j = 0; j < 8; j++) {
                uint32_t c[4], r[4], u[4];
                ldsm(c, (c0 + (j >> 1) * 1024) ^ ((j & 1) << 6)); ldsm_t(r, a0 + j * 1024); ldsm_t(u, a0 + j * 1024 + 512);
                mma(m[(j & 1) * 2], r, c[0], c[1]); mma(m[(j & 1) * 2 + 1], u, c[2], c[3]);
            }
        };
        if (rid < 96) {
#pragma unroll 1
            for (int h = 0; h < 2; h++) {
                if (lane == 0) { mbar_expect(sb + SM_BN, 8192); tma2d(sb + SM_MN, &P.wn, 2 * DM + rid * 16, h * 256, sb + SM_BN); }
                mbar_wait(sb + SM_BN, h);
                late_mod(sb + SM_MN, h);
                asm volatile("" :: "f"(m[0][0]), "f"(m[1][0]), "f"(m[2][0]), "f"(m[3][0]) : "memory");
                __syncwarp();
            }
#pragma unroll
            for (int e = 0; e < 4; e++) {
                float v = rbf((m[0][e] + m[1][e]) + (m[2][e] + m[3][e]));
                if (rid >= 64) v += 1.0f;
                stg_rlx16(X + X_MOD + (rid >> 5) * 8192 + rowoff(2 * t + (e & 1), (rid & 31) * 16 + g + (e >> 1) * 8), pack2(v, 0.f));
            }
        }
        {
            const unsigned side = lds32u(sb + SM_SIDE);
#pragma unroll
            for (int i = 0; i < 8; i++) stg_rlx128(X + blk(X_PART, cta, side) + i * 512 + lane * 16, make_uint4(SENT, SENT, SENT, SENT));
            if (lane == 0) stg_rlx32(X + X_SIDE + cta * 4, side);
        }
        bar_sync<B_Q, NTHR>();
        if (lane == 0) {
            const unsigned tag = lds32u(sb + SM_TAG);
            fence_gpu();
            red_add(X + X_READY, 1);
            int n = 0;
            while ((int)(ldg_acq32(X + X_READY) - tag * NCTA) < 0) { nap(1000); if (++n > SPIN_MAX) __trap(); }
            if (cta == 0) stg_rlx32(X + X_EPOCH, tag);
        }
        __syncwarp();
        {
            stg_rlx128(X + blk(X_Q, head >> 1, 0) + (head & 1) * 2048 + g * 256 + (cta & 3) * 64 + t * 16, make_uint4(0, 0, 0, 0));
            stg_rlx128(X + blk(X_Q, head >> 1, 1) + (head & 1) * 2048 + g * 256 + (cta & 3) * 64 + t * 16, make_uint4(0, 0, 0, 0));
            stg_rlx64(X + blk(X_M1, cta >> 5, lane >> 4) + (cta & 31) * 128 + (lane & 15) * 8, 0, 0);
            const int wt = (cta & 3) * 32 + lane;
            const unsigned mask = __ballot_sync(~0u, blk(X_PART, wt, ldg_rlx32(X + X_SIDE + wt * 4)) & 4096);
            if (lane == 0) sts32u(sb + SM_MASK, mask);
            if (lane < 8) {
                const int task = cta;
                const int rb = task >> 4, c = ((task & 15) >> 1) * 64 + (task & 1) * 4 + ((lane & 7) >> 1) + (lane & 1) * 8;
                const uint2 ga = ldg_rlx64(X + X_MOD + rowoff(rb, c));
                const unsigned short* const xp = (const unsigned short*)px + rb * DM + c;
                sts128(scr + (lane >> 3) * SCR + SC_RX + (lane & 7) * 16, make_uint4(ga.x, ga.y, xp[0] | (xp[16] << 16), xp[32] | (xp[48] << 16)));
            }
            if (rid < NF1) {
#pragma unroll 1
                for (int i = 0; i < 4; i++) {
                    uint4 v[8];
#pragma unroll
                    for (int j = 0; j < 8; j++) v[j] = ldg_rlx128(X + X_MOD + 8192 + (i * 8 + j) * 512 + lane * 16);
#pragma unroll
                    for (int j = 0; j < 8; j++) sts128(sb + SM_MN + (i * 8 + j) * 512 + lane * 16, v[j]);
                }
            }
        }
        bar_arrive<B_RDY, NALL>();
        bar_arrive<B_STG, 64>();
        unsigned t_ref = 0;
        auto until = [&](int x) { while ((int)(now_ns() - t_ref) < x) nap(20); };
        if (elect()) {
#pragma unroll 1
            for (int i = 0; i < 8; i++) { int n = 0; while (lds32u(sb + SM_BAR + i * 64 + 56) < 30) { nap(100); if (++n > SPIN_MAX) __trap(); } }
            t_ref = lds32u(sb + SM_AN) + 256 * TAU + (cta & 7) * (TAU / 8);
            if (rid < NF1) {
#pragma unroll
                for (int i = 0; i < 4; i++) mbar_expect(sb + SM_BAR + i * 64 + 48, 2 * UNIT);
#pragma unroll 1
                for (int i = 0; i < 4; i++) {
                    const uint32_t b = sb + SM_BAR + i * 64 + 48;
                    until(W0 + i * WS);
                    tma5d(sb + 2 * REG + i * UNIT, &P.wg, rid * 16, i * 4, b); tma5d(sb + 2 * REG + 16384 + i * UNIT, &P.wu, rid * 16, i * 4, b);
                }
            }
        }
        if (rid >= DN0) {
            bar_sync<B_LAST, NTHR>();
            if (elect()) {
                mbar_expect(sb + SM_BN, 16384); mbar_expect(sb + SM_BT, FF * 32);
                until(WD0);
                tma5d(sb + 2 * REG + 16384, &P.wd, (rid - DN0) * 16, 0, sb + SM_BT); tma5d(sb + 2 * REG + 16384 + 43 * 512, &P.wd, (rid - DN0) * 16, 43, sb + SM_BT);
                tma2d(sb + 2 * REG, &P.wn, 2 * DM + rid * 16, 0, sb + SM_BN); tma2d(sb + 2 * REG + 8192, &P.wn, 2 * DM + rid * 16, 256, sb + SM_BN);
            }
        }
        __syncwarp();
        if (rid >= DN0) {
            mbar_wait(sb + SM_BN, 0);
            late_mod(sb + 2 * REG, 0); late_mod(sb + 2 * REG + 8192, 1);
#pragma unroll
            for (int e = 0; e < 2; e++)
                sts32u(sb + SM_MN + g * 32 + e * 16 + t * 4, movm(pack2((m[0][2 * e] + m[1][2 * e]) + (m[2][2 * e] + m[3][2 * e]), (m[0][2 * e + 1] + m[1][2 * e + 1]) + (m[2][2 * e + 1] + m[3][2 * e + 1]))));
            bar_arrive<B_DN, NTHR>();
        }
    }
    if (w >= 8) {
        if (rid < NF1) {
            const int b = (tid - 256) >> 3, c = tid & 7;
            char* const ho = pin(X + X_HM + (rid >> 4) * 8192 + ((rid >> 1) & 7) * 512 + b * 64 + (c & 3) * 16 + (rid & 1) * 8 + (c >> 2) * 4);
            const uint32_t pi = pin(scr + SC_F1 + c * 144 + b * 16), si = pin(sb + SM_ST + b * 64);
            bar_sync<B_PRE, NALL>();
            const float4 C = sum8x4<UNIT>(sb + REG + c * 144 + b * 16), S = sum8x4<UNIT>(sb + REG + 1152 + c * 144 + b * 16);
            sts128f(sb + SM_PR + lane * 16, C.x, C.y, C.z, C.w); sts128f(sb + SM_PR + lane * 16, S.x, S.y, S.z, S.w);
            sts128(sb + SM_PR + lane * 16, make_uint4(pi, si, (uint32_t)(size_t)ho, (uint32_t)((size_t)ho >> 32)));
            bar_sync<B_FIN, NALL>();
            const float4 s0_ = lds128(si), s1_ = lds128(si + 16), s2_ = lds128(si + 32), s3_ = lds128(si + 48);
            const float4 p = sum8x4<SCR>(pi);
            const float mean = (((s0_.x + s0_.z) + (s1_.x + s1_.z)) + ((s2_.x + s2_.z) + (s3_.x + s3_.z))) * (1.0f / DM);
            const float sq = (((s0_.y + s0_.w) + (s1_.y + s1_.w)) + ((s2_.y + s2_.w) + (s3_.y + s3_.w))) * (1.0f / DM);
            float rs; asm("rsqrt.approx.ftz.f32 %0, %1;" : "=f"(rs) : "f"(fmaxf(sq - mean * mean, 0.f) + 1e-5f));
            const float g0 = rs * (p.x - mean * C.x) + S.x, g1 = rs * (p.y - mean * C.y) + S.y, u0 = rs * (p.z - mean * C.z) + S.z, u1 = rs * (p.w - mean * C.w) + S.w;
            const unsigned hw = pack2(sigmoid_f(g0) * u0, sigmoid_f(g1) * u1);
            stg_rlx32(ho, hw); stg_rlx32(ho + 4096, hw);
        }
        return;
    }
    const unsigned ce = (lane >> 3) * (DM * 2) + w * 128 + (lane & 7) * 16;
    const uint4 ca = ldg_nc((const char*)pc + ce), cb = ldg_nc((const char*)pc + ce + 4 * DM * 2);
    const uint4 xa = ldg_nc((const char*)px + w * (DM * 2) + lane * 16), xb = ldg_nc((const char*)px + w * (DM * 2) + lane * 16 + 512);
    const uint4 xc = ldg_nc((const char*)px + ce), xd = ldg_nc((const char*)px + ce + 4 * DM * 2);
    if (w >= 4) pf_map(&P.wm + (w & 3));
    char* const qout = X + blk(X_Q, head >> 1, tid >> 7) + (head & 1) * 2048 + ((tid >> 4) & 7) * 256 + (cta & 3) * 64 + (tid & 3) * 16 + ((tid >> 2) & 3) * 4;
    char* const mout = X + blk(X_M1, cta >> 5, w) + (cta & 31) * 128 + lane * 4;
    stg_rlx32(qout, 0);
    if (w < 2) stg_rlx32(mout, 0);
    uint32_t sc[8], xf[8];
    {
        const uint32_t a = (lane >> 3) * 128 + (((lane & 7) ^ (lane >> 3)) << 4), b = (lane & 7) * 128 + (((lane >> 3) ^ (lane & 7)) << 4);
        const uint32_t cs = sb + SM_SC + w * 1024;
        sts128(cs + a, make_uint4(silu2(ca.x), silu2(ca.y), silu2(ca.z), silu2(ca.w)));
        sts128(cs + 512 + (a ^ 64), make_uint4(silu2(cb.x), silu2(cb.y), silu2(cb.z), silu2(cb.w)));
        sts128(myscr + a, xc); sts128(myscr + 512 + (a ^ 64), xd);
        __syncwarp();
        ldsm(*(uint32_t(*)[4])&sc[0], cs + b); ldsm(*(uint32_t(*)[4])&sc[4], cs + (b ^ 64));
        ldsm(*(uint32_t(*)[4])&xf[0], myscr + b); ldsm(*(uint32_t(*)[4])&xf[4], myscr + (b ^ 64));
        __syncwarp();
    }
    {
        float v[16] = {blo(xa.x), bhi(xa.x), blo(xa.y), bhi(xa.y), blo(xa.z), bhi(xa.z), blo(xa.w), bhi(xa.w),
                       blo(xb.x), bhi(xb.x), blo(xb.y), bhi(xb.y), blo(xb.z), bhi(xb.z), blo(xb.w), bhi(xb.w)};
        float s = 0;
#pragma unroll
        for (int i = 0; i < 16; i++) s += v[i];
#pragma unroll
        for (int o = 16; o; o >>= 1) s += __shfl_xor_sync(~0u, s, o);
        s *= (1.0f / DM);
        float q2 = 0;
#pragma unroll
        for (int i = 0; i < 16; i++) q2 += (v[i] - s) * (v[i] - s);
#pragma unroll
        for (int o = 16; o; o >>= 1) q2 += __shfl_xor_sync(~0u, q2, o);
        uint32_t mu2; float rs; ln_consts(s, q2 * (1.0f / DM), mu2, rs);
        if (lane == 0) sts64(sb + SM_ST + w * 8, __uint_as_float(mu2), rs);
    }
    const int lrow = (lane & 7) + ((lane >> 4) << 3), lch = (lane >> 3) & 1;
    const uint32_t off64 = lrow * 64 + ((lch ^ ((lrow >> 1) & 3)) << 4);
    const uint32_t off128 = lrow * 128 + ((lch ^ (lane & 7)) << 4);
    bar_sync<B_INIT, NTHR>();
    mbar_wait(sb + SM_BM, 0);
    {
        float a[4] = {0, 0, 0, 0}, b[4] = {0, 0, 0, 0};
        uint32_t r[4], u[4];
        ldsm_t(r, sb + 4 * REG + (w * 64 + lane) * 16); ldsm_t(u, sb + 4 * REG + (w * 64 + 32 + lane) * 16);
        mma(a, sc[0], 0, sc[1], 0, r[0], r[1]); mma(b, sc[4], 0, sc[5], 0, u[0], u[1]);
        mma(a, sc[2], 0, sc[3], 0, r[2], r[3]); mma(b, sc[6], 0, sc[7], 0, u[2], u[3]);
        sts64(myscr + SC_M + lane * 8, a[0] + b[0], a[1] + b[1]);
    }
    bar_arrive<B_MOD, NTHR>();
    bar_sync<B_ALL, 256>();
    if (w < 2) {
        const float2 m = sum8(scr + SC_M + lane * 8);
        stg_rlx32(mout, ~pack2(m.x, m.y));
    }
    if (tid < 8 * XC) stg_rlx128(X + X_X1 + (cta * 8 * XC + tid) * 16, make_uint4(SENT, SENT, SENT, SENT));
    else if (tid >= 232) stg_rlx128(X + X_HM + (cta * 24 + tid - 232) * 16, make_uint4(SENT, SENT, SENT, SENT));
    {
        const float2 st = lds64(sb + SM_ST + g * 8);
#pragma unroll
        for (int i = 0; i < 8; i++) xf[i] = ln_norm(xf[i], __float_as_uint(st.x), st.y);
    }
    {
        unsigned sv[8], cv[8]; int n = 0;
        bar_sync<B_SIDE, NTHR>();
        const char* const mp = X + blk(X_M1, w >> 2, lds32u(sb + SM_SIDE)) + (w & 3) * 1024 + lane * 4;
        if (lane == 0) while (!ldg_rlx32(mp + 16384 + 7 * 128)) { nap(40); if (++n > SPIN_MAX) __trap(); }
        __syncwarp();
#pragma unroll
        for (int j = 0; j < 8; j++) { sv[j] = ldg_rlx32(mp + j * 128); cv[j] = ldg_rlx32(mp + 16384 + j * 128); }
        while (true) {
            unsigned m = ~0u;
#pragma unroll
            for (int j = 0; j < 8; j++) m = min(m, min(sv[j], cv[j]));
            if (__all_sync(~0u, m)) break;
#pragma unroll
            for (int j = 0; j < 8; j++) { if (!sv[j]) sv[j] = ldg_rlx32(mp + j * 128); if (!cv[j]) cv[j] = ldg_rlx32(mp + 16384 + j * 128); }
            if (++n > SPIN_MAX) __trap();
        }
#pragma unroll
        for (int j = 0; j < 8; j++) xf[j] = add2(mul2(xf[j], add2(~cv[j], ONE2)), ~sv[j]);
        mbar_wait(bar0 + 48, 0);
        float acc[4][4] = {};
#pragma unroll
        for (int j = 0; j < 4; j++) {
            uint32_t r[4], u[4];
            ldsm_t(r, s2 + REG + j * 1024 + off64); ldsm_t(u, s2 + REG + j * 1024 + (off64 ^ 32));
            mma(acc[0], xf[2 * j], 0, xf[2 * j + 1], 0, r[0], r[2]); mma(acc[1], xf[2 * j], 0, xf[2 * j + 1], 0, r[1], r[3]);
            mma(acc[2], xf[2 * j], 0, xf[2 * j + 1], 0, u[0], u[2]); mma(acc[3], xf[2 * j], 0, xf[2 * j + 1], 0, u[1], u[3]);
        }
#pragma unroll
        for (int n2 = 0; n2 < 4; n2++) sts64(myscr + SC_Q + g * 160 + n2 * 32 + t * 8, acc[n2][0], acc[n2][1]);
    }
    bar_arrive<B_WQ, NTHR>();
    bar_sync<B_ALL, 256>();
    {
        const float2 s = sum8(scr + SC_Q + ((tid >> 4) & 7) * 160 + (tid & 15) * 8);
        stg_rlx32(qout, ~pack2(s.x, s.y));
    }
    uint32_t q[16];
    {
        int n = 0;
        const char* const qp = X + blk(X_Q, head >> 1, lds32u(sb + SM_SIDE)) + (head & 1) * 2048 + bat * 256 + t * 16;
        uint4 v[4];
#pragma unroll
        for (int j = 0; j < 4; j++) v[j] = ldg_rlx128(qp + j * 64);
        while (true) {
            bool bad[4];
#pragma unroll
            for (int j = 0; j < 4; j++) bad[j] = !min(min(v[j].x, v[j].y), min(v[j].z, v[j].w));
            if (!__any_sync(~0u, bad[0] | bad[1] | bad[2] | bad[3])) break;
#pragma unroll
            for (int j = 0; j < 4; j++) if (bad[j]) v[j] = ldg_rlx128(qp + j * 64);
            if (++n > SPIN_MAX) __trap();
        }
#pragma unroll
        for (int j = 0; j < 4; j++) { q[4 * j] = ~v[j].x; q[4 * j + 1] = ~v[j].y; q[4 * j + 2] = ~v[j].z; q[4 * j + 3] = ~v[j].w; }
    }
    bar_arrive<B_Q, NTHR>();

    float o[2][4] = {};
    float mrun = -3.0e38f, lrun = 0.f;
    uint32_t wa[16][4], pb[2];
#pragma unroll
    for (int i = 0; i < 16; i++) wa[i][0] = wa[i][1] = wa[i][2] = wa[i][3] = 0;
    constexpr float LOG2E = 1.4426950408889634f, SCALE = 0.08838834764831845f;
    const uint32_t offk = (lane & 15) * 128 + (((lane >> 4) ^ (lane & 7)) << 4);
    float p0, p1;
    auto scores = [&](uint32_t a0) {
        uint32_t kf[8][4];
#pragma unroll
        for (int j = 0; j < 8; j++) ldsm(kf[j], ((a0 + offk) ^ ((j & 3) << 5)) + (j >> 2) * 2048);
        float sa[4] = {0, 0, 0, 0}, sb2[4] = {0, 0, 0, 0};
#pragma unroll
        for (int j = 0; j < 8; j += 2) { mma(sa, kf[j], q[2 * j], q[2 * j + 1]); mma(sb2, kf[j + 1], q[2 * j + 2], q[2 * j + 3]); }
        uint32_t u = pack2(sa[0] + sb2[0], sa[2] + sb2[2]);
        u = pack2(blo(u) * SCALE, bhi(u) * SCALE);
        const float z0 = blo(u), z1 = bhi(u);
        float mx = fmaxf(z0, z1);
        mx = fmaxf(mx, __shfl_xor_sync(~0u, mx, 4)); mx = fmaxf(mx, __shfl_xor_sync(~0u, mx, 8)); mx = fmaxf(mx, __shfl_xor_sync(~0u, mx, 16));
        mx = fmaxf(mx, mrun);
        const float f = ex2((mrun - mx) * LOG2E);
        p0 = ex2((z0 - mx) * LOG2E); p1 = ex2((z1 - mx) * LOG2E);
        mrun = mx; lrun = lrun * f + (p0 + p1);
#pragma unroll
        for (int j = 0; j < 4; j++) { o[0][j] *= f; o[1][j] *= f; }
    };
    const int kvrow = (bat * NH + head) * SK + (SK - WIN) + (w & 3) * 16;
    const int wofs = (w * 8 + (cta & 7)) * TAU / 8;
    auto request = [&](int u) {
        sts32u(bar0 + 56, u - 1);
        while ((int)(now_ns() - lds32u(sb + SM_AN) - u * 8 * TAU - wofs) < 0) nap(20);
        const int sl = (~u & 2) + (u & 1);
        mbar_expect(bar0 + sl * 8, UNIT); tma_kv(s0 + sl * REG, &P.k + (u & 1), kvrow + (u >> 1) * 64, bar0 + sl * 8, pol);
    };
#pragma unroll 1
    for (int it = 0; it < NT - 1; it++) {
        const int si = it < 3 ? it : (it + 1) & 1;
        const uint32_t bar = bar0 + si * 16, a0 = s0 + si * 2 * REG;
        const uint32_t par = it < 3 ? 0 : ((it - 1) >> 1) & 1;
        const bool refill = lane == 0 && it >= 2;
        mbar_wait(bar, par);
        if (refill) {
            request(2 * it + 2);
            const int e = it - (it > WOA_READ ? WOA_READ + 1 : WOA_ISSUE);
            if (e == 0) mbar_expect(barC, 2 * UNIT);
            if (e == 0 || e == WO_GAP) tma2d(s2 + (e ? REG : 0), &P.wo, w * 64, head * 128 + (it > WOA_READ ? 64 : 0) + (e ? 32 : 0), barC);
        }
        __syncwarp();
        if (it == WOA_READ) {
            mbar_wait(barC, 1);
#pragma unroll
            for (int j = 0; j < 16; j++) ldsm_t(wa[j], s2 + (j >> 3) * REG + ((j >> 2) & 1) * 2048 + (off128 ^ ((j & 3) << 5)));
        }
        scores(a0);
        pb[0] = movm(pack2(p0, p0)); pb[1] = movm(pack2(p1, p1));
        mbar_wait(bar + 8, par);
        if (refill) request(2 * it + 3);
        __syncwarp();
        uint32_t vf[8][4];
#pragma unroll
        for (int j = 0; j < 8; j++) ldsm_t(vf[j], ((a0 + off128) ^ ((j & 3) << 5)) + (j >> 2) * 2048 + REG);
#pragma unroll
        for (int j = 0; j < 8; j++) { const bool on = (g >> 1) == (j >> 1); mma(o[j & 1], vf[j], on ? pb[0] : 0, on ? pb[1] : 0); }
    }
    {
        uint32_t wb[16][4];
        mbar_wait(bar0, 1);
        if (rid >= DN0) bar_arrive<B_LAST, NTHR>();
        scores(s0);
        lrun += __shfl_xor_sync(~0u, lrun, 4); lrun += __shfl_xor_sync(~0u, lrun, 8); lrun += __shfl_xor_sync(~0u, lrun, 16);
        if (lane == 0) sts64(sb + SM_ML + w * 8, mrun, lrun);
        bar_arrive<B_ML, NTHR>();
        pb[0] = movm(pack2(p0, p0)); pb[1] = movm(pack2(p1, p1));
        const uint32_t va = pin(s0 + REG + off128);
        auto load_wb = [&](int j) { ldsm_t(wb[j], (va ^ ((j & 3) << 5)) + (3 + (j >> 3)) * REG + ((j >> 2) & 1) * 2048); };
        mbar_wait(barC, 0);
#pragma unroll
        for (int j = 0; j < NPRE; j++) load_wb(j);
        const uint32_t ho = pin(s0 + w * 16 + ((lane & 7) >> 1) * 64 + ((lane >> 3) & 1) * 32 + (lane & 1) * 16), oa = pin(sb + (lane & 7) * (UNIT + 16) + (lane >> 3) * 16);
        const uint32_t rd = pin((t >> 1) * 16 + w * 2 + (g >> 2));
        char* const pp = pin(X + X_PART + ((cta & 3) * 32 + rd) * 8192 + head * 128 + (g & 3) * 32 + (t & 1) * 16);
        const uint32_t ln = pin(lane);
        mbar_wait(bar0 + 8, 1);
        {
            uint32_t vf[8][4];
            float o2[2][4] = {};
#pragma unroll
            for (int j = 0; j < 8; j++) ldsm_t(vf[j], (va ^ ((j & 3) << 5)) + (j >> 2) * 2048);
#pragma unroll
            for (int j = 0; j < 8; j++) { const bool on = (ln >> 3) == (j >> 1); mma((j & 2) ? o2[j & 1] : o[j & 1], vf[j], on ? pb[0] : 0, on ? pb[1] : 0); }
            asm volatile("stmatrix.sync.aligned.m8n8.x2.trans.shared.b16 [%0], {%1,%2};" :: "r"(ho), "r"(pack2(o[0][0] + o2[0][0], o[0][2] + o2[0][2])), "r"(pack2(o[1][0] + o2[1][0], o[1][2] + o2[1][2])) : "memory");
        }
        bar_sync<B_RDY, NALL>();
        float y[4][4] = {};
        uint32_t ob[4][4];
#pragma unroll
        for (int i2 = 0; i2 < 4; i2++) ldsm(ob[i2], oa + i2 * 64);
        const float2 f = lds64(sb + SM_ML + 64 + (ln & 3) * 8);
        const unsigned half = (lds32u(sb + SM_MASK) >> rd & 1) * 4096;
#pragma unroll
        for (int j = NPRE; j < 16; j++) load_wb(j);
#pragma unroll
        for (int j = 0; j < 8; j++)
#pragma unroll
            for (int i = 0; i < 4; i++) mma(y[i], j < 4 ? wa[j * 4 + i] : wb[(j - 4) * 4 + i], ob[j >> 1][2 * (j & 1)], ob[j >> 1][2 * (j & 1) + 1]);
        uint32_t r[4];
#pragma unroll
        for (int i = 0; i < 4; i++) {
            const float lo = f.x * y[i][0] + f.y * y[i][1], hi = f.x * y[i][2] + f.y * y[i][3];
            r[i] = __float_as_uint(((ln & 1) ? hi : lo) + __shfl_xor_sync(~0u, (ln & 1) ? lo : hi, 1));
        }
        asm("min.u32 %0, %0, 0xFFFFFFFE;" : "+r"(r[0]));
        stg_b128(pp + half, make_uint4(r[0], r[1], r[2], r[3]));
    }
    const unsigned side = lds32u(sb + SM_SIDE);
    const char* const x1p = X + (rid & (XC - 1)) * 16384;
    if (rid < NF1) {
        uint32_t wg[4][4], wu[4][4];
        const char* const xp = pin(x1p + blk(X_X1, w >> 2, side) + (w & 3) * 1024 + lane * 16);
        float4 c1[2], sv[2];
#pragma unroll
        for (int h = 0; h < 2; h++) { sv[h] = lds128(sb + SM_MN + (w * 2 + h) * 512 + lane * 16); c1[h] = lds128(sb + SM_MN + 8192 + (w * 2 + h) * 512 + lane * 16); }
        const uint32_t po = pin(myscr + SC_F1 + g * 144 + t * 32), so = pin(t == (g >> 1) ? sb + SM_ST + g * 64 + w * 8 : myscr + 1792 + lane * 8), odd = pin(g & 1);
        const uint32_t wbar = sb + SM_BAR + (w >> 1) * 64 + 48;
        uint4 x0, x1;
        const bool early = go_first(wbar, 1);
        if (early) { spin(clock(), (7 - w) * XDW); x0 = ldg_rlx2x64(xp); x1 = ldg_rlx2x64(xp + 512); mbar_wait(wbar, 1); }
#pragma unroll
        for (int j = 0; j < 4; j++) {
            const uint32_t a = sb + 2 * REG + w * 2048 + (((lane & 7) >> 1) + (lane & 1) * 4 + j * 8 + (lane >> 4) * 32) * 32 + ((lch ^ (lane & 1)) << 4);
            ldsm_t(wg[j], a); ldsm_t(wu[j], a + 16384);
        }
        {
            float cg[4] = {}, cu[4] = {}, sg[4] = {}, su[4] = {};
#pragma unroll
            for (int j = 0; j < 4; j++) {
                const float4 a = c1[j & 1], b = sv[j & 1];
                const uint32_t a0 = __float_as_uint(j >> 1 ? a.z : a.x), a1 = __float_as_uint(j >> 1 ? a.w : a.y), b0 = __float_as_uint(j >> 1 ? b.z : b.x), b1 = __float_as_uint(j >> 1 ? b.w : b.y);
                mma(cg, wg[j], a0, a1); mma(cu, wu[j], a0, a1); mma(sg, wg[j], b0, b1); mma(su, wu[j], b0, b1);
            }
            const uint32_t d = s0 + REG + g * 144 + t * 32;
            sts128f(d, cg[0], cg[2], cu[0], cu[2]); sts128f(d + 16, cg[1], cg[3], cu[1], cu[3]);
            sts128f(d + 1152, sg[0], sg[2], su[0], su[2]); sts128f(d + 1168, sg[1], sg[3], su[1], su[3]);
            bar_arrive<B_PRE, NALL>();
        }
        if (!early) { mbar_wait(sb + SM_BG, 0); spin(clock(), (7 - w) * XDW); x0 = ldg_rlx2x64(xp); x1 = ldg_rlx2x64(xp + 512); }
        int n = 0;
        while (true) {
            const bool b0 = max(x0.x, x0.z) == SENT, b1 = max(x1.x, x1.z) == SENT;
            if (!__any_sync(~0u, b0 | b1)) break;
            if (b0) x0 = ldg_rlx2x64(xp);
            if (b1) x1 = ldg_rlx2x64(xp + 512);
            if (++n > SPIN_MAX) __trap();
        }
        float sm[4] = {}, q0[4] = {}, q1[4] = {}, ag[2][4] = {}, au[2][4] = {};
        {
            const uint32_t a0[4] = {x0.x, x0.y, x0.z, x0.w}, a1[4] = {x1.x, x1.y, x1.z, x1.w};
            mma(sm, a0, ONE2, ONE2); mma(q0, a0, x0.x, x0.z); mma(q1, a0, x0.y, x0.w);
            mma(sm, a1, ONE2, ONE2); mma(q0, a1, x1.x, x1.z); mma(q1, a1, x1.y, x1.w);
#pragma unroll
            for (int j = 0; j < 4; j++) {
                const uint4 xv = (j & 1) ? x1 : x0; const float4 a = c1[j & 1];
                const uint32_t h0 = mul2(j >> 1 ? xv.z : xv.x, __float_as_uint(j >> 1 ? a.z : a.x)), h1 = mul2(j >> 1 ? xv.w : xv.y, __float_as_uint(j >> 1 ? a.w : a.y));
                mma(ag[j & 1], wg[j], h0, h1); mma(au[j & 1], wu[j], h0, h1);
            }
        }
        sts64(so, sm[0] + sm[2], odd ? q0[1] + q1[3] : q0[0] + q1[2]);
        sts128f(po, ag[0][0] + ag[1][0], ag[0][2] + ag[1][2], au[0][0] + au[1][0], au[0][2] + au[1][2]);
        sts128f(po + 16, ag[0][1] + ag[1][1], ag[0][3] + ag[1][3], au[0][1] + au[1][1], au[0][3] + au[1][3]);
        bar_arrive<B_FIN, NALL>();
    } else if (rid >= DN0) {
        const int f = rid - DN0;
        uint32_t wd[12][4];
        const char* const hp0 = pin(X + blk(X_HM, 0, side) + w * 512 + lane * 16);
        const char* const hp1 = pin(X + blk(X_HM, 1, side) + w * 512 + lane * 16);
        auto hm = [&](int j) { return ldg_rlx128((j & 1 ? hp1 : hp0) + (j >> 1) * 16384); };
        unsigned* const op = pin((unsigned*)P.out + (tid >> 3) * 256 + f * 8 + (tid & 7));
        const uint32_t po = pin(myscr + SC_DN + t * 160 + g * 4), pi = pin(scr + SC_DN + (tid >> 3) * 80 + (tid & 7) * 8), gi = pin(sb + SM_MN + tid * 4), first = pin(w < 2);
        uint4 hv[6]; int n = 0;
        auto first_poll = [&]() {
            spin(clock(), w * HDW);
#pragma unroll
            for (int j = 0; j < 6; j++) hv[j] = (j < 5 || w < 3) ? hm(j) : make_uint4(0, 0, 0, 0);
        };
        const bool early = go_first(sb + SM_BT, 0);
        if (early) { first_poll(); mbar_wait(sb + SM_BT, 0); }
#pragma unroll
        for (int j = 0; j < 12; j++)
            if (j < 10 || w < 3) ldsm_t(wd[j], sb + 2 * REG + 16384 + (w + (j >> 1) * 8) * 1024 + (j & 1) * 512 + (((lane & 7) >> 1) + (lane & 1) * 4 + (lane >> 4) * 8) * 32 + ((lch ^ (lane & 1)) << 4));
            else wd[j][0] = wd[j][1] = wd[j][2] = wd[j][3] = 0;
        if (!early) { mbar_wait(sb + SM_BG, 0); first_poll(); }
        while (true) {
            unsigned m[6];
#pragma unroll
            for (int j = 0; j < 6; j++) m[j] = max(max(hv[j].x, hv[j].y), max(hv[j].z, hv[j].w));
            if (__all_sync(~0u, max(max(max(m[0], m[1]), m[2]), max(max(m[3], m[4]), m[5])) != SENT)) break;
#pragma unroll
            for (int j = 0; j < 6; j++) if (m[j] == SENT) hv[j] = hm(j);
            if (++n > SPIN_MAX) __trap();
        }
        float d[4][4] = {};
#pragma unroll
        for (int j = 0; j < 6; j++) { mma(d[(2 * j) & 3], wd[2 * j], hv[j].x, hv[j].y); mma(d[(2 * j + 1) & 3], wd[2 * j + 1], hv[j].z, hv[j].w); }
#pragma unroll
        for (int e = 0; e < 4; e++) sts32(po + (e & 1) * 80 + (e >> 1) * 32, (d[0][e] + d[1][e]) + (d[2][e] + d[3][e]));
        if (!first) bar_arrive<B_DN, NTHR>();
        else {
            bar_sync<B_DN, NTHR>();
            const float2 s = sum8(pi);
            const unsigned gw = lds32u(gi), res = lds32u(gi + 256);
            asm volatile("st.global.u32 [%0], %1;" :: "l"(op), "r"(add2(res, mul2(gw, pack2(s.x, s.y)))) : "memory");
        }
    }
}

typedef CUresult (*EncodeFn)(CUtensorMap*, CUtensorMapDataType, cuuint32_t, void*, const cuuint64_t*, const cuuint64_t*, const cuuint32_t*,
                             const cuuint32_t*, CUtensorMapInterleave, CUtensorMapSwizzle, CUtensorMapL2promotion, CUtensorMapFloatOOBfill);

void make2d(EncodeFn enc, CUtensorMap* m, const void* p, int rows, int cols, int brows, int bcols, CUtensorMapSwizzle sw) {
    cuuint64_t dims[2] = {(cuuint64_t)cols, (cuuint64_t)rows}, strides[1] = {(cuuint64_t)cols * 2};
    cuuint32_t box[2] = {(cuuint32_t)bcols, (cuuint32_t)brows}, es[2] = {1, 1};
    enc(m, CU_TENSOR_MAP_DATA_TYPE_BFLOAT16, 2, (void*)p, dims, strides, box, es, CU_TENSOR_MAP_INTERLEAVE_NONE, sw,
        CU_TENSOR_MAP_L2_PROMOTION_L2_128B, CU_TENSOR_MAP_FLOAT_OOB_FILL_NONE);
}
void make5d(EncodeFn enc, CUtensorMap* m, const void* p, int rows, int cols, int d, int nb) {
    const cuuint64_t rs = (cuuint64_t)cols * 2;
    cuuint64_t dims[5] = {(cuuint64_t)cols, 4, 2, (cuuint64_t)d / 4, (cuuint64_t)rows / (2 * d)}, strides[4] = {rs, rs * d, rs * 4, rs * 2 * d};
    cuuint32_t box[5] = {16, 4, 2, (cuuint32_t)d / 4, (cuuint32_t)nb}, es[5] = {1, 1, 1, 1, 1};
    enc(m, CU_TENSOR_MAP_DATA_TYPE_BFLOAT16, 5, (void*)p, dims, strides, box, es, CU_TENSOR_MAP_INTERLEAVE_NONE, CU_TENSOR_MAP_SWIZZLE_32B,
        CU_TENSOR_MAP_L2_PROMOTION_L2_128B, CU_TENSOR_MAP_FLOAT_OOB_FILL_NONE);
}
void makekv(EncodeFn enc, CUtensorMap* m, const void* p) {
    cuuint64_t dims[3] = {64, (cuuint64_t)NB * NH * SK, 2}, strides[2] = {256, 128};
    cuuint32_t box[3] = {64, 16, 2}, es[3] = {1, 1, 1};
    enc(m, CU_TENSOR_MAP_DATA_TYPE_BFLOAT16, 3, (void*)p, dims, strides, box, es, CU_TENSOR_MAP_INTERLEAVE_NONE, CU_TENSOR_MAP_SWIZZLE_128B,
        CU_TENSOR_MAP_L2_PROMOTION_NONE, CU_TENSOR_MAP_FLOAT_OOB_FILL_NONE);
}

}

extern "C" void kernel_launch(void* const* d_in, const int* in_sizes, int n_in, void* d_out, int out_size) {
    (void)in_sizes; (void)n_in; (void)out_size;
    static EncodeFn enc = nullptr;
    static void* raw = nullptr;
    if (!enc) {
        void* fn = nullptr; cudaDriverEntryPointQueryResult qr;
        cudaGetDriverEntryPoint("cuTensorMapEncodeTiled", &fn, cudaEnableDefault, &qr);
        enc = (EncodeFn)fn;
        cudaFuncSetAttribute(fused_kernel, cudaFuncAttributeMaxDynamicSharedMemorySize, SM_TOTAL);
        cudaGetSymbolAddress(&raw, g_raw);
    }
    Params P;
    makekv(enc, &P.k, d_in[1]);
    makekv(enc, &P.v, d_in[2]);
    make2d(enc, &P.wq, d_in[3], DM, NH * DH, 64, 32, CU_TENSOR_MAP_SWIZZLE_64B);
    make2d(enc, &P.wo, d_in[4], NH * DH, DM, 32, 64, CU_TENSOR_MAP_SWIZZLE_128B);
    make2d(enc, &P.wm, d_in[10], DM, 6 * DM, 256, 8, CU_TENSOR_MAP_SWIZZLE_NONE);
    make2d(enc, &P.wn, d_in[10], DM, 6 * DM, 256, 16, CU_TENSOR_MAP_SWIZZLE_32B);
    make5d(enc, &P.wg, d_in[6], DM, FF, 16, 4);
    make5d(enc, &P.wu, d_in[7], DM, FF, 16, 4);
    make5d(enc, &P.wd, d_in[8], FF, DM, 8, 43);
    P.out = (__nv_bfloat16*)d_out;
    typedef const __nv_bfloat16* W;
    fused_kernel<<<NCTA, NALL, SM_TOTAL>>>((W)d_in[0], (W)d_in[9], (W)d_in[1], (W)d_in[10], (W)d_in[3], (char*)(((size_t)raw + X_ALIGN - 1) & ~(size_t)(X_ALIGN - 1)), P);
}
```

```cpp
#include <cuda_runtime.h>
#include <cuda_bf16.h>
#include <cuda.h>
#include <stdint.h>

namespace {

constexpr int NB = 8, DM = 512, NH = 32, DH = 128, SK = 4096, WIN = 1024, FF = 1376;
constexpr int NCTA = 128, NTHR = 288, NALL = 320;
constexpr int NT = 16;
constexpr int NF1 = 86, DN0 = 96;
constexpr unsigned SENT = 0xFFFFFFFFu;
constexpr int SPIN_MAX = 1 << 20;

constexpr int PWIN0 = 12;
constexpr int PWIN = 16;
constexpr int PSW = 22;
constexpr int NTRK = 4;
constexpr int PFK = 3;
constexpr int QN = 6;
constexpr int TAU = 166;
constexpr int ANCH0 = 176;
constexpr int LEAD = 1600;
constexpr int PACE0 = 7000;
constexpr int PNAP = 200;
constexpr int WOA_ISSUE = 3;
constexpr int WO_GAP = 2;
constexpr int WOA_READ = 8;
constexpr int NPRE = 9;
constexpr int W0 = 850;
constexpr int WS = 180;
constexpr int WD0 = 1700;
constexpr int RT0 = 1700;
constexpr int HD0 = 1000;
constexpr int XDW = 30;
constexpr int HDW = 30;
constexpr int XC = 2;

constexpr int UNIT = 4096, REG = 8 * UNIT;
constexpr int SM_SCR = 6 * REG;
constexpr int SCR = 2048;
constexpr int SM_MN = SM_SCR + 8 * SCR;
constexpr int SM_SC = SM_MN + 8192;
constexpr int SM_BAR = SM_SC + 8192;
constexpr int SM_BM = SM_BAR + 512, SM_BT = SM_BM + 8, SM_BN = SM_BM + 16, SM_BG = SM_BM + 24;
constexpr int SM_AN = SM_BM + 32, SM_SIDE = SM_BM + 36, SM_TAG = SM_BM + 40, SM_MASK = SM_BM + 44;
constexpr int SM_ST = SM_BAR + 576;
constexpr int SM_ML = SM_ST + 512;
constexpr int SM_PR = SM_ML + 96;
constexpr int SM_TOTAL = SM_PR + 512;
constexpr int SC_M = 0, SC_Q = 256;
constexpr int SC_F1 = 0, SC_DN = 0, SC_RX = 1536;
constexpr int B_INIT = 0, B_ALL = 2, B_MOD = 3, B_WQ = 4, B_LAST = 5, B_RDY = 6, B_DN = 7, B_PRE = 8, B_FIN = 9, B_STG = 10, B_SIDE = 11, B_Q = 12, B_ML = 13;

constexpr unsigned HOME = 0xB3000;
constexpr int X_PART = 0;
constexpr int X_Q = 0x100000;
constexpr int X_M1 = 0x140000;
constexpr int X_X1 = 0x150000;
constexpr int X_HM = 0x160000;
constexpr int X_MOD = 0x170000;
constexpr int X_SIDE = 0x176000;
constexpr int X_EPOCH = 0x176400;
constexpr int X_READY = 0x176480;
constexpr int X_LAG = 0x178000;
constexpr int X_ANC = 0x158000;
constexpr int X_PRB = 0x180000;
constexpr int X_ALIGN = 0x200000;
static_assert(XC == 2, "one store writes all copies of x1");
__device__ uint4 g_raw[2 * X_ALIGN / 16];
__device__ __forceinline__ unsigned blk(unsigned base, unsigned k, unsigned s) { const unsigned o = base + k * 8192; return o + ((__popc(o & HOME) ^ s) & 1) * 4096; }

struct Params {
    CUtensorMap wm, wq, k, v, wn, wo, wg, wu, wd;
    __nv_bfloat16* out;
};

__device__ __forceinline__ int tile_key(int i) { return (i & 1) * 128 + (i & 2) * 32 + (i & 12) * 64; }

__device__ __forceinline__ uint32_t smem_u32(const void* p) { return (uint32_t)__cvta_generic_to_shared(p); }
__device__ __forceinline__ void mbar_init(uint32_t a, uint32_t c) { asm volatile("mbarrier.init.shared::cta.b64 [%0], %1;" :: "r"(a), "r"(c) : "memory"); }
__device__ __forceinline__ void mbar_expect(uint32_t a, uint32_t b) { asm volatile("mbarrier.arrive.expect_tx.shared::cta.b64 _, [%0], %1;" :: "r"(a), "r"(b) : "memory"); }
__device__ __forceinline__ void mbar_wait(uint32_t a, uint32_t par) {
    uint32_t ok; int n = 0;
    do {
        asm volatile("{\n.reg .pred p;\nmbarrier.try_wait.parity.shared::cta.b64 p, [%1], %2, 2000;\nselp.u32 %0, 1, 0, p;\n}" : "=r"(ok) : "r"(a), "r"(par) : "memory");
        if (++n > SPIN_MAX) __trap();
    } while (!ok);
}
__device__ __forceinline__ bool mbar_test(uint32_t a, uint32_t par) {
    uint32_t ok; asm volatile("{\n.reg .pred p;\nmbarrier.test_wait.parity.shared::cta.b64 p, [%1], %2;\nselp.u32 %0, 1, 0, p;\n}" : "=r"(ok) : "r"(a), "r"(par) : "memory"); return ok;
}
__device__ __forceinline__ void tma2d(uint32_t dst, const CUtensorMap* m, int x, int y, uint32_t bar) {
    asm volatile("cp.async.bulk.tensor.2d.shared::cluster.global.mbarrier::complete_tx::bytes [%0], [%1, {%3, %4}], [%2];"
                 :: "r"(dst), "l"(m), "r"(bar), "r"(x), "r"(y) : "memory");
}
__device__ __forceinline__ void tma5d(uint32_t dst, const CUtensorMap* m, int x, int y, uint32_t bar) {
    asm volatile("cp.async.bulk.tensor.5d.shared::cluster.global.mbarrier::complete_tx::bytes [%0], [%1, {%3, 0, 0, 0, %4}], [%2];"
                 :: "r"(dst), "l"(m), "r"(bar), "r"(x), "r"(y) : "memory");
}
__device__ __forceinline__ void tma_kv(uint32_t dst, const CUtensorMap* m, int row, uint32_t bar, uint64_t pol) {
    asm volatile("cp.async.bulk.tensor.3d.shared::cluster.global.mbarrier::complete_tx::bytes.L2::cache_hint [%0], [%1, {0, %3, 0}], [%2], %4;"
                 :: "r"(dst), "l"(m), "r"(bar), "r"(row), "l"(pol) : "memory");
}
__device__ __forceinline__ void pf_bulk(const void* p, uint32_t n) { asm volatile("cp.async.bulk.prefetch.L2.global [%0], %1;" :: "l"(p), "r"(n) : "memory"); }
__device__ __forceinline__ void pf_line(const void* p) { asm volatile("prefetch.global.L2 [%0];" :: "l"(p) : "memory"); }
__device__ __forceinline__ void pf_if(const void* p, unsigned i, unsigned n) { asm volatile("{\n.reg .pred p;\nsetp.lt.u32 p, %1, %2;\n@p prefetch.global.L2 [%0];\n}" :: "l"(p), "r"(i), "r"(n) : "memory"); }
__device__ __forceinline__ uint4 ldg_nc(const void* p) { uint4 v; asm volatile("ld.global.nc.v4.u32 {%0,%1,%2,%3}, [%4];" : "=r"(v.x), "=r"(v.y), "=r"(v.z), "=r"(v.w) : "l"(p)); return v; }
__device__ __forceinline__ bool elect() { uint32_t p; asm volatile("{\n.reg .pred p;\nelect.sync _|p, -1;\nselp.u32 %0, 1, 0, p;\n}" : "=r"(p)); return p; }
__device__ __forceinline__ void pf_map(const CUtensorMap* m) { asm volatile("prefetch.tensormap [%0];" :: "l"(m) : "memory"); }
__device__ __forceinline__ void ldsm(uint32_t (&r)[4], uint32_t a) {
    asm volatile("ldmatrix.sync.aligned.m8n8.x4.shared.b16 {%0,%1,%2,%3}, [%4];" : "=r"(r[0]), "=r"(r[1]), "=r"(r[2]), "=r"(r[3]) : "r"(a) : "memory");
}
__device__ __forceinline__ void ldsm_t(uint32_t (&r)[4], uint32_t a) {
    asm volatile("ldmatrix.sync.aligned.m8n8.x4.trans.shared.b16 {%0,%1,%2,%3}, [%4];" : "=r"(r[0]), "=r"(r[1]), "=r"(r[2]), "=r"(r[3]) : "r"(a) : "memory");
}
__device__ __forceinline__ void mma(float (&c)[4], uint32_t a0, uint32_t a1, uint32_t a2, uint32_t a3, uint32_t b0, uint32_t b1) {
    asm("mma.sync.aligned.m16n8k16.row.col.f32.bf16.bf16.f32 {%0,%1,%2,%3}, {%4,%5,%6,%7}, {%8,%9}, {%0,%1,%2,%3};"
        : "+f"(c[0]), "+f"(c[1]), "+f"(c[2]), "+f"(c[3]) : "r"(a0), "r"(a1), "r"(a2), "r"(a3), "r"(b0), "r"(b1));
}
__device__ __forceinline__ void mma(float (&c)[4], const uint32_t (&a)[4], uint32_t b0, uint32_t b1) { mma(c, a[0], a[1], a[2], a[3], b0, b1); }
__device__ __forceinline__ void mmav(float (&c)[4], const uint32_t (&a)[4], uint32_t b0, uint32_t b1) {
    asm volatile("mma.sync.aligned.m16n8k16.row.col.f32.bf16.bf16.f32 {%0,%1,%2,%3}, {%4,%5,%6,%7}, {%8,%9}, {%0,%1,%2,%3};"
        : "+f"(c[0]), "+f"(c[1]), "+f"(c[2]), "+f"(c[3]) : "r"(a[0]), "r"(a[1]), "r"(a[2]), "r"(a[3]), "r"(b0), "r"(b1));
}
__device__ __forceinline__ uint32_t pin(uint32_t v) { asm volatile("shfl.sync.bfly.b32 %0, %0, 0, 31, -1;" : "+r"(v)); return v; }
template <class T> __device__ __forceinline__ T* pin(T* p) { const size_t a = (size_t)p; return (T*)(pin((uint32_t)a) | (size_t)pin((uint32_t)(a >> 32)) << 32); }
__device__ __forceinline__ uint32_t movm(uint32_t a) { uint32_t r; asm volatile("movmatrix.sync.aligned.m8n8.trans.b16 %0, %1;" : "=r"(r) : "r"(a)); return r; }
__device__ __forceinline__ uint32_t pack2(float lo, float hi) { uint32_t r; asm("cvt.rn.bf16x2.f32 %0, %1, %2;" : "=r"(r) : "f"(hi), "f"(lo)); return r; }
__device__ __forceinline__ float blo(uint32_t w) { return __uint_as_float(w << 16); }
__device__ __forceinline__ float bhi(uint32_t w) { return __uint_as_float(w & 0xFFFF0000u); }
__device__ __forceinline__ float rbf(float x) { return blo(pack2(x, 0.f)); }
__device__ __forceinline__ uint32_t add2(uint32_t a, uint32_t b) { uint32_t r; asm("add.rn.bf16x2 %0, %1, %2;" : "=r"(r) : "r"(a), "r"(b)); return r; }
__device__ __forceinline__ uint32_t sub2(uint32_t a, uint32_t b) { uint32_t r; asm("sub.rn.bf16x2 %0, %1, %2;" : "=r"(r) : "r"(a), "r"(b)); return r; }
__device__ __forceinline__ uint32_t mul2(uint32_t a, uint32_t b) { uint32_t r; asm("mul.rn.bf16x2 %0, %1, %2;" : "=r"(r) : "r"(a), "r"(b)); return r; }
constexpr uint32_t ONE2 = 0x3F803F80u;
__device__ __forceinline__ float ex2(float x) { float y; asm("ex2.approx.ftz.f32 %0, %1;" : "=f"(y) : "f"(x)); return y; }
__device__ __forceinline__ uint4 ldg_rlx128(const void* p) {
    uint4 v; asm volatile("ld.relaxed.gpu.global.v4.u32 {%0,%1,%2,%3}, [%4];" : "=r"(v.x), "=r"(v.y), "=r"(v.z), "=r"(v.w) : "l"(p) : "memory"); return v;
}
__device__ __forceinline__ uint4 ldg_rlx2x64(const void* p) {
    unsigned long long a, b; asm volatile("ld.relaxed.gpu.global.v2.u64 {%0,%1}, [%2];" : "=l"(a), "=l"(b) : "l"(p) : "memory");
    return make_uint4((unsigned)a, (unsigned)(a >> 32), (unsigned)b, (unsigned)(b >> 32));
}
__device__ __forceinline__ uint2 ldg_rlx64(const void* p) {
    unsigned long long a; asm volatile("ld.relaxed.gpu.global.u64 %0, [%1];" : "=l"(a) : "l"(p) : "memory"); return make_uint2((unsigned)a, (unsigned)(a >> 32));
}
__device__ __forceinline__ unsigned ldg_acq32(const void* p) { unsigned v; asm volatile("ld.acquire.gpu.global.u32 %0, [%1];" : "=r"(v) : "l"(p) : "memory"); return v; }
__device__ __forceinline__ void red_add(void* p, unsigned v) { asm volatile("red.relaxed.gpu.global.add.u32 [%0], %1;" :: "l"(p), "r"(v) : "memory"); }
__device__ __forceinline__ unsigned now_ns() { unsigned t; asm volatile("mov.u32 %0, %%globaltimer_lo;" : "=r"(t)); return t; }
__device__ __forceinline__ void nap(unsigned ns) { asm volatile("nanosleep.u32 %0;" :: "r"(ns)); }
__device__ __forceinline__ unsigned ldg_rlx32(const void* p) { unsigned v; asm volatile("ld.relaxed.gpu.global.u32 %0, [%1];" : "=r"(v) : "l"(p) : "memory"); return v; }
__device__ __forceinline__ void stg_rlx32(void* p, unsigned v) { asm volatile("st.relaxed.gpu.global.u32 [%0], %1;" :: "l"(p), "r"(v) : "memory"); }
__device__ __forceinline__ void stg_rlx16(void* p, unsigned v) { asm volatile("st.relaxed.gpu.global.u16 [%0], %1;" :: "l"(p), "h"((unsigned short)v) : "memory"); }
__device__ __forceinline__ uint4 ldg_b128(const void* p) {
    unsigned long long a, b; asm volatile("{\n.reg .b128 x;\nld.relaxed.gpu.global.b128 x, [%2];\nmov.b128 {%0,%1}, x;\n}" : "=l"(a), "=l"(b) : "l"(p) : "memory");
    return make_uint4((unsigned)a, (unsigned)(a >> 32), (unsigned)b, (unsigned)(b >> 32));
}
__device__ __forceinline__ void stg_b128(void* p, uint4 v) {
    asm volatile("{\n.reg .b128 x;\nmov.b128 x, {%1,%2};\nst.relaxed.gpu.global.b128 [%0], x;\n}" :: "l"(p), "l"(v.x | ((unsigned long long)v.y << 32)), "l"(v.z | ((unsigned long long)v.w << 32)) : "memory");
}
__device__ __forceinline__ int rowoff(int b, int c) { return ((c >> 6) * 2 + ((c >> 2) & 1)) * 512 + b * 64 + (c & 3) * 16 + ((c >> 3) & 1) * 8 + ((c >> 5) & 1) * 4 + ((c >> 4) & 1) * 2; }
__device__ __forceinline__ void stg_rlx64(void* p, unsigned lo, unsigned hi) {
    unsigned long long a = lo | ((unsigned long long)hi << 32); asm volatile("st.relaxed.gpu.global.u64 [%0], %1;" :: "l"(p), "l"(a) : "memory");
}
__device__ __forceinline__ void stg_rlx128(void* p, uint4 v) { asm volatile("st.relaxed.gpu.global.v4.u32 [%0], {%1,%2,%3,%4};" :: "l"(p), "r"(v.x), "r"(v.y), "r"(v.z), "r"(v.w) : "memory"); }
__device__ __forceinline__ void sts32u(uint32_t a, unsigned x) { asm volatile("st.volatile.shared.u32 [%0], %1;" :: "r"(a), "r"(x) : "memory"); }
__device__ __forceinline__ unsigned lds32u(uint32_t a) { unsigned v; asm volatile("ld.volatile.shared.u32 %0, [%1];" : "=r"(v) : "r"(a) : "memory"); return v; }
__device__ __forceinline__ void spin(unsigned c0, unsigned d) { if (d) while ((unsigned)clock() - c0 < d) {} }
__device__ __forceinline__ void fence_gpu() { asm volatile("fence.acq_rel.gpu;" ::: "memory"); }
__device__ __forceinline__ bool valid4(const uint4& v) { return max(max(v.x, v.y), max(v.z, v.w)) != SENT; }
template <int ID, int N> __device__ __forceinline__ void bar_sync() { asm volatile("bar.sync %0, %1;" :: "n"(ID), "n"(N) : "memory"); }
template <int ID, int N> __device__ __forceinline__ void bar_arrive() { asm volatile("bar.arrive %0, %1;" :: "n"(ID), "n"(N) : "memory"); }
__device__ __forceinline__ void sts64(uint32_t a, float x, float y) { asm volatile("st.shared.v2.f32 [%0], {%1,%2};" :: "r"(a), "f"(x), "f"(y) : "memory"); }
__device__ __forceinline__ void sts128(uint32_t a, uint4 v) { asm volatile("st.volatile.shared.v4.u32 [%0], {%1,%2,%3,%4};" :: "r"(a), "r"(v.x), "r"(v.y), "r"(v.z), "r"(v.w) : "memory"); }
__device__ __forceinline__ void sts128f(uint32_t a, float x, float y, float z, float w) { asm volatile("st.volatile.shared.v4.f32 [%0], {%1,%2,%3,%4};" :: "r"(a), "f"(x), "f"(y), "f"(z), "f"(w) : "memory"); }
__device__ __forceinline__ void sts32(uint32_t a, float x) { asm volatile("st.shared.f32 [%0], %1;" :: "r"(a), "f"(x) : "memory"); }
__device__ __forceinline__ float2 lds64(uint32_t a) { float2 v; asm volatile("ld.shared.v2.f32 {%0,%1}, [%2];" : "=f"(v.x), "=f"(v.y) : "r"(a) : "memory"); return v; }
__device__ __forceinline__ float lds32(uint32_t a) { float v; asm volatile("ld.shared.f32 %0, [%1];" : "=f"(v) : "r"(a) : "memory"); return v; }
__device__ __forceinline__ float4 lds128(uint32_t a) { float4 v; asm volatile("ld.shared.v4.f32 {%0,%1,%2,%3}, [%4];" : "=f"(v.x), "=f"(v.y), "=f"(v.z), "=f"(v.w) : "r"(a) : "memory"); return v; }
__device__ __forceinline__ float2 sum8(uint32_t a) {
    float2 v[8];
#pragma unroll
    for (int i = 0; i < 8; i++) v[i] = lds64(a + i * SCR);
    return make_float2(((v[0].x + v[1].x) + (v[2].x + v[3].x)) + ((v[4].x + v[5].x) + (v[6].x + v[7].x)),
                       ((v[0].y + v[1].y) + (v[2].y + v[3].y)) + ((v[4].y + v[5].y) + (v[6].y + v[7].y)));
}
template <int STRIDE> __device__ __forceinline__ float4 sum8x4(uint32_t a) {
    float4 v[8];
#pragma unroll
    for (int i = 0; i < 8; i++) v[i] = lds128(a + i * STRIDE);
    return make_float4(((v[0].x + v[1].x) + (v[2].x + v[3].x)) + ((v[4].x + v[5].x) + (v[6].x + v[7].x)), ((v[0].y + v[1].y) + (v[2].y + v[3].y)) + ((v[4].y + v[5].y) + (v[6].y + v[7].y)),
                       ((v[0].z + v[1].z) + (v[2].z + v[3].z)) + ((v[4].z + v[5].z) + (v[6].z + v[7].z)), ((v[0].w + v[1].w) + (v[2].w + v[3].w)) + ((v[4].w + v[5].w) + (v[6].w + v[7].w)));
}
__device__ __forceinline__ float rcp(float x) { float y; asm("rcp.approx.ftz.f32 %0, %1;" : "=f"(y) : "f"(x)); return y; }
__device__ __forceinline__ float sigmoid_f(float x) { return rcp(1.0f + ex2(x * -1.4426950408889634f)); }
__device__ __forceinline__ uint32_t silu2(uint32_t c) { const float a = blo(c), b = bhi(c); return pack2(a * sigmoid_f(a), b * sigmoid_f(b)); }
__device__ __forceinline__ void ln_consts(float mean, float var, uint32_t& mu2, float& rs) {
    mu2 = pack2(mean, mean);
    float sd; asm("sqrt.approx.ftz.f32 %0, %1;" : "=f"(sd) : "f"(rbf(rbf(var) + 1e-5f)));
    rs = rcp(rbf(sd));
}
__device__ __forceinline__ uint32_t ln_norm(uint32_t x2, uint32_t mu2, float rs) { const uint32_t d = sub2(x2, mu2); return pack2(blo(d) * rs, bhi(d) * rs); }

__global__ void __launch_bounds__(NALL, 1) fused_kernel(const __nv_bfloat16* const px, const __nv_bfloat16* const pc, const __nv_bfloat16* const pk, const __nv_bfloat16* const pwm,
                                                        const __nv_bfloat16* const pwq, char* const X, const __grid_constant__ Params P) {
    extern __shared__ __align__(1024) unsigned char smem[];
    const uint32_t sb = smem_u32(smem);
    const int tid = threadIdx.x, w = tid >> 5, lane = tid & 31, g = lane >> 2, t = lane & 3;
    const int cta = blockIdx.x, head = cta >> 2, bat = (cta & 3) * 2 + (w >> 2);
    const uint32_t s0 = sb + w * UNIT, s2 = s0 + 4 * REG;
    const uint32_t bar0 = sb + SM_BAR + w * 64;
    const uint32_t barC = bar0 + 32;
    const uint32_t scr = sb + SM_SCR, myscr = scr + w * SCR;
    pf_if((const char*)pwm + ((cta * 4 + (tid >> 4)) * (6 * DM * 2) + (tid & 15) * 128), w, 2);
    pf_if((const char*)pk + (unsigned)(((((cta & 3) * 2 + (w & 1)) * NH + head) * SK + (SK - WIN - 16) + (w >> 1) * 16) * (DH * 2) + lane * 128), w - 2, PFK);
    const int rid = !(cta & 1) ? cta >> 1 : (cta >> 2) + (cta & 2 ? 64 : 96);
    const unsigned t_start = now_ns();
    uint64_t pol;
    asm volatile("createpolicy.fractional.L2::evict_first.b64 %0, 1.0;" : "=l"(pol));
    auto go_first = [&](uint32_t wbar, uint32_t par) {
        for (int n = 0;; n++) {
            if (mbar_test(wbar, par)) return false;
            if (mbar_test(sb + SM_BG, 0)) return true;
            if (n > SPIN_MAX * 4) __trap();
            nap(20);
        }
    };
    if (w == 9) {
        const uint32_t sl = sb + SM_PR + lane * 16;
        char* const pl = X + blk(X_PRB, cta >> 1, lane & 1) + (lane >> 1) * 256 + (cta & 1) * 128;
        {
            char* const ps = X + X_PRB + (cta >> 1) * 8192 + g * 256 + (cta & 1) * 128 + t * 16;
            sts32u(sl, 0);
#pragma unroll
            for (int i = 0; i < 4; i++) stg_rlx128(ps + i * 2048, make_uint4(1, 1, 1, 1));
            __syncwarp();
        }
        unsigned v; asm volatile("atom.relaxed.gpu.global.add.u32 %0, [%1], 1;" : "=r"(v) : "l"(pl) : "memory");
        unsigned tag = ldg_rlx32(X + X_EPOCH);
        if (lane == 0) pf_bulk(pwq + (size_t)cta * QN * 1024, QN * 2048);
        if (lane == 0) sts32u(sb + SM_AN, t_start + ANCH0);
        if (lane < 8) sts32u(sb + SM_BAR + lane * 64 + 56, 0);
        unsigned side;
        {
            int d, n = 0;
#pragma unroll 1
            for (int r = 0; r < 4; r++) {
                if (v == SENT) __trap();
                asm volatile("cp.async.cg.shared.global [%0], [%1], 16;" :: "r"(sl), "l"(pl) : "memory");
                unsigned m;
                do {
                    m = __ballot_sync(~0u, lds32u(sl));
                    d = __popc(m & 0xAAAAAAAAu) - __popc(m & 0x55555555u);
                    if (++n > SPIN_MAX) __trap();
                } while (abs(d) < 6 && m != ~0u);
                if (abs(d) >= 6) break;
                asm volatile("cp.async.wait_all;" ::: "memory");
                sts32u(sl, 0);
                asm volatile("atom.relaxed.gpu.global.add.u32 %0, [%1], 1;" : "=r"(v) : "l"(pl) : "memory");
            }
            side = d > 0;
            tag++;
            if (lane == 0) { sts32u(sb + SM_SIDE, side); sts32u(sb + SM_TAG, tag); }
            bar_arrive<B_SIDE, NTHR>();
        }
        asm volatile("cp.async.wait_all;" ::: "memory");
        while (now_ns() - t_start < PACE0) nap(200);
        for (int n = 0; n < SPIN_MAX; n++) {
            const uint32_t wb = sb + SM_BAR + (lane & 7) * 64;
            const unsigned seen = lds32u(wb + 56), u = seen + ((lane >> 3) & 1), t1 = now_ns();
            const unsigned more = mbar_test(wb + (u < 6 ? u : (~u & 2) + (u & 1)) * 8, u < 6 ? 0 : ((u - 2) >> 2) & 1);
            const unsigned lo = __reduce_min_sync(~0u, seen), sum = __reduce_add_sync(~0u, lane < 8 ? seen + more : lane < 16 ? more : 0);
            if (lo == 30) break;
            if (lo && lane < 2) stg_rlx64(X + X_LAG + (cta >> 5) * 8192 + lane * 4096 + (cta & 31) * 128, t1 - sum * TAU, tag);
            uint2 a = make_uint2(0, 0);
            if (cta == 0) {
                uint2 u[4];
#pragma unroll
                for (int i = 0; i < 4; i++) u[i] = ldg_rlx64(X + blk(X_LAG, i, side) + lane * 128);
                const int s = __reduce_add_sync(~0u, (int)(u[0].x + u[1].x + u[2].x + u[3].x - 4 * t_start));
                if (__all_sync(~0u, (u[0].y == tag) & (u[1].y == tag) & (u[2].y == tag) & (u[3].y == tag)) && lane < 2) {
                    a = make_uint2(t_start + s / NCTA, tag);
                    stg_rlx64(X + X_ANC + lane * 4096, a.x, tag);
                }
            } else if (lane == 0) a = ldg_rlx64(X + blk(X_ANC, 0, side));
            if (lane == 0 && a.y == tag) sts32u(sb + SM_AN, a.x - LEAD);
            __syncwarp();
            nap(PNAP);
        }
        {
            bar_sync<B_ML, NTHR>();
            const float2 ml = lds64(sb + SM_ML + (lane & 7) * 8);
            float M = fmaxf(ml.x, __shfl_xor_sync(~0u, ml.x, 1)); M = fmaxf(M, __shfl_xor_sync(~0u, M, 2));
            const float e = ex2((ml.x - M) * 1.4426950408889634f);
            float L = e * ml.y; L += __shfl_xor_sync(~0u, L, 1); L += __shfl_xor_sync(~0u, L, 2);
            if (lane < 8) sts32(sb + SM_ML + 64 + lane * 4, e * rcp(L));
        }
        bar_arrive<B_RDY, NALL>();
        bar_sync<B_STG, 64>();
        {
            const char* const pp = pin(X + blk(X_PART, cta, side) + lane * 16);
            char* const xo = pin(X + (lane >> 4) * 16384 + blk(X_X1, (cta >> 3) & 1, lane >> 3) + (cta & 7) * 512 + (cta >> 4) * 64 + (lane & 7) * 8);
            const float4 gx = lds128(scr + SC_RX + (lane & 7) * 16);
            const unsigned t0 = lds32u(sb + SM_AN) + 256 * TAU + RT0 + (cta & 7) * (TAU / 8);
            while ((int)(now_ns() - t0) < 0) nap(20);
            uint4 v[8]; int n = 0;
            float a[4];
#pragma unroll
            for (int j = 0; j < 8; j++) v[j] = ldg_b128(pp + j * 512);
            while (true) {
#define RSUM(f) (((__uint_as_float(v[0].f) + __uint_as_float(v[1].f)) + (__uint_as_float(v[2].f) + __uint_as_float(v[3].f))) + ((__uint_as_float(v[4].f) + __uint_as_float(v[5].f)) + (__uint_as_float(v[6].f) + __uint_as_float(v[7].f))))
                const bool ok = __all_sync(~0u, max(max(max(v[0].x, v[1].x), max(v[2].x, v[3].x)), max(max(v[4].x, v[5].x), max(v[6].x, v[7].x))) != SENT);
                a[0] = RSUM(x); a[1] = RSUM(y); a[2] = RSUM(z); a[3] = RSUM(w);
                asm volatile("" : "+f"(a[0]), "+f"(a[1]), "+f"(a[2]), "+f"(a[3]));
                if (ok) break;
#pragma unroll
                for (int j = 0; j < 8; j++) if (v[j].x == SENT) v[j] = ldg_b128(pp + j * 512);
                if (++n > SPIN_MAX) __trap();
            }
#pragma unroll
            for (int i = 0; i < 4; i++) a[i] += __shfl_xor_sync(~0u, a[i], 8);
#pragma unroll
            for (int i = 0; i < 4; i++) a[i] += __shfl_xor_sync(~0u, a[i], 16);
            stg_rlx64(xo, add2(__float_as_uint(gx.z), mul2(__float_as_uint(gx.x), pack2(a[0], a[1]))), add2(__float_as_uint(gx.w), mul2(__float_as_uint(gx.y), pack2(a[2], a[3]))));
        }
        if (rid >= DN0) {
            const unsigned c1 = clock();
            const int f = rid - DN0;
            const char* const rp = X + (rid & (XC - 1)) * 16384 + blk(X_X1, f >> 4, side) + (rowoff(g, f * 16 + t * 4) & 4092);
            unsigned r[4]; int n = 0;
            spin(c1, HD0 - 450);
            do {
#pragma unroll
                for (int i = 0; i < 4; i++) r[i] = ldg_rlx32(rp + i * 16);
                if (++n > SPIN_MAX) __trap();
            } while (max(max(r[0], r[1]), max(r[2], r[3])) == SENT);
            const unsigned sel = (f & 1) ? 0x7632 : 0x5410;
            sts64(sb + SM_MN + 256 + lane * 8, __uint_as_float(__byte_perm(r[0], r[1], sel)), __uint_as_float(__byte_perm(r[2], r[3], sel)));
            __syncwarp();
            spin(c1, HD0);
        }
        if (lane == 0) asm volatile("mbarrier.arrive.shared::cta.b64 _, [%0];" :: "r"(sb + SM_BG) : "memory");
    } else if (w == 8) {
        const int row0 = ((cta & 3) * 2 * NH + head) * SK + (SK - WIN);
        auto kv_unit = [&](int u) {
            const uint32_t b = sb + SM_BAR + (u & 7) * 64 + (u >> 3) * 8;
            mbar_expect(b, UNIT);
            tma_kv(sb + (u >> 3) * REG + (u & 7) * UNIT, (u & 8) ? &P.v : &P.k, row0 + ((u >> 2) & 1) * NH * SK + (u & 3) * 16 + tile_key(u >> 4), b, pol);
        };
        if (elect()) {
            mbar_init(sb + SM_BM, 1);
#pragma unroll
            for (int i = 0; i < 8; i++) mbar_init(sb + SM_BAR + i * 64 + 48, 1);
            asm volatile("fence.mbarrier_init.release.cluster;" ::: "memory");
            mbar_expect(sb + SM_BM, 512 * 16);
            tma2d(sb + 4 * REG, &P.wm, cta * 8, 0, sb + SM_BM); tma2d(sb + 4 * REG + 256 * 16, &P.wm, cta * 8, 256, sb + SM_BM);
#pragma unroll
            for (int i = 0; i < 8; i++) { const uint32_t b = sb + SM_BAR + i * 64 + 48; mbar_expect(b, UNIT); tma2d(sb + 5 * REG + i * UNIT, &P.wq, cta * 32, i * 64, b); }
            mbar_init(sb + SM_BN, 1); mbar_init(sb + SM_BT, 1); mbar_init(sb + SM_BG, 1);
#pragma unroll
            for (int i = 0; i < 48; i++) mbar_init(sb + SM_BAR + (i & 7) * 64 + (i >> 3) * 8, 1);
            asm volatile("fence.mbarrier_init.release.cluster;" ::: "memory");
        }
        __syncwarp();
        bar_arrive<B_INIT, NTHR>();
        {
            uint32_t mine = lane >= NTRK ? 0 : lane < 8 ? sb + SM_BAR + lane * 64 + 48 : sb + SM_BM;
            int next = 0, lim = 32, n = 0;
            while (next < 48) {
                const bool idle = lane < (next < PSW ? PWIN0 : PWIN) && (mine == 0 || mbar_test(mine, 0));
                const unsigned m = __ballot_sync(~0u, idle);
                const int u = next + __popc(m & ((1u << lane) - 1));
                if (idle) {
                    mine = 0;
                    if (u < lim) { kv_unit(u); mine = sb + SM_BAR + (u & 7) * 64 + (u >> 3) * 8; }
                }
                next = min(next + __popc(m), lim);
                if (next == lim) {
                    if (lim == 32) { bar_sync<B_MOD, NTHR>(); } else if (lim == 40) { bar_sync<B_WQ, NTHR>(); }
                    lim += 8;
                }
                if (!m) nap(30);
                if (++n > SPIN_MAX) __trap();
            }
        }
        if (lane < 5) pf_map(&P.wn + lane);
        float m[4][4] = {};
        auto late_mod = [&](uint32_t a, int h) {
            const int lrow = (lane & 7) + ((lane >> 4) << 3), lch = (lane >> 3) & 1;
            const uint32_t a0 = a + lrow * 32 + ((lch ^ ((lrow >> 2) & 1)) << 4);
            const uint32_t c0 = sb + SM_SC + h * 4096 + (lane & 7) * 128 + (((lane >> 3) ^ (lane & 7)) << 4);
#pragma unroll
            for (int j = 0; j < 8; j++) {
                uint32_t c[4], r[4], u[4];
                ldsm(c, (c0 + (j >> 1) * 1024) ^ ((j & 1) << 6)); ldsm_t(r, a0 + j * 1024); ldsm_t(u, a0 + j * 1024 + 512);
                mma(m[(j & 1) * 2], r, c[0], c[1]); mma(m[(j & 1) * 2 + 1], u, c[2], c[3]);
            }
        };
        if (rid < 96) {
#pragma unroll 1
            for (int h = 0; h < 2; h++) {
                if (lane == 0) { mbar_expect(sb + SM_BN, 8192); tma2d(sb + SM_MN, &P.wn, 2 * DM + rid * 16, h * 256, sb + SM_BN); }
                mbar_wait(sb + SM_BN, h);
                late_mod(sb + SM_MN, h);
                asm volatile("" :: "f"(m[0][0]), "f"(m[1][0]), "f"(m[2][0]), "f"(m[3][0]) : "memory");
                __syncwarp();
            }
#pragma unroll
            for (int e = 0; e < 4; e++) {
                float v = rbf((m[0][e] + m[1][e]) + (m[2][e] + m[3][e]));
                if (rid >= 64) v += 1.0f;
                stg_rlx16(X + X_MOD + (rid >> 5) * 8192 + rowoff(2 * t + (e & 1), (rid & 31) * 16 + g + (e >> 1) * 8), pack2(v, 0.f));
            }
        }
        {
            const unsigned side = lds32u(sb + SM_SIDE);
#pragma unroll
            for (int i = 0; i < 8; i++) stg_rlx128(X + blk(X_PART, cta, side) + i * 512 + lane * 16, make_uint4(SENT, SENT, SENT, SENT));
            if (lane == 0) stg_rlx32(X + X_SIDE + cta * 4, side);
        }
        bar_sync<B_Q, NTHR>();
        if (lane == 0) {
            const unsigned tag = lds32u(sb + SM_TAG);
            fence_gpu();
            red_add(X + X_READY, 1);
            int n = 0;
            while ((int)(ldg_acq32(X + X_READY) - tag * NCTA) < 0) { nap(1000); if (++n > SPIN_MAX) __trap(); }
            if (cta == 0) stg_rlx32(X + X_EPOCH, tag);
        }
        __syncwarp();
        {
            stg_rlx128(X + blk(X_Q, head >> 1, 0) + (head & 1) * 2048 + g * 256 + (cta & 3) * 64 + t * 16, make_uint4(0, 0, 0, 0));
            stg_rlx128(X + blk(X_Q, head >> 1, 1) + (head & 1) * 2048 + g * 256 + (cta & 3) * 64 + t * 16, make_uint4(0, 0, 0, 0));
            stg_rlx64(X + blk(X_M1, cta >> 5, lane >> 4) + (cta & 31) * 128 + (lane & 15) * 8, 0, 0);
            const int wt = (cta & 3) * 32 + lane;
            const unsigned mask = __ballot_sync(~0u, blk(X_PART, wt, ldg_rlx32(X + X_SIDE + wt * 4)) & 4096);
            if (lane == 0) sts32u(sb + SM_MASK, mask);
            if (lane < 8) {
                const int task = cta;
                const int rb = task >> 4, c = ((task & 15) >> 1) * 64 + (task & 1) * 4 + ((lane & 7) >> 1) + (lane & 1) * 8;
                const uint2 ga = ldg_rlx64(X + X_MOD + rowoff(rb, c));
                const unsigned short* const xp = (const unsigned short*)px + rb * DM + c;
                sts128(scr + (lane >> 3) * SCR + SC_RX + (lane & 7) * 16, make_uint4(ga.x, ga.y, xp[0] | (xp[16] << 16), xp[32] | (xp[48] << 16)));
            }
            if (rid < NF1) {
#pragma unroll 1
                for (int i = 0; i < 4; i++) {
                    uint4 v[8];
#pragma unroll
                    for (int j = 0; j < 8; j++) v[j] = ldg_rlx128(X + X_MOD + 8192 + (i * 8 + j) * 512 + lane * 16);
#pragma unroll
                    for (int j = 0; j < 8; j++) sts128(sb + SM_MN + (i * 8 + j) * 512 + lane * 16, v[j]);
                }
            }
        }
        bar_arrive<B_RDY, NALL>();
        bar_arrive<B_STG, 64>();
        unsigned t_ref = 0;
        auto until = [&](int x) { while ((int)(now_ns() - t_ref) < x) nap(20); };
        if (elect()) {
#pragma unroll 1
            for (int i = 0; i < 8; i++) { int n = 0; while (lds32u(sb + SM_BAR + i * 64 + 56) < 30) { nap(100); if (++n > SPIN_MAX) __trap(); } }
            t_ref = lds32u(sb + SM_AN) + 256 * TAU + (cta & 7) * (TAU / 8);
            if (rid < NF1) {
#pragma unroll
                for (int i = 0; i < 4; i++) mbar_expect(sb + SM_BAR + i * 64 + 48, 2 * UNIT);
#pragma unroll 1
                for (int i = 0; i < 4; i++) {
                    const uint32_t b = sb + SM_BAR + i * 64 + 48;
                    until(W0 + i * WS);
                    tma5d(sb + 2 * REG + i * UNIT, &P.wg, rid * 16, i * 4, b); tma5d(sb + 2 * REG + 16384 + i * UNIT, &P.wu, rid * 16, i * 4, b);
                }
            }
        }
        if (rid >= DN0) {
            bar_sync<B_LAST, NTHR>();
            if (elect()) {
                mbar_expect(sb + SM_BN, 16384); mbar_expect(sb + SM_BT, FF * 32);
                until(WD0);
                tma5d(sb + 2 * REG + 16384, &P.wd, (rid - DN0) * 16, 0, sb + SM_BT); tma5d(sb + 2 * REG + 16384 + 43 * 512, &P.wd, (rid - DN0) * 16, 43, sb + SM_BT);
                tma2d(sb + 2 * REG, &P.wn, 2 * DM + rid * 16, 0, sb + SM_BN); tma2d(sb + 2 * REG + 8192, &P.wn, 2 * DM + rid * 16, 256, sb + SM_BN);
            }
        }
        __syncwarp();
        if (rid >= DN0) {
            mbar_wait(sb + SM_BN, 0);
            late_mod(sb + 2 * REG, 0); late_mod(sb + 2 * REG + 8192, 1);
#pragma unroll
            for (int e = 0; e < 2; e++)
                sts32u(sb + SM_MN + g * 32 + e * 16 + t * 4, movm(pack2((m[0][2 * e] + m[1][2 * e]) + (m[2][2 * e] + m[3][2 * e]), (m[0][2 * e + 1] + m[1][2 * e + 1]) + (m[2][2 * e + 1] + m[3][2 * e + 1]))));
            bar_arrive<B_DN, NTHR>();
        }
    }
    if (w >= 8) {
        if (rid < NF1) {
            const int b = (tid - 256) >> 3, c = tid & 7;
            char* const ho = pin(X + X_HM + (rid >> 4) * 8192 + ((rid >> 1) & 7) * 512 + b * 64 + (c & 3) * 16 + (rid & 1) * 8 + (c >> 2) * 4);
            const uint32_t pi = pin(scr + SC_F1 + c * 144 + b * 16), si = pin(sb + SM_ST + b * 64);
            bar_sync<B_PRE, NALL>();
            const float4 C = sum8x4<UNIT>(sb + REG + c * 144 + b * 16), S = sum8x4<UNIT>(sb + REG + 1152 + c * 144 + b * 16);
            sts128f(sb + SM_PR + lane * 16, C.x, C.y, C.z, C.w); sts128f(sb + SM_PR + lane * 16, S.x, S.y, S.z, S.w);
            sts128(sb + SM_PR + lane * 16, make_uint4(pi, si, (uint32_t)(size_t)ho, (uint32_t)((size_t)ho >> 32)));
            bar_sync<B_FIN, NALL>();
            const float4 s0_ = lds128(si), s1_ = lds128(si + 16), s2_ = lds128(si + 32), s3_ = lds128(si + 48);
            const float4 p = sum8x4<SCR>(pi);
            const float mean = (((s0_.x + s0_.z) + (s1_.x + s1_.z)) + ((s2_.x + s2_.z) + (s3_.x + s3_.z))) * (1.0f / DM);
            const float sq = (((s0_.y + s0_.w) + (s1_.y + s1_.w)) + ((s2_.y + s2_.w) + (s3_.y + s3_.w))) * (1.0f / DM);
            float rs; asm("rsqrt.approx.ftz.f32 %0, %1;" : "=f"(rs) : "f"(fmaxf(sq - mean * mean, 0.f) + 1e-5f));
            const float g0 = rs * (p.x - mean * C.x) + S.x, g1 = rs * (p.y - mean * C.y) + S.y, u0 = rs * (p.z - mean * C.z) + S.z, u1 = rs * (p.w - mean * C.w) + S.w;
            const unsigned hw = pack2(sigmoid_f(g0) * u0, sigmoid_f(g1) * u1);
            stg_rlx32(ho, hw); stg_rlx32(ho + 4096, hw);
        }
        return;
    }
    const unsigned ce = (lane >> 3) * (DM * 2) + w * 128 + (lane & 7) * 16;
    const uint4 ca = ldg_nc((const char*)pc + ce), cb = ldg_nc((const char*)pc + ce + 4 * DM * 2);
    const uint4 xa = ldg_nc((const char*)px + w * (DM * 2) + lane * 16), xb = ldg_nc((const char*)px + w * (DM * 2) + lane * 16 + 512);
    const uint4 xc = ldg_nc((const char*)px + ce), xd = ldg_nc((const char*)px + ce + 4 * DM * 2);
    if (w >= 4) pf_map(&P.wm + (w & 3));
    char* const qout = X + blk(X_Q, head >> 1, tid >> 7) + (head & 1) * 2048 + ((tid >> 4) & 7) * 256 + (cta & 3) * 64 + (tid & 3) * 16 + ((tid >> 2) & 3) * 4;
    char* const mout = X + blk(X_M1, cta >> 5, w) + (cta & 31) * 128 + lane * 4;
    stg_rlx32(qout, 0);
    if (w < 2) stg_rlx32(mout, 0);
    uint32_t sc[8], xf[8];
    {
        const uint32_t a = (lane >> 3) * 128 + (((lane & 7) ^ (lane >> 3)) << 4), b = (lane & 7) * 128 + (((lane >> 3) ^ (lane & 7)) << 4);
        const uint32_t cs = sb + SM_SC + w * 1024;
        sts128(cs + a, make_uint4(silu2(ca.x), silu2(ca.y), silu2(ca.z), silu2(ca.w)));
        sts128(cs + 512 + (a ^ 64), make_uint4(silu2(cb.x), silu2(cb.y), silu2(cb.z), silu2(cb.w)));
        sts128(myscr + a, xc); sts128(myscr + 512 + (a ^ 64), xd);
        __syncwarp();
        ldsm(*(uint32_t(*)[4])&sc[0], cs + b); ldsm(*(uint32_t(*)[4])&sc[4], cs + (b ^ 64));
        ldsm(*(uint32_t(*)[4])&xf[0], myscr + b); ldsm(*(uint32_t(*)[4])&xf[4], myscr + (b ^ 64));
        __syncwarp();
    }
    {
        float v[16] = {blo(xa.x), bhi(xa.x), blo(xa.y), bhi(xa.y), blo(xa.z), bhi(xa.z), blo(xa.w), bhi(xa.w),
                       blo(xb.x), bhi(xb.x), blo(xb.y), bhi(xb.y), blo(xb.z), bhi(xb.z), blo(xb.w), bhi(xb.w)};
        float s = 0;
#pragma unroll
        for (int i = 0; i < 16; i++) s += v[i];
#pragma unroll
        for (int o = 16; o; o >>= 1) s += __shfl_xor_sync(~0u, s, o);
        s *= (1.0f / DM);
        float q2 = 0;
#pragma unroll
        for (int i = 0; i < 16; i++) q2 += (v[i] - s) * (v[i] - s);
#pragma unroll
        for (int o = 16; o; o >>= 1) q2 += __shfl_xor_sync(~0u, q2, o);
        uint32_t mu2; float rs; ln_consts(s, q2 * (1.0f / DM), mu2, rs);
        if (lane == 0) sts64(sb + SM_ST + w * 8, __uint_as_float(mu2), rs);
    }
    const int lrow = (lane & 7) + ((lane >> 4) << 3), lch = (lane >> 3) & 1;
    const uint32_t off64 = lrow * 64 + ((lch ^ ((lrow >> 1) & 3)) << 4);
    const uint32_t off128 = lrow * 128 + ((lch ^ (lane & 7)) << 4);
    bar_sync<B_INIT, NTHR>();
    mbar_wait(sb + SM_BM, 0);
    {
        float a[4] = {0, 0, 0, 0}, b[4] = {0, 0, 0, 0};
        uint32_t r[4], u[4];
        ldsm_t(r, sb + 4 * REG + (w * 64 + lane) * 16); ldsm_t(u, sb + 4 * REG + (w * 64 + 32 + lane) * 16);
        mma(a, sc[0], 0, sc[1], 0, r[0], r[1]); mma(b, sc[4], 0, sc[5], 0, u[0], u[1]);
        mma(a, sc[2], 0, sc[3], 0, r[2], r[3]); mma(b, sc[6], 0, sc[7], 0, u[2], u[3]);
        sts64(myscr + SC_M + lane * 8, a[0] + b[0], a[1] + b[1]);
    }
    bar_arrive<B_MOD, NTHR>();
    bar_sync<B_ALL, 256>();
    if (w < 2) {
        const float2 m = sum8(scr + SC_M + lane * 8);
        stg_rlx32(mout, ~pack2(m.x, m.y));
    }
    if (tid < 8 * XC) stg_rlx128(X + X_X1 + (cta * 8 * XC + tid) * 16, make_uint4(SENT, SENT, SENT, SENT));
    else if (tid >= 232) stg_rlx128(X + X_HM + (cta * 24 + tid - 232) * 16, make_uint4(SENT, SENT, SENT, SENT));
    {
        const float2 st = lds64(sb + SM_ST + g * 8);
#pragma unroll
        for (int i = 0; i < 8; i++) xf[i] = ln_norm(xf[i], __float_as_uint(st.x), st.y);
    }
    {
        unsigned sv[8], cv[8]; int n = 0;
        bar_sync<B_SIDE, NTHR>();
        const char* const mp = X + blk(X_M1, w >> 2, lds32u(sb + SM_SIDE)) + (w & 3) * 1024 + lane * 4;
        if (lane == 0) while (!ldg_rlx32(mp + 16384 + 7 * 128)) { nap(40); if (++n > SPIN_MAX) __trap(); }
        __syncwarp();
#pragma unroll
        for (int j = 0; j < 8; j++) { sv[j] = ldg_rlx32(mp + j * 128); cv[j] = ldg_rlx32(mp + 16384 + j * 128); }
        while (true) {
            unsigned m = ~0u;
#pragma unroll
            for (int j = 0; j < 8; j++) m = min(m, min(sv[j], cv[j]));
            if (__all_sync(~0u, m)) break;
#pragma unroll
            for (int j = 0; j < 8; j++) { if (!sv[j]) sv[j] = ldg_rlx32(mp + j * 128); if (!cv[j]) cv[j] = ldg_rlx32(mp + 16384 + j * 128); }
            if (++n > SPIN_MAX) __trap();
        }
#pragma unroll
        for (int j = 0; j < 8; j++) xf[j] = add2(mul2(xf[j], add2(~cv[j], ONE2)), ~sv[j]);
        mbar_wait(bar0 + 48, 0);
        float acc[4][4] = {};
#pragma unroll
        for (int j = 0; j < 4; j++) {
            uint32_t r[4], u[4];
            ldsm_t(r, s2 + REG + j * 1024 + off64); ldsm_t(u, s2 + REG + j * 1024 + (off64 ^ 32));
            mma(acc[0], xf[2 * j], 0, xf[2 * j + 1], 0, r[0], r[2]); mma(acc[1], xf[2 * j], 0, xf[2 * j + 1], 0, r[1], r[3]);
            mma(acc[2], xf[2 * j], 0, xf[2 * j + 1], 0, u[0], u[2]); mma(acc[3], xf[2 * j], 0, xf[2 * j + 1], 0, u[1], u[3]);
        }
#pragma unroll
        for (int n2 = 0; n2 < 4; n2++) sts64(myscr + SC_Q + g * 160 + n2 * 32 + t * 8, acc[n2][0], acc[n2][1]);
    }
    bar_arrive<B_WQ, NTHR>();
    bar_sync<B_ALL, 256>();
    {
        const float2 s = sum8(scr + SC_Q + ((tid >> 4) & 7) * 160 + (tid & 15) * 8);
        stg_rlx32(qout, ~pack2(s.x, s.y));
    }
    uint32_t q[16];
    {
        int n = 0;
        const char* const qp = X + blk(X_Q, head >> 1, lds32u(sb + SM_SIDE)) + (head & 1) * 2048 + bat * 256 + t * 16;
        uint4 v[4];
#pragma unroll
        for (int j = 0; j < 4; j++) v[j] = ldg_rlx128(qp + j * 64);
        while (true) {
            bool bad[4];
#pragma unroll
            for (int j = 0; j < 4; j++) bad[j] = !min(min(v[j].x, v[j].y), min(v[j].z, v[j].w));
            if (!__any_sync(~0u, bad[0] | bad[1] | bad[2] | bad[3])) break;
#pragma unroll
            for (int j = 0; j < 4; j++) if (bad[j]) v[j] = ldg_rlx128(qp + j * 64);
            if (++n > SPIN_MAX) __trap();
        }
#pragma unroll
        for (int j = 0; j < 4; j++) { q[4 * j] = ~v[j].x; q[4 * j + 1] = ~v[j].y; q[4 * j + 2] = ~v[j].z; q[4 * j + 3] = ~v[j].w; }
    }
    bar_arrive<B_Q, NTHR>();

    float o[2][4] = {};
    float mrun = -3.0e38f, lrun = 0.f;
    uint32_t wa[16][4], pb[2];
#pragma unroll
    for (int i = 0; i < 16; i++) wa[i][0] = wa[i][1] = wa[i][2] = wa[i][3] = 0;
    constexpr float LOG2E = 1.4426950408889634f, SCALE = 0.08838834764831845f;
    const uint32_t offk = (lane & 15) * 128 + (((lane >> 4) ^ (lane & 7)) << 4);
    float p0, p1;
    auto scores = [&](uint32_t a0) {
        uint32_t kf[8][4];
#pragma unroll
        for (int j = 0; j < 8; j++) ldsm(kf[j], ((a0 + offk) ^ ((j & 3) << 5)) + (j >> 2) * 2048);
        float sa[4] = {0, 0, 0, 0}, sb2[4] = {0, 0, 0, 0};
#pragma unroll
        for (int j = 0; j < 8; j += 2) { mma(sa, kf[j], q[2 * j], q[2 * j + 1]); mma(sb2, kf[j + 1], q[2 * j + 2], q[2 * j + 3]); }
        uint32_t u = pack2(sa[0] + sb2[0], sa[2] + sb2[2]);
        u = pack2(blo(u) * SCALE, bhi(u) * SCALE);
        const float z0 = blo(u), z1 = bhi(u);
        float mx = fmaxf(z0, z1);
        mx = fmaxf(mx, __shfl_xor_sync(~0u, mx, 4)); mx = fmaxf(mx, __shfl_xor_sync(~0u, mx, 8)); mx = fmaxf(mx, __shfl_xor_sync(~0u, mx, 16));
        mx = fmaxf(mx, mrun);
        const float f = ex2((mrun - mx) * LOG2E);
        p0 = ex2((z0 - mx) * LOG2E); p1 = ex2((z1 - mx) * LOG2E);
        mrun = mx; lrun = lrun * f + (p0 + p1);
#pragma unroll
        for (int j = 0; j < 4; j++) { o[0][j] *= f; o[1][j] *= f; }
    };
    const int kvrow = (bat * NH + head) * SK + (SK - WIN) + (w & 3) * 16;
    const int wofs = (w * 8 + (cta & 7)) * TAU / 8;
    auto request = [&](int u) {
        sts32u(bar0 + 56, u - 1);
        while ((int)(now_ns() - lds32u(sb + SM_AN) - u * 8 * TAU - wofs) < 0) nap(20);
        const int sl = (~u & 2) + (u & 1);
        mbar_expect(bar0 + sl * 8, UNIT); tma_kv(s0 + sl * REG, &P.k + (u & 1), kvrow + tile_key(u >> 1), bar0 + sl * 8, pol);
    };
#pragma unroll 1
    for (int it = 0; it < NT - 1; it++) {
        const int si = it < 3 ? it : (it + 1) & 1;
        const uint32_t bar = bar0 + si * 16, a0 = s0 + si * 2 * REG;
        const uint32_t par = it < 3 ? 0 : ((it - 1) >> 1) & 1;
        const bool refill = lane == 0 && it >= 2;
        mbar_wait(bar, par);
        if (refill) {
            request(2 * it + 2);
            const int e = it - (it > WOA_READ ? WOA_READ + 1 : WOA_ISSUE);
            if (e == 0) mbar_expect(barC, 2 * UNIT);
            if (e == 0 || e == WO_GAP) tma2d(s2 + (e ? REG : 0), &P.wo, w * 64, head * 128 + (it > WOA_READ ? 64 : 0) + (e ? 32 : 0), barC);
        }
        __syncwarp();
        if (it == WOA_READ) {
            mbar_wait(barC, 1);
#pragma unroll
            for (int j = 0; j < 16; j++) ldsm_t(wa[j], s2 + (j >> 3) * REG + ((j >> 2) & 1) * 2048 + (off128 ^ ((j & 3) << 5)));
        }
        scores(a0);
        pb[0] = movm(pack2(p0, p0)); pb[1] = movm(pack2(p1, p1));
        mbar_wait(bar + 8, par);
        if (refill) request(2 * it + 3);
        __syncwarp();
        uint32_t vf[8][4];
#pragma unroll
        for (int j = 0; j < 8; j++) ldsm_t(vf[j], ((a0 + off128) ^ ((j & 3) << 5)) + (j >> 2) * 2048 + REG);
#pragma unroll
        for (int j = 0; j < 8; j++) { const bool on = (g >> 1) == (j >> 1); mma(o[j & 1], vf[j], on ? pb[0] : 0, on ? pb[1] : 0); }
    }
    {
        uint32_t wb[16][4];
        mbar_wait(bar0, 1);
        if (rid >= DN0) bar_arrive<B_LAST, NTHR>();
        scores(s0);
        lrun += __shfl_xor_sync(~0u, lrun, 4); lrun += __shfl_xor_sync(~0u, lrun, 8); lrun += __shfl_xor_sync(~0u, lrun, 16);
        if (lane == 0) sts64(sb + SM_ML + w * 8, mrun, lrun);
        bar_arrive<B_ML, NTHR>();
        pb[0] = movm(pack2(p0, p0)); pb[1] = movm(pack2(p1, p1));
        const uint32_t va = pin(s0 + REG + off128);
        auto load_wb = [&](int j) { ldsm_t(wb[j], (va ^ ((j & 3) << 5)) + (3 + (j >> 3)) * REG + ((j >> 2) & 1) * 2048); };
        mbar_wait(barC, 0);
#pragma unroll
        for (int j = 0; j < NPRE; j++) load_wb(j);
        const uint32_t ho = pin(s0 + w * 16 + ((lane & 7) >> 1) * 64 + ((lane >> 3) & 1) * 32 + (lane & 1) * 16), oa = pin(sb + (lane & 7) * (UNIT + 16) + (lane >> 3) * 16);
        const uint32_t rd = pin((t >> 1) * 16 + w * 2 + (g >> 2));
        char* const pp = pin(X + X_PART + ((cta & 3) * 32 + rd) * 8192 + head * 128 + (g & 3) * 32 + (t & 1) * 16);
        const uint32_t ln = pin(lane);
        mbar_wait(bar0 + 8, 1);
        {
            uint32_t vf[8][4];
            float o2[2][4] = {};
#pragma unroll
            for (int j = 0; j < 8; j++) ldsm_t(vf[j], (va ^ ((j & 3) << 5)) + (j >> 2) * 2048);
#pragma unroll
            for (int j = 0; j < 8; j++) { const bool on = (ln >> 3) == (j >> 1); mma((j & 2) ? o2[j & 1] : o[j & 1], vf[j], on ? pb[0] : 0, on ? pb[1] : 0); }
            asm volatile("stmatrix.sync.aligned.m8n8.x2.trans.shared.b16 [%0], {%1,%2};" :: "r"(ho), "r"(pack2(o[0][0] + o2[0][0], o[0][2] + o2[0][2])), "r"(pack2(o[1][0] + o2[1][0], o[1][2] + o2[1][2])) : "memory");
        }
        bar_sync<B_RDY, NALL>();
        float y[4][4] = {};
        uint32_t ob[4][4];
#pragma unroll
        for (int i2 = 0; i2 < 4; i2++) ldsm(ob[i2], oa + i2 * 64);
        const float2 f = lds64(sb + SM_ML + 64 + (ln & 3) * 8);
        const unsigned half = (lds32u(sb + SM_MASK) >> rd & 1) * 4096;
#pragma unroll
        for (int j = NPRE; j < 16; j++) load_wb(j);
#pragma unroll
        for (int j = 0; j < 8; j++)
#pragma unroll
            for (int i = 0; i < 4; i++) mma(y[i], j < 4 ? wa[j * 4 + i] : wb[(j - 4) * 4 + i], ob[j >> 1][2 * (j & 1)], ob[j >> 1][2 * (j & 1) + 1]);
        uint32_t r[4];
#pragma unroll
        for (int i = 0; i < 4; i++) {
            const float lo = f.x * y[i][0] + f.y * y[i][1], hi = f.x * y[i][2] + f.y * y[i][3];
            r[i] = __float_as_uint(((ln & 1) ? hi : lo) + __shfl_xor_sync(~0u, (ln & 1) ? lo : hi, 1));
        }
        asm("min.u32 %0, %0, 0xFFFFFFFE;" : "+r"(r[0]));
        stg_b128(pp + half, make_uint4(r[0], r[1], r[2], r[3]));
    }
    const unsigned side = lds32u(sb + SM_SIDE);
    const char* const x1p = X + (rid & (XC - 1)) * 16384;
    if (rid < NF1) {
        uint32_t wg[4][4], wu[4][4];
        const char* const xp = pin(x1p + blk(X_X1, w >> 2, side) + (w & 3) * 1024 + lane * 16);
        float4 c1[2], sv[2];
#pragma unroll
        for (int h = 0; h < 2; h++) { sv[h] = lds128(sb + SM_MN + (w * 2 + h) * 512 + lane * 16); c1[h] = lds128(sb + SM_MN + 8192 + (w * 2 + h) * 512 + lane * 16); }
        const uint32_t po = pin(myscr + SC_F1 + g * 144 + t * 32), so = pin(t == (g >> 1) ? sb + SM_ST + g * 64 + w * 8 : myscr + 1792 + lane * 8), odd = pin(g & 1);
        const uint32_t wbar = sb + SM_BAR + (w >> 1) * 64 + 48;
        uint4 x0, x1;
        const bool early = go_first(wbar, 1);
        if (early) { spin(clock(), (7 - w) * XDW); x0 = ldg_rlx2x64(xp); x1 = ldg_rlx2x64(xp + 512); mbar_wait(wbar, 1); }
#pragma unroll
        for (int j = 0; j < 4; j++) {
            const uint32_t a = sb + 2 * REG + w * 2048 + (((lane & 7) >> 1) + (lane & 1) * 4 + j * 8 + (lane >> 4) * 32) * 32 + ((lch ^ (lane & 1)) << 4);
            ldsm_t(wg[j], a); ldsm_t(wu[j], a + 16384);
        }
        {
            float cg[4] = {}, cu[4] = {}, sg[4] = {}, su[4] = {};
#pragma unroll
            for (int j = 0; j < 4; j++) {
                const float4 a = c1[j & 1], b = sv[j & 1];
                const uint32_t a0 = __float_as_uint(j >> 1 ? a.z : a.x), a1 = __float_as_uint(j >> 1 ? a.w : a.y), b0 = __float_as_uint(j >> 1 ? b.z : b.x), b1 = __float_as_uint(j >> 1 ? b.w : b.y);
                mma(cg, wg[j], a0, a1); mma(cu, wu[j], a0, a1); mma(sg, wg[j], b0, b1); mma(su, wu[j], b0, b1);
            }
            const uint32_t d = s0 + REG + g * 144 + t * 32;
            sts128f(d, cg[0], cg[2], cu[0], cu[2]); sts128f(d + 16, cg[1], cg[3], cu[1], cu[3]);
            sts128f(d + 1152, sg[0], sg[2], su[0], su[2]); sts128f(d + 1168, sg[1], sg[3], su[1], su[3]);
            bar_arrive<B_PRE, NALL>();
        }
        if (!early) { mbar_wait(sb + SM_BG, 0); spin(clock(), (7 - w) * XDW); x0 = ldg_rlx2x64(xp); x1 = ldg_rlx2x64(xp + 512); }
        int n = 0;
        while (true) {
            const bool b0 = max(x0.x, x0.z) == SENT, b1 = max(x1.x, x1.z) == SENT;
            if (!__any_sync(~0u, b0 | b1)) break;
            if (b0) x0 = ldg_rlx2x64(xp);
            if (b1) x1 = ldg_rlx2x64(xp + 512);
            if (++n > SPIN_MAX) __trap();
        }
        float sm[4] = {}, q0[4] = {}, q1[4] = {}, ag[2][4] = {}, au[2][4] = {};
        {
            const uint32_t a0[4] = {x0.x, x0.y, x0.z, x0.w}, a1[4] = {x1.x, x1.y, x1.z, x1.w};
            mma(sm, a0, ONE2, ONE2); mma(q0, a0, x0.x, x0.z); mma(q1, a0, x0.y, x0.w);
            mma(sm, a1, ONE2, ONE2); mma(q0, a1, x1.x, x1.z); mma(q1, a1, x1.y, x1.w);
#pragma unroll
            for (int j = 0; j < 4; j++) {
                const uint4 xv = (j & 1) ? x1 : x0; const float4 a = c1[j & 1];
                const uint32_t h0 = mul2(j >> 1 ? xv.z : xv.x, __float_as_uint(j >> 1 ? a.z : a.x)), h1 = mul2(j >> 1 ? xv.w : xv.y, __float_as_uint(j >> 1 ? a.w : a.y));
                mma(ag[j & 1], wg[j], h0, h1); mma(au[j & 1], wu[j], h0, h1);
            }
        }
        sts64(so, sm[0] + sm[2], odd ? q0[1] + q1[3] : q0[0] + q1[2]);
        sts128f(po, ag[0][0] + ag[1][0], ag[0][2] + ag[1][2], au[0][0] + au[1][0], au[0][2] + au[1][2]);
        sts128f(po + 16, ag[0][1] + ag[1][1], ag[0][3] + ag[1][3], au[0][1] + au[1][1], au[0][3] + au[1][3]);
        bar_arrive<B_FIN, NALL>();
    } else if (rid >= DN0) {
        const int f = rid - DN0;
        uint32_t wd[12][4];
        const char* const hp0 = pin(X + blk(X_HM, 0, side) + w * 512 + lane * 16);
        const char* const hp1 = pin(X + blk(X_HM, 1, side) + w * 512 + lane * 16);
        auto hm = [&](int j) { return ldg_rlx128((j & 1 ? hp1 : hp0) + (j >> 1) * 16384); };
        unsigned* const op = pin((unsigned*)P.out + (tid >> 3) * 256 + f * 8 + (tid & 7));
        const uint32_t po = pin(myscr + SC_DN + t * 160 + g * 4), pi = pin(scr + SC_DN + (tid >> 3) * 80 + (tid & 7) * 8), gi = pin(sb + SM_MN + tid * 4), first = pin(w < 2);
        uint4 hv[6]; int n = 0;
        auto first_poll = [&]() {
            spin(clock(), w * HDW);
#pragma unroll
            for (int j = 0; j < 6; j++) hv[j] = (j < 5 || w < 3) ? hm(j) : make_uint4(0, 0, 0, 0);
        };
        const bool early = go_first(sb + SM_BT, 0);
        if (early) { first_poll(); mbar_wait(sb + SM_BT, 0); }
#pragma unroll
        for (int j = 0; j < 12; j++)
            if (j < 10 || w < 3) ldsm_t(wd[j], sb + 2 * REG + 16384 + (w + (j >> 1) * 8) * 1024 + (j & 1) * 512 + (((lane & 7) >> 1) + (lane & 1) * 4 + (lane >> 4) * 8) * 32 + ((lch ^ (lane & 1)) << 4));
            else wd[j][0] = wd[j][1] = wd[j][2] = wd[j][3] = 0;
        if (!early) { mbar_wait(sb + SM_BG, 0); first_poll(); }
        while (true) {
            unsigned m[6];
#pragma unroll
            for (int j = 0; j < 6; j++) m[j] = max(max(hv[j].x, hv[j].y), max(hv[j].z, hv[j].w));
            if (__all_sync(~0u, max(max(max(m[0], m[1]), m[2]), max(max(m[3], m[4]), m[5])) != SENT)) break;
#pragma unroll
            for (int j = 0; j < 6; j++) if (m[j] == SENT) hv[j] = hm(j);
            if (++n > SPIN_MAX) __trap();
        }
        float d[4][4] = {};
#pragma unroll
        for (int j = 0; j < 6; j++) { mma(d[(2 * j) & 3], wd[2 * j], hv[j].x, hv[j].y); mma(d[(2 * j + 1) & 3], wd[2 * j + 1], hv[j].z, hv[j].w); }
#pragma unroll
        for (int e = 0; e < 4; e++) sts32(po + (e & 1) * 80 + (e >> 1) * 32, (d[0][e] + d[1][e]) + (d[2][e] + d[3][e]));
        if (!first) bar_arrive<B_DN, NTHR>();
        else {
            bar_sync<B_DN, NTHR>();
            const float2 s = sum8(pi);
            const unsigned gw = lds32u(gi), res = lds32u(gi + 256);
            asm volatile("st.global.u32 [%0], %1;" :: "l"(op), "r"(add2(res, mul2(gw, pack2(s.x, s.y)))) : "memory");
        }
    }
}

typedef CUresult (*EncodeFn)(CUtensorMap*, CUtensorMapDataType, cuuint32_t, void*, const cuuint64_t*, const cuuint64_t*, const cuuint32_t*,
                             const cuuint32_t*, CUtensorMapInterleave, CUtensorMapSwizzle, CUtensorMapL2promotion, CUtensorMapFloatOOBfill);

void make2d(EncodeFn enc, CUtensorMap* m, const void* p, int rows, int cols, int brows, int bcols, CUtensorMapSwizzle sw) {
    cuuint64_t dims[2] = {(cuuint64_t)cols, (cuuint64_t)rows}, strides[1] = {(cuuint64_t)cols * 2};
    cuuint32_t box[2] = {(cuuint32_t)bcols, (cuuint32_t)brows}, es[2] = {1, 1};
    enc(m, CU_TENSOR_MAP_DATA_TYPE_BFLOAT16, 2, (void*)p, dims, strides, box, es, CU_TENSOR_MAP_INTERLEAVE_NONE, sw,
        CU_TENSOR_MAP_L2_PROMOTION_L2_128B, CU_TENSOR_MAP_FLOAT_OOB_FILL_NONE);
}
void make5d(EncodeFn enc, CUtensorMap* m, const void* p, int rows, int cols, int d, int nb) {
    const cuuint64_t rs = (cuuint64_t)cols * 2;
    cuuint64_t dims[5] = {(cuuint64_t)cols, 4, 2, (cuuint64_t)d / 4, (cuuint64_t)rows / (2 * d)}, strides[4] = {rs, rs * d, rs * 4, rs * 2 * d};
    cuuint32_t box[5] = {16, 4, 2, (cuuint32_t)d / 4, (cuuint32_t)nb}, es[5] = {1, 1, 1, 1, 1};
    enc(m, CU_TENSOR_MAP_DATA_TYPE_BFLOAT16, 5, (void*)p, dims, strides, box, es, CU_TENSOR_MAP_INTERLEAVE_NONE, CU_TENSOR_MAP_SWIZZLE_32B,
        CU_TENSOR_MAP_L2_PROMOTION_L2_128B, CU_TENSOR_MAP_FLOAT_OOB_FILL_NONE);
}
void makekv(EncodeFn enc, CUtensorMap* m, const void* p) {
    cuuint64_t dims[3] = {64, (cuuint64_t)NB * NH * SK, 2}, strides[2] = {256, 128};
    cuuint32_t box[3] = {64, 16, 2}, es[3] = {1, 1, 1};
    enc(m, CU_TENSOR_MAP_DATA_TYPE_BFLOAT16, 3, (void*)p, dims, strides, box, es, CU_TENSOR_MAP_INTERLEAVE_NONE, CU_TENSOR_MAP_SWIZZLE_128B,
        CU_TENSOR_MAP_L2_PROMOTION_NONE, CU_TENSOR_MAP_FLOAT_OOB_FILL_NONE);
}

}

extern "C" void kernel_launch(void* const* d_in, const int* in_sizes, int n_in, void* d_out, int out_size) {
    (void)in_sizes; (void)n_in; (void)out_size;
    static EncodeFn enc = nullptr;
    static void* raw = nullptr;
    if (!enc) {
        void* fn = nullptr; cudaDriverEntryPointQueryResult qr;
        cudaGetDriverEntryPoint("cuTensorMapEncodeTiled", &fn, cudaEnableDefault, &qr);
        enc = (EncodeFn)fn;
        cudaFuncSetAttribute(fused_kernel, cudaFuncAttributeMaxDynamicSharedMemorySize, SM_TOTAL);
        cudaGetSymbolAddress(&raw, g_raw);
    }
    Params P;
    makekv(enc, &P.k, d_in[1]);
    makekv(enc, &P.v, d_in[2]);
    make2d(enc, &P.wq, d_in[3], DM, NH * DH, 64, 32, CU_TENSOR_MAP_SWIZZLE_64B);
    make2d(enc, &P.wo, d_in[4], NH * DH, DM, 32, 64, CU_TENSOR_MAP_SWIZZLE_128B);
    make2d(enc, &P.wm, d_in[10], DM, 6 * DM, 256, 8, CU_TENSOR_MAP_SWIZZLE_NONE);
    make2d(enc, &P.wn, d_in[10], DM, 6 * DM, 256, 16, CU_TENSOR_MAP_SWIZZLE_32B);
    make5d(enc, &P.wg, d_in[6], DM, FF, 16, 4);
    make5d(enc, &P.wu, d_in[7], DM, FF, 16, 4);
    make5d(enc, &P.wd, d_in[8], FF, DM, 8, 43);
    P.out = (__nv_bfloat16*)d_out;
    typedef const __nv_bfloat16* W;
    fused_kernel<<<NCTA, NALL, SM_TOTAL>>>((W)d_in[0], (W)d_in[9], (W)d_in[1], (W)d_in[10], (W)d_in[3], (char*)(((size_t)raw + X_ALIGN - 1) & ~(size_t)(X_ALIGN - 1)), P);
}
```

```cpp
#include <cuda_runtime.h>
#include <cuda_bf16.h>
#include <cuda.h>
#include <stdint.h>

namespace {

constexpr int NB = 8, DM = 512, NH = 32, DH = 128, SK = 4096, WIN = 1024, FF = 1376;
constexpr int NCTA = 128, NTHR = 288, NALL = 320;
constexpr int NT = 16;
constexpr int NF1 = 86, DN0 = 96;
constexpr unsigned SENT = 0xFFFFFFFFu;
constexpr int SPIN_MAX = 1 << 20;

constexpr int PWIN0 = 12;
constexpr int PWIN = 16;
constexpr int PSW = 22;
constexpr int NTRK = 4;
constexpr int PFK = 3;
constexpr int QN = 6;
constexpr int TAU = 166;
constexpr int ANCH0 = 176;
constexpr int LEAD = 1600;
constexpr int PACE0 = 7000;
constexpr int PNAP = 200;
constexpr int WOA_ISSUE = 3;
constexpr int WO_GAP = 2;
constexpr int WOA_READ = 8;
constexpr int NPRE = 9;
constexpr int W0 = 850;
constexpr int WS = 180;
constexpr int WD0 = 1700;
constexpr int RT0 = 1700;
constexpr int HD0 = 1000;
constexpr int XDW = 30;
constexpr int HDW = 45;
constexpr int XC = 2;

constexpr int UNIT = 4096, REG = 8 * UNIT;
constexpr int SM_SCR = 6 * REG;
constexpr int SCR = 2048;
constexpr int SM_MN = SM_SCR + 8 * SCR;
constexpr int SM_SC = SM_MN + 8192;
constexpr int SM_BAR = SM_SC + 8192;
constexpr int SM_BM = SM_BAR + 512, SM_BT = SM_BM + 8, SM_BN = SM_BM + 16, SM_BG = SM_BM + 24;
constexpr int SM_AN = SM_BM + 32, SM_SIDE = SM_BM + 36, SM_TAG = SM_BM + 40, SM_MASK = SM_BM + 44;
constexpr int SM_ST = SM_BAR + 576;
constexpr int SM_ML = SM_ST + 512;
constexpr int SM_PR = SM_ML + 96;
constexpr int SM_TOTAL = SM_PR + 512;
constexpr int SC_M = 0, SC_Q = 256;
constexpr int SC_F1 = 0, SC_DN = 0, SC_RX = 1536;
constexpr int B_INIT = 0, B_ALL = 2, B_MOD = 3, B_WQ = 4, B_LAST = 5, B_RDY = 6, B_DN = 7, B_PRE = 8, B_FIN = 9, B_STG = 10, B_SIDE = 11, B_Q = 12, B_ML = 13;

constexpr unsigned HOME = 0xB3000;
constexpr int X_PART = 0;
constexpr int X_Q = 0x100000;
constexpr int X_M1 = 0x140000;
constexpr int X_X1 = 0x150000;
constexpr int X_HM = 0x160000;
constexpr int X_MOD = 0x170000;
constexpr int X_SIDE = 0x176000;
constexpr int X_EPOCH = 0x176400;
constexpr int X_READY = 0x176480;
constexpr int X_LAG = 0x178000;
constexpr int X_ANC = 0x158000;
constexpr int X_PRB = 0x180000;
constexpr int X_ALIGN = 0x200000;
static_assert(XC == 2, "one store writes all copies of x1");
__device__ uint4 g_raw[2 * X_ALIGN / 16];
__device__ __forceinline__ unsigned blk(unsigned base, unsigned k, unsigned s) { const unsigned o = base + k * 8192; return o + ((__popc(o & HOME) ^ s) & 1) * 4096; }

struct Params {
    CUtensorMap wm, wq, k, v, wn, wo, wg, wu, wd;
    __nv_bfloat16* out;
};

__device__ __forceinline__ int tile_key(int i) { return (i & 1) * 128 + (i & 2) * 32 + (i & 12) * 64; }

__device__ __forceinline__ uint32_t smem_u32(const void* p) { return (uint32_t)__cvta_generic_to_shared(p); }
__device__ __forceinline__ void mbar_init(uint32_t a, uint32_t c) { asm volatile("mbarrier.init.shared::cta.b64 [%0], %1;" :: "r"(a), "r"(c) : "memory"); }
__device__ __forceinline__ void mbar_expect(uint32_t a, uint32_t b) { asm volatile("mbarrier.arrive.expect_tx.shared::cta.b64 _, [%0], %1;" :: "r"(a), "r"(b) : "memory"); }
__device__ __forceinline__ void mbar_wait(uint32_t a, uint32_t par) {
    uint32_t ok; int n = 0;
    do {
        asm volatile("{\n.reg .pred p;\nmbarrier.try_wait.parity.shared::cta.b64 p, [%1], %2, 2000;\nselp.u32 %0, 1, 0, p;\n}" : "=r"(ok) : "r"(a), "r"(par) : "memory");
        if (++n > SPIN_MAX) __trap();
    } while (!ok);
}
__device__ __forceinline__ bool mbar_test(uint32_t a, uint32_t par) {
    uint32_t ok; asm volatile("{\n.reg .pred p;\nmbarrier.test_wait.parity.shared::cta.b64 p, [%1], %2;\nselp.u32 %0, 1, 0, p;\n}" : "=r"(ok) : "r"(a), "r"(par) : "memory"); return ok;
}
__device__ __forceinline__ void tma2d(uint32_t dst, const CUtensorMap* m, int x, int y, uint32_t bar) {
    asm volatile("cp.async.bulk.tensor.2d.shared::cluster.global.mbarrier::complete_tx::bytes [%0], [%1, {%3, %4}], [%2];"
                 :: "r"(dst), "l"(m), "r"(bar), "r"(x), "r"(y) : "memory");
}
__device__ __forceinline__ void tma5d(uint32_t dst, const CUtensorMap* m, int x, int y, uint32_t bar) {
    asm volatile("cp.async.bulk.tensor.5d.shared::cluster.global.mbarrier::complete_tx::bytes [%0], [%1, {%3, 0, 0, 0, %4}], [%2];"
                 :: "r"(dst), "l"(m), "r"(bar), "r"(x), "r"(y) : "memory");
}
__device__ __forceinline__ void tma_kv(uint32_t dst, const CUtensorMap* m, int row, uint32_t bar, uint64_t pol) {
    asm volatile("cp.async.bulk.tensor.3d.shared::cluster.global.mbarrier::complete_tx::bytes.L2::cache_hint [%0], [%1, {0, %3, 0}], [%2], %4;"
                 :: "r"(dst), "l"(m), "r"(bar), "r"(row), "l"(pol) : "memory");
}
__device__ __forceinline__ void pf_bulk(const void* p, uint32_t n) { asm volatile("cp.async.bulk.prefetch.L2.global [%0], %1;" :: "l"(p), "r"(n) : "memory"); }
__device__ __forceinline__ void pf_if(const void* p, unsigned i, unsigned n) { asm volatile("{\n.reg .pred p;\nsetp.lt.u32 p, %1, %2;\n@p prefetch.global.L2 [%0];\n}" :: "l"(p), "r"(i), "r"(n) : "memory"); }
__device__ __forceinline__ uint4 ldg_nc(const void* p) { uint4 v; asm volatile("ld.global.nc.v4.u32 {%0,%1,%2,%3}, [%4];" : "=r"(v.x), "=r"(v.y), "=r"(v.z), "=r"(v.w) : "l"(p)); return v; }
__device__ __forceinline__ bool elect() { uint32_t p; asm volatile("{\n.reg .pred p;\nelect.sync _|p, -1;\nselp.u32 %0, 1, 0, p;\n}" : "=r"(p)); return p; }
__device__ __forceinline__ void pf_map(const CUtensorMap* m) { asm volatile("prefetch.tensormap [%0];" :: "l"(m) : "memory"); }
__device__ __forceinline__ void ldsm(uint32_t (&r)[4], uint32_t a) {
    asm volatile("ldmatrix.sync.aligned.m8n8.x4.shared.b16 {%0,%1,%2,%3}, [%4];" : "=r"(r[0]), "=r"(r[1]), "=r"(r[2]), "=r"(r[3]) : "r"(a) : "memory");
}
__device__ __forceinline__ void ldsm_t(uint32_t (&r)[4], uint32_t a) {
    asm volatile("ldmatrix.sync.aligned.m8n8.x4.trans.shared.b16 {%0,%1,%2,%3}, [%4];" : "=r"(r[0]), "=r"(r[1]), "=r"(r[2]), "=r"(r[3]) : "r"(a) : "memory");
}
__device__ __forceinline__ void mma(float (&c)[4], uint32_t a0, uint32_t a1, uint32_t a2, uint32_t a3, uint32_t b0, uint32_t b1) {
    asm("mma.sync.aligned.m16n8k16.row.col.f32.bf16.bf16.f32 {%0,%1,%2,%3}, {%4,%5,%6,%7}, {%8,%9}, {%0,%1,%2,%3};"
        : "+f"(c[0]), "+f"(c[1]), "+f"(c[2]), "+f"(c[3]) : "r"(a0), "r"(a1), "r"(a2), "r"(a3), "r"(b0), "r"(b1));
}
__device__ __forceinline__ void mma(float (&c)[4], const uint32_t (&a)[4], uint32_t b0, uint32_t b1) { mma(c, a[0], a[1], a[2], a[3], b0, b1); }
__device__ __forceinline__ uint32_t pin(uint32_t v) { asm volatile("shfl.sync.bfly.b32 %0, %0, 0, 31, -1;" : "+r"(v)); return v; }
template <class T> __device__ __forceinline__ T* pin(T* p) { const size_t a = (size_t)p; return (T*)(pin((uint32_t)a) | (size_t)pin((uint32_t)(a >> 32)) << 32); }
__device__ __forceinline__ uint32_t movm(uint32_t a) { uint32_t r; asm volatile("movmatrix.sync.aligned.m8n8.trans.b16 %0, %1;" : "=r"(r) : "r"(a)); return r; }
__device__ __forceinline__ uint32_t pack2(float lo, float hi) { uint32_t r; asm("cvt.rn.bf16x2.f32 %0, %1, %2;" : "=r"(r) : "f"(hi), "f"(lo)); return r; }
__device__ __forceinline__ float blo(uint32_t w) { return __uint_as_float(w << 16); }
__device__ __forceinline__ float bhi(uint32_t w) { return __uint_as_float(w & 0xFFFF0000u); }
__device__ __forceinline__ float rbf(float x) { return blo(pack2(x, 0.f)); }
__device__ __forceinline__ uint32_t add2(uint32_t a, uint32_t b) { uint32_t r; asm("add.rn.bf16x2 %0, %1, %2;" : "=r"(r) : "r"(a), "r"(b)); return r; }
__device__ __forceinline__ uint32_t sub2(uint32_t a, uint32_t b) { uint32_t r; asm("sub.rn.bf16x2 %0, %1, %2;" : "=r"(r) : "r"(a), "r"(b)); return r; }
__device__ __forceinline__ uint32_t mul2(uint32_t a, uint32_t b) { uint32_t r; asm("mul.rn.bf16x2 %0, %1, %2;" : "=r"(r) : "r"(a), "r"(b)); return r; }
constexpr uint32_t ONE2 = 0x3F803F80u;
constexpr float LOG2E = 1.4426950408889634f, SCALE = 0.08838834764831845f;
__device__ __forceinline__ float ex2(float x) { float y; asm("ex2.approx.ftz.f32 %0, %1;" : "=f"(y) : "f"(x)); return y; }
__device__ __forceinline__ uint4 ldg_rlx128(const void* p) {
    uint4 v; asm volatile("ld.relaxed.gpu.global.v4.u32 {%0,%1,%2,%3}, [%4];" : "=r"(v.x), "=r"(v.y), "=r"(v.z), "=r"(v.w) : "l"(p) : "memory"); return v;
}
__device__ __forceinline__ uint4 ldg_rlx2x64(const void* p) {
    unsigned long long a, b; asm volatile("ld.relaxed.gpu.global.v2.u64 {%0,%1}, [%2];" : "=l"(a), "=l"(b) : "l"(p) : "memory");
    return make_uint4((unsigned)a, (unsigned)(a >> 32), (unsigned)b, (unsigned)(b >> 32));
}
__device__ __forceinline__ uint2 ldg_rlx64(const void* p) {
    unsigned long long a; asm volatile("ld.relaxed.gpu.global.u64 %0, [%1];" : "=l"(a) : "l"(p) : "memory"); return make_uint2((unsigned)a, (unsigned)(a >> 32));
}
__device__ __forceinline__ unsigned ldg_acq32(const void* p) { unsigned v; asm volatile("ld.acquire.gpu.global.u32 %0, [%1];" : "=r"(v) : "l"(p) : "memory"); return v; }
__device__ __forceinline__ void red_add(void* p, unsigned v) { asm volatile("red.relaxed.gpu.global.add.u32 [%0], %1;" :: "l"(p), "r"(v) : "memory"); }
__device__ __forceinline__ unsigned now_ns() { unsigned t; asm volatile("mov.u32 %0, %%globaltimer_lo;" : "=r"(t)); return t; }
__device__ __forceinline__ void nap(unsigned ns) { asm volatile("nanosleep.u32 %0;" :: "r"(ns)); }
__device__ __forceinline__ unsigned ldg_rlx32(const void* p) { unsigned v; asm volatile("ld.relaxed.gpu.global.u32 %0, [%1];" : "=r"(v) : "l"(p) : "memory"); return v; }
__device__ __forceinline__ void stg_rlx32(void* p, unsigned v) { asm volatile("st.relaxed.gpu.global.u32 [%0], %1;" :: "l"(p), "r"(v) : "memory"); }
__device__ __forceinline__ void stg_rlx16(void* p, unsigned v) { asm volatile("st.relaxed.gpu.global.u16 [%0], %1;" :: "l"(p), "h"((unsigned short)v) : "memory"); }
__device__ __forceinline__ uint4 ldg_b128(const void* p) {
    unsigned long long a, b; asm volatile("{\n.reg .b128 x;\nld.relaxed.gpu.global.b128 x, [%2];\nmov.b128 {%0,%1}, x;\n}" : "=l"(a), "=l"(b) : "l"(p) : "memory");
    return make_uint4((unsigned)a, (unsigned)(a >> 32), (unsigned)b, (unsigned)(b >> 32));
}
__device__ __forceinline__ void stg_b128(void* p, uint4 v) {
    asm volatile("{\n.reg .b128 x;\nmov.b128 x, {%1,%2};\nst.relaxed.gpu.global.b128 [%0], x;\n}" :: "l"(p), "l"(v.x | ((unsigned long long)v.y << 32)), "l"(v.z | ((unsigned long long)v.w << 32)) : "memory");
}
__device__ __forceinline__ int rowoff(int b, int c) { return ((c >> 6) * 2 + ((c >> 2) & 1)) * 512 + b * 64 + (c & 3) * 16 + ((c >> 3) & 1) * 8 + ((c >> 5) & 1) * 4 + ((c >> 4) & 1) * 2; }
__device__ __forceinline__ void stg_rlx64(void* p, unsigned lo, unsigned hi) {
    unsigned long long a = lo | ((unsigned long long)hi << 32); asm volatile("st.relaxed.gpu.global.u64 [%0], %1;" :: "l"(p), "l"(a) : "memory");
}
__device__ __forceinline__ void stg_rlx128(void* p, uint4 v) { asm volatile("st.relaxed.gpu.global.v4.u32 [%0], {%1,%2,%3,%4};" :: "l"(p), "r"(v.x), "r"(v.y), "r"(v.z), "r"(v.w) : "memory"); }
__device__ __forceinline__ void sts32u(uint32_t a, unsigned x) { asm volatile("st.volatile.shared.u32 [%0], %1;" :: "r"(a), "r"(x) : "memory"); }
__device__ __forceinline__ unsigned lds32u(uint32_t a) { unsigned v; asm volatile("ld.volatile.shared.u32 %0, [%1];" : "=r"(v) : "r"(a) : "memory"); return v; }
__device__ __forceinline__ void spin(unsigned c0, unsigned d) { if (d) while ((unsigned)clock() - c0 < d) {} }
__device__ __forceinline__ void fence_gpu() { asm volatile("fence.acq_rel.gpu;" ::: "memory"); }
template <int ID, int N> __device__ __forceinline__ void bar_sync() { asm volatile("bar.sync %0, %1;" :: "n"(ID), "n"(N) : "memory"); }
template <int ID, int N> __device__ __forceinline__ void bar_arrive() { asm volatile("bar.arrive %0, %1;" :: "n"(ID), "n"(N) : "memory"); }
__device__ __forceinline__ void sts64(uint32_t a, float x, float y) { asm volatile("st.shared.v2.f32 [%0], {%1,%2};" :: "r"(a), "f"(x), "f"(y) : "memory"); }
__device__ __forceinline__ void sts128(uint32_t a, uint4 v) { asm volatile("st.volatile.shared.v4.u32 [%0], {%1,%2,%3,%4};" :: "r"(a), "r"(v.x), "r"(v.y), "r"(v.z), "r"(v.w) : "memory"); }
__device__ __forceinline__ void sts128f(uint32_t a, float x, float y, float z, float w) { asm volatile("st.volatile.shared.v4.f32 [%0], {%1,%2,%3,%4};" :: "r"(a), "f"(x), "f"(y), "f"(z), "f"(w) : "memory"); }
__device__ __forceinline__ void sts32(uint32_t a, float x) { asm volatile("st.shared.f32 [%0], %1;" :: "r"(a), "f"(x) : "memory"); }
__device__ __forceinline__ float2 lds64(uint32_t a) { float2 v; asm volatile("ld.shared.v2.f32 {%0,%1}, [%2];" : "=f"(v.x), "=f"(v.y) : "r"(a) : "memory"); return v; }
__device__ __forceinline__ float lds32(uint32_t a) { float v; asm volatile("ld.shared.f32 %0, [%1];" : "=f"(v) : "r"(a) : "memory"); return v; }
__device__ __forceinline__ float4 lds128(uint32_t a) { float4 v; asm volatile("ld.shared.v4.f32 {%0,%1,%2,%3}, [%4];" : "=f"(v.x), "=f"(v.y), "=f"(v.z), "=f"(v.w) : "r"(a) : "memory"); return v; }
__device__ __forceinline__ float2 sum8(uint32_t a) {
    float2 v[8];
#pragma unroll
    for (int i = 0; i < 8; i++) v[i] = lds64(a + i * SCR);
    return make_float2(((v[0].x + v[1].x) + (v[2].x + v[3].x)) + ((v[4].x + v[5].x) + (v[6].x + v[7].x)),
                       ((v[0].y + v[1].y) + (v[2].y + v[3].y)) + ((v[4].y + v[5].y) + (v[6].y + v[7].y)));
}
template <int STRIDE> __device__ __forceinline__ float4 sum8x4(uint32_t a) {
    float4 v[8];
#pragma unroll
    for (int i = 0; i < 8; i++) v[i] = lds128(a + i * STRIDE);
    return make_float4(((v[0].x + v[1].x) + (v[2].x + v[3].x)) + ((v[4].x + v[5].x) + (v[6].x + v[7].x)), ((v[0].y + v[1].y) + (v[2].y + v[3].y)) + ((v[4].y + v[5].y) + (v[6].y + v[7].y)),
                       ((v[0].z + v[1].z) + (v[2].z + v[3].z)) + ((v[4].z + v[5].z) + (v[6].z + v[7].z)), ((v[0].w + v[1].w) + (v[2].w + v[3].w)) + ((v[4].w + v[5].w) + (v[6].w + v[7].w)));
}
__device__ __forceinline__ float rcp(float x) { float y; asm("rcp.approx.ftz.f32 %0, %1;" : "=f"(y) : "f"(x)); return y; }
__device__ __forceinline__ float sigmoid_f(float x) { return rcp(1.0f + ex2(x * -LOG2E)); }
__device__ __forceinline__ uint32_t silu2(uint32_t c) { const float a = blo(c), b = bhi(c); return pack2(a * sigmoid_f(a), b * sigmoid_f(b)); }
__device__ __forceinline__ void ln_consts(float mean, float var, uint32_t& mu2, float& rs) {
    mu2 = pack2(mean, mean);
    float sd; asm("sqrt.approx.ftz.f32 %0, %1;" : "=f"(sd) : "f"(rbf(rbf(var) + 1e-5f)));
    rs = rcp(rbf(sd));
}
__device__ __forceinline__ uint32_t ln_norm(uint32_t x2, uint32_t mu2, float rs) { const uint32_t d = sub2(x2, mu2); return pack2(blo(d) * rs, bhi(d) * rs); }

__global__ void __launch_bounds__(NALL, 1) fused_kernel(const __nv_bfloat16* const px, const __nv_bfloat16* const pc, const __nv_bfloat16* const pk, const __nv_bfloat16* const pwm,
                                                        const __nv_bfloat16* const pwq, char* const X, const __grid_constant__ Params P) {
    extern __shared__ __align__(1024) unsigned char smem[];
    const uint32_t sb = smem_u32(smem);
    const int tid = threadIdx.x, w = tid >> 5, lane = tid & 31, g = lane >> 2, t = lane & 3;
    const int cta = blockIdx.x, head = cta >> 2, bat = (cta & 3) * 2 + (w >> 2);
    const uint32_t s0 = sb + w * UNIT, s2 = s0 + 4 * REG;
    const uint32_t bar0 = sb + SM_BAR + w * 64;
    const uint32_t barC = bar0 + 32;
    const uint32_t scr = sb + SM_SCR, myscr = scr + w * SCR;
    pf_if((const char*)pwm + ((cta * 4 + (tid >> 4)) * (6 * DM * 2) + (tid & 15) * 128), w, 2);
    pf_if((const char*)pk + (unsigned)(((((cta & 3) * 2 + (w & 1)) * NH + head) * SK + (SK - WIN - 16) + (w >> 1) * 16) * (DH * 2) + lane * 128), w - 2, PFK);
    const int rid = !(cta & 1) ? cta >> 1 : (cta >> 2) + (cta & 2 ? 64 : 96);
    const unsigned t_start = now_ns();
    uint64_t pol;
    asm volatile("createpolicy.fractional.L2::evict_first.b64 %0, 1.0;" : "=l"(pol));
    auto go_first = [&](uint32_t wbar, uint32_t par) {
        for (int n = 0;; n++) {
            if (__all_sync(~0u, mbar_test(wbar, par))) return false;
            if (__all_sync(~0u, mbar_test(sb + SM_BG, 0))) return true;
            if (n > SPIN_MAX * 4) __trap();
            nap(20);
        }
    };
    if (w == 9) {
        const uint32_t sl = sb + SM_PR + lane * 16;
        char* const pl = X + blk(X_PRB, cta >> 1, lane & 1) + (lane >> 1) * 256 + (cta & 1) * 128;
        {
            char* const ps = X + X_PRB + (cta >> 1) * 8192 + g * 256 + (cta & 1) * 128 + t * 16;
            sts32u(sl, 0);
#pragma unroll
            for (int i = 0; i < 4; i++) stg_rlx128(ps + i * 2048, make_uint4(1, 1, 1, 1));
            __syncwarp();
        }
        unsigned v; asm volatile("atom.relaxed.gpu.global.add.u32 %0, [%1], 1;" : "=r"(v) : "l"(pl) : "memory");
        unsigned tag = ldg_rlx32(X + X_EPOCH);
        if (lane == 0) pf_bulk(pwq + (size_t)cta * QN * 1024, QN * 2048);
        if (lane == 0) sts32u(sb + SM_AN, t_start + ANCH0);
        if (lane < 8) sts32u(sb + SM_BAR + lane * 64 + 56, 0);
        unsigned side;
        {
            int d, n = 0;
#pragma unroll 1
            for (int r = 0; r < 4; r++) {
                if (v == SENT) __trap();
                asm volatile("cp.async.cg.shared.global [%0], [%1], 16;" :: "r"(sl), "l"(pl) : "memory");
                unsigned m;
                do {
                    m = __ballot_sync(~0u, lds32u(sl));
                    d = __popc(m & 0xAAAAAAAAu) - __popc(m & 0x55555555u);
                    if (++n > SPIN_MAX) __trap();
                } while (abs(d) < 6 && m != ~0u);
                if (abs(d) >= 6) break;
                asm volatile("cp.async.wait_all;" ::: "memory");
                sts32u(sl, 0);
                asm volatile("atom.relaxed.gpu.global.add.u32 %0, [%1], 1;" : "=r"(v) : "l"(pl) : "memory");
            }
            side = d > 0;
            tag++;
            if (lane == 0) { sts32u(sb + SM_SIDE, side); sts32u(sb + SM_TAG, tag); }
            bar_arrive<B_SIDE, NTHR>();
        }
        asm volatile("cp.async.wait_all;" ::: "memory");
        while (now_ns() - t_start < PACE0) nap(200);
        for (int n = 0; n < SPIN_MAX; n++) {
            const uint32_t wb = sb + SM_BAR + (lane & 7) * 64;
            const unsigned seen = lds32u(wb + 56), u = seen + ((lane >> 3) & 1), t1 = now_ns();
            const unsigned more = mbar_test(wb + (u < 6 ? u : (~u & 2) + (u & 1)) * 8, u < 6 ? 0 : ((u - 2) >> 2) & 1);
            const unsigned lo = __reduce_min_sync(~0u, seen), sum = __reduce_add_sync(~0u, lane < 8 ? seen + more : lane < 16 ? more : 0);
            if (lo == 30) break;
            if (lo && lane < 2) stg_rlx64(X + X_LAG + (cta >> 5) * 8192 + lane * 4096 + (cta & 31) * 128, t1 - sum * TAU, tag);
            uint2 a = make_uint2(0, 0);
            if (cta == 0) {
                uint2 u[4];
#pragma unroll
                for (int i = 0; i < 4; i++) u[i] = ldg_rlx64(X + blk(X_LAG, i, side) + lane * 128);
                const int s = __reduce_add_sync(~0u, (int)(u[0].x + u[1].x + u[2].x + u[3].x - 4 * t_start));
                if (__all_sync(~0u, (u[0].y == tag) & (u[1].y == tag) & (u[2].y == tag) & (u[3].y == tag)) && lane < 2) {
                    a = make_uint2(t_start + s / NCTA, tag);
                    stg_rlx64(X + X_ANC + lane * 4096, a.x, tag);
                }
            } else if (lane == 0) a = ldg_rlx64(X + blk(X_ANC, 0, side));
            if (lane == 0 && a.y == tag) sts32u(sb + SM_AN, a.x - LEAD);
            __syncwarp();
            nap(PNAP);
        }
        {
            bar_sync<B_ML, NTHR>();
            const float2 ml = lds64(sb + SM_ML + (lane & 7) * 8);
            float M = fmaxf(ml.x, __shfl_xor_sync(~0u, ml.x, 1)); M = fmaxf(M, __shfl_xor_sync(~0u, M, 2));
            const float e = ex2((ml.x - M) * LOG2E);
            float L = e * ml.y; L += __shfl_xor_sync(~0u, L, 1); L += __shfl_xor_sync(~0u, L, 2);
            if (lane < 8) sts32(sb + SM_ML + 64 + lane * 4, e * rcp(L));
        }
        bar_arrive<B_RDY, NALL>();
        bar_sync<B_STG, 64>();
        {
            const char* const pp = pin(X + blk(X_PART, cta, side) + lane * 16);
            char* const xo = pin(X + (lane >> 4) * 16384 + blk(X_X1, (cta >> 3) & 1, lane >> 3) + (cta & 7) * 512 + (cta >> 4) * 64 + (lane & 7) * 8);
            const float4 gx = lds128(scr + SC_RX + (lane & 7) * 16);
            const unsigned t0 = lds32u(sb + SM_AN) + 256 * TAU + RT0 + (cta & 7) * (TAU / 8);
            while ((int)(now_ns() - t0) < 0) nap(20);
            uint4 v[8]; int n = 0;
            float a[4];
#pragma unroll
            for (int j = 0; j < 8; j++) v[j] = ldg_b128(pp + j * 512);
            while (true) {
#define RSUM(f) (((__uint_as_float(v[0].f) + __uint_as_float(v[1].f)) + (__uint_as_float(v[2].f) + __uint_as_float(v[3].f))) + ((__uint_as_float(v[4].f) + __uint_as_float(v[5].f)) + (__uint_as_float(v[6].f) + __uint_as_float(v[7].f))))
                const bool ok = __all_sync(~0u, max(max(max(v[0].x, v[1].x), max(v[2].x, v[3].x)), max(max(v[4].x, v[5].x), max(v[6].x, v[7].x))) != SENT);
                a[0] = RSUM(x); a[1] = RSUM(y); a[2] = RSUM(z); a[3] = RSUM(w);
                asm volatile("" : "+f"(a[0]), "+f"(a[1]), "+f"(a[2]), "+f"(a[3]));
                if (ok) break;
#pragma unroll
                for (int j = 0; j < 8; j++) if (v[j].x == SENT) v[j] = ldg_b128(pp + j * 512);
                if (++n > SPIN_MAX) __trap();
            }
#pragma unroll
            for (int i = 0; i < 4; i++) a[i] += __shfl_xor_sync(~0u, a[i], 8);
#pragma unroll
            for (int i = 0; i < 4; i++) a[i] += __shfl_xor_sync(~0u, a[i], 16);
            stg_rlx64(xo, add2(__float_as_uint(gx.z), mul2(__float_as_uint(gx.x), pack2(a[0], a[1]))), add2(__float_as_uint(gx.w), mul2(__float_as_uint(gx.y), pack2(a[2], a[3]))));
        }
        if (rid >= DN0) {
            const unsigned c1 = clock();
            const int f = rid - DN0;
            const char* const rp = X + (rid & (XC - 1)) * 16384 + blk(X_X1, f >> 4, side) + (rowoff(g, f * 16 + t * 4) & 4092);
            unsigned r[4]; int n = 0;
            spin(c1, HD0 - 450);
            do {
#pragma unroll
                for (int i = 0; i < 4; i++) r[i] = ldg_rlx32(rp + i * 16);
                if (++n > SPIN_MAX) __trap();
            } while (max(max(r[0], r[1]), max(r[2], r[3])) == SENT);
            const unsigned sel = (f & 1) ? 0x7632 : 0x5410;
            sts64(sb + SM_MN + 256 + lane * 8, __uint_as_float(__byte_perm(r[0], r[1], sel)), __uint_as_float(__byte_perm(r[2], r[3], sel)));
            __syncwarp();
            spin(c1, HD0);
        }
        if (lane == 0) asm volatile("mbarrier.arrive.shared::cta.b64 _, [%0];" :: "r"(sb + SM_BG) : "memory");
    } else if (w == 8) {
        const int row0 = ((cta & 3) * 2 * NH + head) * SK + (SK - WIN);
        auto kv_unit = [&](int u) {
            const uint32_t b = sb + SM_BAR + (u & 7) * 64 + (u >> 3) * 8;
            mbar_expect(b, UNIT);
            tma_kv(sb + (u >> 3) * REG + (u & 7) * UNIT, (u & 8) ? &P.v : &P.k, row0 + ((u >> 2) & 1) * NH * SK + (u & 3) * 16 + tile_key(u >> 4), b, pol);
        };
        if (elect()) {
            mbar_init(sb + SM_BM, 1);
#pragma unroll
            for (int i = 0; i < 8; i++) mbar_init(sb + SM_BAR + i * 64 + 48, 1);
            asm volatile("fence.mbarrier_init.release.cluster;" ::: "memory");
            mbar_expect(sb + SM_BM, 512 * 16);
            tma2d(sb + 4 * REG, &P.wm, cta * 8, 0, sb + SM_BM); tma2d(sb + 4 * REG + 256 * 16, &P.wm, cta * 8, 256, sb + SM_BM);
#pragma unroll
            for (int i = 0; i < 8; i++) { const uint32_t b = sb + SM_BAR + i * 64 + 48; mbar_expect(b, UNIT); tma2d(sb + 5 * REG + i * UNIT, &P.wq, cta * 32, i * 64, b); }
            mbar_init(sb + SM_BN, 1); mbar_init(sb + SM_BT, 1); mbar_init(sb + SM_BG, 1);
#pragma unroll
            for (int i = 0; i < 48; i++) mbar_init(sb + SM_BAR + (i & 7) * 64 + (i >> 3) * 8, 1);
            asm volatile("fence.mbarrier_init.release.cluster;" ::: "memory");
        }
        __syncwarp();
        bar_arrive<B_INIT, NTHR>();
        {
            uint32_t mine = lane >= NTRK ? 0 : lane < 8 ? sb + SM_BAR + lane * 64 + 48 : sb + SM_BM;
            int next = 0, lim = 32, n = 0;
            while (next < 48) {
                const bool idle = lane < (next < PSW ? PWIN0 : PWIN) && (mine == 0 || mbar_test(mine, 0));
                const unsigned m = __ballot_sync(~0u, idle);
                const int u = next + __popc(m & ((1u << lane) - 1));
                if (idle) {
                    mine = 0;
                    if (u < lim) { kv_unit(u); mine = sb + SM_BAR + (u & 7) * 64 + (u >> 3) * 8; }
                }
                next = min(next + __popc(m), lim);
                if (next == lim) {
                    if (lim == 32) { bar_sync<B_MOD, NTHR>(); } else if (lim == 40) { bar_sync<B_WQ, NTHR>(); }
                    lim += 8;
                }
                if (!m) nap(30);
                if (++n > SPIN_MAX) __trap();
            }
        }
        if (lane < 5) pf_map(&P.wn + lane);
        float m[4][4] = {};
        auto late_mod = [&](uint32_t a, int h) {
            const int lrow = (lane & 7) + ((lane >> 4) << 3), lch = (lane >> 3) & 1;
            const uint32_t a0 = a + lrow * 32 + ((lch ^ ((lrow >> 2) & 1)) << 4);
            const uint32_t c0 = sb + SM_SC + h * 4096 + (lane & 7) * 128 + (((lane >> 3) ^ (lane & 7)) << 4);
#pragma unroll
            for (int j = 0; j < 8; j++) {
                uint32_t c[4], r[4], u[4];
                ldsm(c, (c0 + (j >> 1) * 1024) ^ ((j & 1) << 6)); ldsm_t(r, a0 + j * 1024); ldsm_t(u, a0 + j * 1024 + 512);
                mma(m[(j & 1) * 2], r, c[0], c[1]); mma(m[(j & 1) * 2 + 1], u, c[2], c[3]);
            }
        };
        if (rid < 96) {
#pragma unroll 1
            for (int h = 0; h < 2; h++) {
                if (lane == 0) { mbar_expect(sb + SM_BN, 8192); tma2d(sb + SM_MN, &P.wn, 2 * DM + rid * 16, h * 256, sb + SM_BN); }
                mbar_wait(sb + SM_BN, h);
                late_mod(sb + SM_MN, h);
                asm volatile("" :: "f"(m[0][0]), "f"(m[1][0]), "f"(m[2][0]), "f"(m[3][0]) : "memory");
                __syncwarp();
            }
#pragma unroll
            for (int e = 0; e < 4; e++) {
                float v = rbf((m[0][e] + m[1][e]) + (m[2][e] + m[3][e]));
                if (rid >= 64) v += 1.0f;
                stg_rlx16(X + X_MOD + (rid >> 5) * 8192 + rowoff(2 * t + (e & 1), (rid & 31) * 16 + g + (e >> 1) * 8), pack2(v, 0.f));
            }
        }
        {
            const unsigned side = lds32u(sb + SM_SIDE);
#pragma unroll
            for (int i = 0; i < 8; i++) stg_rlx128(X + blk(X_PART, cta, side) + i * 512 + lane * 16, make_uint4(SENT, SENT, SENT, SENT));
            if (lane == 0) stg_rlx32(X + X_SIDE + cta * 4, side);
        }
        bar_sync<B_Q, NTHR>();
        if (lane == 0) {
            const unsigned tag = lds32u(sb + SM_TAG);
            fence_gpu();
            red_add(X + X_READY, 1);
            int n = 0;
            while ((int)(ldg_acq32(X + X_READY) - tag * NCTA) < 0) { nap(1000); if (++n > SPIN_MAX) __trap(); }
            if (cta == 0) stg_rlx32(X + X_EPOCH, tag);
        }
        __syncwarp();
        {
            stg_rlx128(X + blk(X_Q, head >> 1, 0) + (head & 1) * 2048 + g * 256 + (cta & 3) * 64 + t * 16, make_uint4(0, 0, 0, 0));
            stg_rlx128(X + blk(X_Q, head >> 1, 1) + (head & 1) * 2048 + g * 256 + (cta & 3) * 64 + t * 16, make_uint4(0, 0, 0, 0));
            stg_rlx64(X + blk(X_M1, cta >> 5, lane >> 4) + (cta & 31) * 128 + (lane & 15) * 8, 0, 0);
            const int wt = (cta & 3) * 32 + lane;
            const unsigned mask = __ballot_sync(~0u, blk(X_PART, wt, ldg_rlx32(X + X_SIDE + wt * 4)) & 4096);
            if (lane == 0) sts32u(sb + SM_MASK, mask);
            if (lane < 8) {
                const int task = cta;
                const int rb = task >> 4, c = ((task & 15) >> 1) * 64 + (task & 1) * 4 + ((lane & 7) >> 1) + (lane & 1) * 8;
                const uint2 ga = ldg_rlx64(X + X_MOD + rowoff(rb, c));
                const unsigned short* const xp = (const unsigned short*)px + rb * DM + c;
                sts128(scr + (lane >> 3) * SCR + SC_RX + (lane & 7) * 16, make_uint4(ga.x, ga.y, xp[0] | (xp[16] << 16), xp[32] | (xp[48] << 16)));
            }
            if (rid < NF1) {
#pragma unroll 1
                for (int i = 0; i < 4; i++) {
                    uint4 v[8];
#pragma unroll
                    for (int j = 0; j < 8; j++) v[j] = ldg_rlx128(X + X_MOD + 8192 + (i * 8 + j) * 512 + lane * 16);
#pragma unroll
                    for (int j = 0; j < 8; j++) sts128(sb + SM_MN + (i * 8 + j) * 512 + lane * 16, v[j]);
                }
            }
        }
        bar_arrive<B_RDY, NALL>();
        bar_arrive<B_STG, 64>();
        unsigned t_ref = 0;
        auto until = [&](int x) { while ((int)(now_ns() - t_ref) < x) nap(20); };
        if (elect()) {
#pragma unroll 1
            for (int i = 0; i < 8; i++) { int n = 0; while (lds32u(sb + SM_BAR + i * 64 + 56) < 30) { nap(100); if (++n > SPIN_MAX) __trap(); } }
            t_ref = lds32u(sb + SM_AN) + 256 * TAU + (cta & 7) * (TAU / 8);
            if (rid < NF1) {
#pragma unroll
                for (int i = 0; i < 4; i++) mbar_expect(sb + SM_BAR + i * 64 + 48, 2 * UNIT);
#pragma unroll 1
                for (int i = 0; i < 4; i++) {
                    const uint32_t b = sb + SM_BAR + i * 64 + 48;
                    until(W0 + i * WS);
                    tma5d(sb + 2 * REG + i * UNIT, &P.wg, rid * 16, i * 4, b); tma5d(sb + 2 * REG + 16384 + i * UNIT, &P.wu, rid * 16, i * 4, b);
                }
            }
        }
        if (rid >= DN0) {
            bar_sync<B_LAST, NTHR>();
            if (elect()) {
                mbar_expect(sb + SM_BN, 16384); mbar_expect(sb + SM_BT, FF * 32);
                until(WD0);
                tma5d(sb + 2 * REG + 16384, &P.wd, (rid - DN0) * 16, 0, sb + SM_BT);
                tma2d(sb + 2 * REG, &P.wn, 2 * DM + rid * 16, 0, sb + SM_BN); tma2d(sb + 2 * REG + 8192, &P.wn, 2 * DM + rid * 16, 256, sb + SM_BN);
            }
        }
        __syncwarp();
        if (rid >= DN0) {
            mbar_wait(sb + SM_BN, 0);
            late_mod(sb + 2 * REG, 0); late_mod(sb + 2 * REG + 8192, 1);
#pragma unroll
            for (int e = 0; e < 2; e++)
                sts32u(sb + SM_MN + g * 32 + e * 16 + t * 4, movm(pack2((m[0][2 * e] + m[1][2 * e]) + (m[2][2 * e] + m[3][2 * e]), (m[0][2 * e + 1] + m[1][2 * e + 1]) + (m[2][2 * e + 1] + m[3][2 * e + 1]))));
            bar_arrive<B_DN, NTHR>();
        }
    }
    if (w >= 8) {
        if (rid < NF1) {
            const int b = (tid - 256) >> 3, c = tid & 7;
            char* const ho = pin(X + X_HM + (rid >> 4) * 8192 + ((rid >> 1) & 7) * 512 + b * 64 + (rid & 1) * 32 + c * 4);
            const uint32_t pi = pin(scr + SC_F1 + c * 144 + b * 16), si = pin(sb + SM_ST + b * 64);
            bar_sync<B_PRE, NALL>();
            float4 C = sum8x4<UNIT>(sb + REG + c * 144 + b * 16), S = sum8x4<UNIT>(sb + REG + 1152 + c * 144 + b * 16);
            S.x *= -LOG2E; S.y *= -LOG2E; C.x *= LOG2E; C.y *= LOG2E;
            sts128f(sb + SM_PR + lane * 16, C.x, C.y, C.z, C.w); sts128f(sb + SM_PR + lane * 16, S.x, S.y, S.z, S.w);
            sts128(sb + SM_PR + lane * 16, make_uint4(pi, si, (uint32_t)(size_t)ho, (uint32_t)((size_t)ho >> 32)));
            bar_sync<B_FIN, NALL>();
            const float4 s0_ = lds128(si), s1_ = lds128(si + 16), s2_ = lds128(si + 32), s3_ = lds128(si + 48);
            const float4 p = sum8x4<SCR>(pi);
            const float mean = (((s0_.x + s0_.z) + (s1_.x + s1_.z)) + ((s2_.x + s2_.z) + (s3_.x + s3_.z))) * (1.0f / DM);
            const float sq = (((s0_.y + s0_.w) + (s1_.y + s1_.w)) + ((s2_.y + s2_.w) + (s3_.y + s3_.w))) * (1.0f / DM);
            float rs; asm("rsqrt.approx.ftz.f32 %0, %1;" : "=f"(rs) : "f"(fmaxf(sq - mean * mean, 0.f) + 1e-5f));
            const float e0 = rs * (mean * C.x - LOG2E * p.x) + S.x, e1 = rs * (mean * C.y - LOG2E * p.y) + S.y;
            const float u0 = rs * (p.z - mean * C.z) + S.z, u1 = rs * (p.w - mean * C.w) + S.w;
            const unsigned hw = pack2(rcp(1.0f + ex2(e0)) * u0, rcp(1.0f + ex2(e1)) * u1);
            stg_rlx32(ho, hw); stg_rlx32(ho + 4096, hw);
        }
        return;
    }
    const unsigned ce = (lane >> 3) * (DM * 2) + w * 128 + (lane & 7) * 16;
    const uint4 ca = ldg_nc((const char*)pc + ce), cb = ldg_nc((const char*)pc + ce + 4 * DM * 2);
    const uint4 xa = ldg_nc((const char*)px + w * (DM * 2) + lane * 16), xb = ldg_nc((const char*)px + w * (DM * 2) + lane * 16 + 512);
    const uint4 xc = ldg_nc((const char*)px + ce), xd = ldg_nc((const char*)px + ce + 4 * DM * 2);
    if (w >= 4) pf_map(&P.wm + (w & 3));
    char* const qout = X + blk(X_Q, head >> 1, tid >> 7) + (head & 1) * 2048 + ((tid >> 4) & 7) * 256 + (cta & 3) * 64 + (tid & 3) * 16 + ((tid >> 2) & 3) * 4;
    char* const mout = X + blk(X_M1, cta >> 5, w) + (cta & 31) * 128 + lane * 4;
    stg_rlx32(qout, 0);
    if (w < 2) stg_rlx32(mout, 0);
    uint32_t sc[8], xf[8];
    {
        const uint32_t a = (lane >> 3) * 128 + (((lane & 7) ^ (lane >> 3)) << 4), b = (lane & 7) * 128 + (((lane >> 3) ^ (lane & 7)) << 4);
        const uint32_t cs = sb + SM_SC + w * 1024;
        sts128(cs + a, make_uint4(silu2(ca.x), silu2(ca.y), silu2(ca.z), silu2(ca.w)));
        sts128(cs + 512 + (a ^ 64), make_uint4(silu2(cb.x), silu2(cb.y), silu2(cb.z), silu2(cb.w)));
        sts128(myscr + a, xc); sts128(myscr + 512 + (a ^ 64), xd);
        __syncwarp();
        ldsm(*(uint32_t(*)[4])&sc[0], cs + b); ldsm(*(uint32_t(*)[4])&sc[4], cs + (b ^ 64));
        ldsm(*(uint32_t(*)[4])&xf[0], myscr + b); ldsm(*(uint32_t(*)[4])&xf[4], myscr + (b ^ 64));
        __syncwarp();
    }
    {
        float v[16] = {blo(xa.x), bhi(xa.x), blo(xa.y), bhi(xa.y), blo(xa.z), bhi(xa.z), blo(xa.w), bhi(xa.w),
                       blo(xb.x), bhi(xb.x), blo(xb.y), bhi(xb.y), blo(xb.z), bhi(xb.z), blo(xb.w), bhi(xb.w)};
        float s = 0;
#pragma unroll
        for (int i = 0; i < 16; i++) s += v[i];
#pragma unroll
        for (int o = 16; o; o >>= 1) s += __shfl_xor_sync(~0u, s, o);
        s *= (1.0f / DM);
        float q2 = 0;
#pragma unroll
        for (int i = 0; i < 16; i++) q2 += (v[i] - s) * (v[i] - s);
#pragma unroll
        for (int o = 16; o; o >>= 1) q2 += __shfl_xor_sync(~0u, q2, o);
        uint32_t mu2; float rs; ln_consts(s, q2 * (1.0f / DM), mu2, rs);
        if (lane == 0) sts64(sb + SM_ST + w * 8, __uint_as_float(mu2), rs);
    }
    const int lrow = (lane & 7) + ((lane >> 4) << 3), lch = (lane >> 3) & 1;
    const uint32_t off64 = lrow * 64 + ((lch ^ ((lrow >> 1) & 3)) << 4);
    const uint32_t off128 = lrow * 128 + ((lch ^ (lane & 7)) << 4);
    bar_sync<B_INIT, NTHR>();
    mbar_wait(sb + SM_BM, 0);
    {
        float a[4] = {0, 0, 0, 0}, b[4] = {0, 0, 0, 0};
        uint32_t r[4], u[4];
        ldsm_t(r, sb + 4 * REG + (w * 64 + lane) * 16); ldsm_t(u, sb + 4 * REG + (w * 64 + 32 + lane) * 16);
        mma(a, sc[0], 0, sc[1], 0, r[0], r[1]); mma(b, sc[4], 0, sc[5], 0, u[0], u[1]);
        mma(a, sc[2], 0, sc[3], 0, r[2], r[3]); mma(b, sc[6], 0, sc[7], 0, u[2], u[3]);
        sts64(myscr + SC_M + lane * 8, a[0] + b[0], a[1] + b[1]);
    }
    bar_arrive<B_MOD, NTHR>();
    bar_sync<B_ALL, 256>();
    if (w < 2) {
        const float2 m = sum8(scr + SC_M + lane * 8);
        stg_rlx32(mout, ~pack2(m.x, m.y));
    }
    if (tid < 8 * XC) stg_rlx128(X + X_X1 + (cta * 8 * XC + tid) * 16, make_uint4(SENT, SENT, SENT, SENT));
    else if (tid >= 232) stg_rlx128(X + X_HM + (cta * 24 + tid - 232) * 16, make_uint4(SENT, SENT, SENT, SENT));
    {
        const float2 st = lds64(sb + SM_ST + g * 8);
#pragma unroll
        for (int i = 0; i < 8; i++) xf[i] = ln_norm(xf[i], __float_as_uint(st.x), st.y);
    }
    {
        unsigned sv[8], cv[8]; int n = 0;
        bar_sync<B_SIDE, NTHR>();
        const char* const mp = X + blk(X_M1, w >> 2, lds32u(sb + SM_SIDE)) + (w & 3) * 1024 + lane * 4;
        if (lane == 0) while (!ldg_rlx32(mp + 16384 + 7 * 128)) { nap(40); if (++n > SPIN_MAX) __trap(); }
        __syncwarp();
#pragma unroll
        for (int j = 0; j < 8; j++) { sv[j] = ldg_rlx32(mp + j * 128); cv[j] = ldg_rlx32(mp + 16384 + j * 128); }
        while (true) {
            unsigned m = ~0u;
#pragma unroll
            for (int j = 0; j < 8; j++) m = min(m, min(sv[j], cv[j]));
            if (__all_sync(~0u, m)) break;
#pragma unroll
            for (int j = 0; j < 8; j++) { if (!sv[j]) sv[j] = ldg_rlx32(mp + j * 128); if (!cv[j]) cv[j] = ldg_rlx32(mp + 16384 + j * 128); }
            if (++n > SPIN_MAX) __trap();
        }
#pragma unroll
        for (int j = 0; j < 8; j++) xf[j] = add2(mul2(xf[j], add2(~cv[j], ONE2)), ~sv[j]);
        mbar_wait(bar0 + 48, 0);
        float acc[4][4] = {};
#pragma unroll
        for (int j = 0; j < 4; j++) {
            uint32_t r[4], u[4];
            ldsm_t(r, s2 + REG + j * 1024 + off64); ldsm_t(u, s2 + REG + j * 1024 + (off64 ^ 32));
            mma(acc[0], xf[2 * j], 0, xf[2 * j + 1], 0, r[0], r[2]); mma(acc[1], xf[2 * j], 0, xf[2 * j + 1], 0, r[1], r[3]);
            mma(acc[2], xf[2 * j], 0, xf[2 * j + 1], 0, u[0], u[2]); mma(acc[3], xf[2 * j], 0, xf[2 * j + 1], 0, u[1], u[3]);
        }
#pragma unroll
        for (int n2 = 0; n2 < 4; n2++) sts64(myscr + SC_Q + g * 160 + n2 * 32 + t * 8, acc[n2][0], acc[n2][1]);
    }
    bar_arrive<B_WQ, NTHR>();
    bar_sync<B_ALL, 256>();
    {
        const float2 s = sum8(scr + SC_Q + ((tid >> 4) & 7) * 160 + (tid & 15) * 8);
        stg_rlx32(qout, ~pack2(s.x, s.y));
    }
    uint32_t q[16];
    {
        int n = 0;
        const char* const qp = X + blk(X_Q, head >> 1, lds32u(sb + SM_SIDE)) + (head & 1) * 2048 + bat * 256 + t * 16;
        uint4 v[4];
#pragma unroll
        for (int j = 0; j < 4; j++) v[j] = ldg_rlx128(qp + j * 64);
        while (true) {
            bool bad[4];
#pragma unroll
            for (int j = 0; j < 4; j++) bad[j] = !min(min(v[j].x, v[j].y), min(v[j].z, v[j].w));
            if (!__any_sync(~0u, bad[0] | bad[1] | bad[2] | bad[3])) break;
#pragma unroll
            for (int j = 0; j < 4; j++) if (bad[j]) v[j] = ldg_rlx128(qp + j * 64);
            if (++n > SPIN_MAX) __trap();
        }
#pragma unroll
        for (int j = 0; j < 4; j++) { q[4 * j] = ~v[j].x; q[4 * j + 1] = ~v[j].y; q[4 * j + 2] = ~v[j].z; q[4 * j + 3] = ~v[j].w; }
    }
    bar_arrive<B_Q, NTHR>();

    float o[2][4] = {};
    float mrun = -3.0e38f, lrun = 0.f;
    uint32_t wa[16][4], pb[2];
#pragma unroll
    for (int i = 0; i < 16; i++) wa[i][0] = wa[i][1] = wa[i][2] = wa[i][3] = 0;
    const uint32_t offk = (lane & 15) * 128 + (((lane >> 4) ^ (lane & 7)) << 4);
    float p0, p1;
    auto scores = [&](uint32_t a0) {
        uint32_t kf[8][4];
#pragma unroll
        for (int j = 0; j < 8; j++) ldsm(kf[j], ((a0 + offk) ^ ((j & 3) << 5)) + (j >> 2) * 2048);
        float sa[4] = {0, 0, 0, 0}, sb2[4] = {0, 0, 0, 0};
#pragma unroll
        for (int j = 0; j < 8; j += 2) { mma(sa, kf[j], q[2 * j], q[2 * j + 1]); mma(sb2, kf[j + 1], q[2 * j + 2], q[2 * j + 3]); }
        uint32_t u = pack2(sa[0] + sb2[0], sa[2] + sb2[2]);
        u = pack2(blo(u) * SCALE, bhi(u) * SCALE);
        const float z0 = blo(u), z1 = bhi(u);
        float mx = fmaxf(z0, z1);
        mx = fmaxf(mx, __shfl_xor_sync(~0u, mx, 4)); mx = fmaxf(mx, __shfl_xor_sync(~0u, mx, 8)); mx = fmaxf(mx, __shfl_xor_sync(~0u, mx, 16));
        mx = fmaxf(mx, mrun);
        const float f = ex2((mrun - mx) * LOG2E);
        p0 = ex2((z0 - mx) * LOG2E); p1 = ex2((z1 - mx) * LOG2E);
        mrun = mx; lrun = lrun * f + (p0 + p1);
#pragma unroll
        for (int j = 0; j < 4; j++) { o[0][j] *= f; o[1][j] *= f; }
    };
    const int kvrow = (bat * NH + head) * SK + (SK - WIN) + (w & 3) * 16;
    const int wofs = (w * 8 + (cta & 7)) * TAU / 8;
    auto request = [&](int u) {
        sts32u(bar0 + 56, u - 1);
        while ((int)(now_ns() - lds32u(sb + SM_AN) - u * 8 * TAU - wofs) < 0) nap(20);
        const int sl = (~u & 2) + (u & 1);
        mbar_expect(bar0 + sl * 8, UNIT); tma_kv(s0 + sl * REG, &P.k + (u & 1), kvrow + tile_key(u >> 1), bar0 + sl * 8, pol);
    };
#pragma unroll 1
    for (int it = 0; it < NT - 1; it++) {
        const int si = it < 3 ? it : (it + 1) & 1;
        const uint32_t bar = bar0 + si * 16, a0 = s0 + si * 2 * REG;
        const uint32_t par = it < 3 ? 0 : ((it - 1) >> 1) & 1;
        const bool refill = lane == 0 && it >= 2;
        mbar_wait(bar, par);
        if (refill) {
            request(2 * it + 2);
            const int e = it - (it > WOA_READ ? WOA_READ + 1 : WOA_ISSUE);
            if (e == 0) mbar_expect(barC, 2 * UNIT);
            if (e == 0 || e == WO_GAP) tma2d(s2 + (e ? REG : 0), &P.wo, w * 64, head * 128 + (it > WOA_READ ? 64 : 0) + (e ? 32 : 0), barC);
        }
        __syncwarp();
        if (it == WOA_READ) {
            mbar_wait(barC, 1);
#pragma unroll
            for (int j = 0; j < 16; j++) ldsm_t(wa[j], s2 + (j >> 3) * REG + ((j >> 2) & 1) * 2048 + (off128 ^ ((j & 3) << 5)));
        }
        scores(a0);
        pb[0] = movm(pack2(p0, p0)); pb[1] = movm(pack2(p1, p1));
        mbar_wait(bar + 8, par);
        if (refill) request(2 * it + 3);
        __syncwarp();
        uint32_t vf[8][4];
#pragma unroll
        for (int j = 0; j < 8; j++) ldsm_t(vf[j], ((a0 + off128) ^ ((j & 3) << 5)) + (j >> 2) * 2048 + REG);
#pragma unroll
        for (int j = 0; j < 8; j++) { const bool on = (g >> 1) == (j >> 1); mma(o[j & 1], vf[j], on ? pb[0] : 0, on ? pb[1] : 0); }
    }
    {
        uint32_t wb[16][4];
        mbar_wait(bar0, 1);
        if (rid >= DN0) bar_arrive<B_LAST, NTHR>();
        scores(s0);
        lrun += __shfl_xor_sync(~0u, lrun, 4); lrun += __shfl_xor_sync(~0u, lrun, 8); lrun += __shfl_xor_sync(~0u, lrun, 16);
        if (lane == 0) sts64(sb + SM_ML + w * 8, mrun, lrun);
        bar_arrive<B_ML, NTHR>();
        pb[0] = movm(pack2(p0, p0)); pb[1] = movm(pack2(p1, p1));
        const uint32_t va = pin(s0 + REG + off128);
        auto load_wb = [&](int j) { ldsm_t(wb[j], (va ^ ((j & 3) << 5)) + (3 + (j >> 3)) * REG + ((j >> 2) & 1) * 2048); };
        mbar_wait(barC, 0);
#pragma unroll
        for (int j = 0; j < NPRE; j++) load_wb(j);
        const uint32_t ho = pin(s0 + w * 16 + ((lane & 7) >> 1) * 64 + ((lane >> 3) & 1) * 32 + (lane & 1) * 16), oa = pin(sb + (lane & 7) * (UNIT + 16) + (lane >> 3) * 16);
        const uint32_t rd = pin((t >> 1) * 16 + w * 2 + (g >> 2));
        char* const pp = pin(X + X_PART + ((cta & 3) * 32 + rd) * 8192 + head * 128 + (g & 3) * 32 + (t & 1) * 16);
        const uint32_t ln = pin(lane);
        mbar_wait(bar0 + 8, 1);
        {
            uint32_t vf[8][4];
            float o2[2][4] = {};
#pragma unroll
            for (int j = 0; j < 8; j++) ldsm_t(vf[j], (va ^ ((j & 3) << 5)) + (j >> 2) * 2048);
#pragma unroll
            for (int j = 0; j < 8; j++) { const bool on = (ln >> 3) == (j >> 1); mma((j & 2) ? o2[j & 1] : o[j & 1], vf[j], on ? pb[0] : 0, on ? pb[1] : 0); }
            asm volatile("stmatrix.sync.aligned.m8n8.x2.trans.shared.b16 [%0], {%1,%2};" :: "r"(ho), "r"(pack2(o[0][0] + o2[0][0], o[0][2] + o2[0][2])), "r"(pack2(o[1][0] + o2[1][0], o[1][2] + o2[1][2])) : "memory");
        }
        bar_sync<B_RDY, NALL>();
        float y[4][4] = {};
        uint32_t ob[4][4];
#pragma unroll
        for (int i2 = 0; i2 < 4; i2++) ldsm(ob[i2], oa + i2 * 64);
        const float2 f = lds64(sb + SM_ML + 64 + (ln & 3) * 8);
        const unsigned half = (lds32u(sb + SM_MASK) >> rd & 1) * 4096;
#pragma unroll
        for (int j = NPRE; j < 16; j++) load_wb(j);
#pragma unroll
        for (int j = 0; j < 8; j++)
#pragma unroll
            for (int i = 0; i < 4; i++) mma(y[i], j < 4 ? wa[j * 4 + i] : wb[(j - 4) * 4 + i], ob[j >> 1][2 * (j & 1)], ob[j >> 1][2 * (j & 1) + 1]);
        uint32_t r[4];
#pragma unroll
        for (int i = 0; i < 4; i++) {
            const float lo = f.x * y[i][0] + f.y * y[i][1], hi = f.x * y[i][2] + f.y * y[i][3];
            r[i] = __float_as_uint(((ln & 1) ? hi : lo) + __shfl_xor_sync(~0u, (ln & 1) ? lo : hi, 1));
        }
        asm("min.u32 %0, %0, 0xFFFFFFFE;" : "+r"(r[0]));
        stg_b128(pp + half, make_uint4(r[0], r[1], r[2], r[3]));
    }
    const unsigned side = lds32u(sb + SM_SIDE);
    const char* const x1p = X + (rid & (XC - 1)) * 16384;
    if (rid < NF1) {
        uint32_t wg[4][4], wu[4][4];
        const char* const xp = pin(x1p + blk(X_X1, w >> 2, side) + (w & 3) * 1024 + lane * 16);
        float4 c1[2], sv[2];
#pragma unroll
        for (int h = 0; h < 2; h++) { sv[h] = lds128(sb + SM_MN + (w * 2 + h) * 512 + lane * 16); c1[h] = lds128(sb + SM_MN + 8192 + (w * 2 + h) * 512 + lane * 16); }
        const uint32_t po = pin(myscr + SC_F1 + g * 144 + t * 32), so = pin(t == (g >> 1) ? sb + SM_ST + g * 64 + w * 8 : myscr + 1792 + lane * 8), odd = pin(g & 1);
        const uint32_t wbar = sb + SM_BAR + (w >> 1) * 64 + 48;
        uint4 x0, x1;
        const bool early = go_first(wbar, 1);
        if (early) { spin(clock(), (7 - w) * XDW); x0 = ldg_rlx2x64(xp); x1 = ldg_rlx2x64(xp + 512); mbar_wait(wbar, 1); }
#pragma unroll
        for (int j = 0; j < 4; j++) {
            const uint32_t a = sb + 2 * REG + w * 2048 + (((lane & 7) >> 1) + (lane & 1) * 4 + j * 8 + (lane >> 4) * 32) * 32 + ((lch ^ (lane & 1)) << 4);
            ldsm_t(wg[j], a); ldsm_t(wu[j], a + 16384);
        }
        {
            float cg[4] = {}, cu[4] = {}, sg[4] = {}, su[4] = {};
#pragma unroll
            for (int j = 0; j < 4; j++) {
                const float4 a = c1[j & 1], b = sv[j & 1];
                const uint32_t a0 = __float_as_uint(j >> 1 ? a.z : a.x), a1 = __float_as_uint(j >> 1 ? a.w : a.y), b0 = __float_as_uint(j >> 1 ? b.z : b.x), b1 = __float_as_uint(j >> 1 ? b.w : b.y);
                mma(cg, wg[j], a0, a1); mma(cu, wu[j], a0, a1); mma(sg, wg[j], b0, b1); mma(su, wu[j], b0, b1);
            }
            const uint32_t d = s0 + REG + g * 144 + t * 32;
            sts128f(d, cg[0], cg[2], cu[0], cu[2]); sts128f(d + 16, cg[1], cg[3], cu[1], cu[3]);
            sts128f(d + 1152, sg[0], sg[2], su[0], su[2]); sts128f(d + 1168, sg[1], sg[3], su[1], su[3]);
            bar_arrive<B_PRE, NALL>();
        }
        if (!early) { mbar_wait(sb + SM_BG, 0); spin(clock(), (7 - w) * XDW); x0 = ldg_rlx2x64(xp); x1 = ldg_rlx2x64(xp + 512); }
        int n = 0;
        while (true) {
            const bool b0 = max(x0.x, x0.z) == SENT, b1 = max(x1.x, x1.z) == SENT;
            if (!__any_sync(~0u, b0 | b1)) break;
            if (b0) x0 = ldg_rlx2x64(xp);
            if (b1) x1 = ldg_rlx2x64(xp + 512);
            if (++n > SPIN_MAX) __trap();
        }
        float sm[4] = {}, q0[4] = {}, q1[4] = {}, ag[2][4] = {}, au[2][4] = {};
        {
            const uint32_t a0[4] = {x0.x, x0.y, x0.z, x0.w}, a1[4] = {x1.x, x1.y, x1.z, x1.w};
            mma(sm, a0, ONE2, ONE2); mma(q0, a0, x0.x, x0.z); mma(q1, a0, x0.y, x0.w);
            mma(sm, a1, ONE2, ONE2); mma(q0, a1, x1.x, x1.z); mma(q1, a1, x1.y, x1.w);
#pragma unroll
            for (int j = 0; j < 4; j++) {
                const uint4 xv = (j & 1) ? x1 : x0; const float4 a = c1[j & 1];
                const uint32_t h0 = mul2(j >> 1 ? xv.z : xv.x, __float_as_uint(j >> 1 ? a.z : a.x)), h1 = mul2(j >> 1 ? xv.w : xv.y, __float_as_uint(j >> 1 ? a.w : a.y));
                mma(ag[j & 1], wg[j], h0, h1); mma(au[j & 1], wu[j], h0, h1);
            }
        }
        sts64(so, sm[0] + sm[2], odd ? q0[1] + q1[3] : q0[0] + q1[2]);
        sts128f(po, ag[0][0] + ag[1][0], ag[0][2] + ag[1][2], au[0][0] + au[1][0], au[0][2] + au[1][2]);
        sts128f(po + 16, ag[0][1] + ag[1][1], ag[0][3] + ag[1][3], au[0][1] + au[1][1], au[0][3] + au[1][3]);
        bar_arrive<B_FIN, NALL>();
    } else if (rid >= DN0) {
        const int f = rid - DN0;
        uint32_t wd[12][4];
        const char* const hp0 = pin(X + blk(X_HM, 0, side) + w * 512 + lane * 16);
        const char* const hp1 = pin(X + blk(X_HM, 1, side) + w * 512 + lane * 16);
        auto hm = [&](int j) { return ldg_rlx128((j & 1 ? hp1 : hp0) + (j >> 1) * 16384); };
        __nv_bfloat16* const op = pin(P.out + ((tid >> 4) & 7) * DM + f * 16 + (tid & 15));
        const uint32_t po = pin(myscr + SC_DN + t * 160 + g * 16), pi = pin(scr + SC_DN + (w & 3) * 160 + (tid & 7) * 16 + (tid & 8) + ((tid >> 4) & 1) * 4), gi = pin(sb + SM_MN + tid * 2), first = pin(w < 4);
        uint4 hv[6]; int n = 0;
        auto first_poll = [&]() {
            spin(clock(), w * HDW);
#pragma unroll
            for (int j = 0; j < 6; j++) hv[j] = (j < 5 || w < 3) ? hm(j) : make_uint4(0, 0, 0, 0);
        };
        const bool early = go_first(sb + SM_BT, 0);
        if (early) { first_poll(); mbar_wait(sb + SM_BT, 0); }
#pragma unroll
        for (int j = 0; j < 12; j++)
            if (j < 10 || w < 3) ldsm_t(wd[j], sb + 2 * REG + 16384 + (w + (j >> 1) * 8) * 1024 + (j & 1) * 512 + (((lane >> 1) & 1) + (lane & 1) * 2 + (lane & 4) + (lane >> 4) * 8) * 32 + ((lch ^ ((lane >> 2) & 1)) << 4));
            else wd[j][0] = wd[j][1] = wd[j][2] = wd[j][3] = 0;
        if (!early) { mbar_wait(sb + SM_BG, 0); first_poll(); }
        while (true) {
            unsigned m[6];
#pragma unroll
            for (int j = 0; j < 6; j++) m[j] = max(max(hv[j].x, hv[j].y), max(hv[j].z, hv[j].w));
            if (__all_sync(~0u, max(max(max(m[0], m[1]), m[2]), max(max(m[3], m[4]), m[5])) != SENT)) break;
#pragma unroll
            for (int j = 0; j < 6; j++) if (m[j] == SENT) hv[j] = hm(j);
            if (++n > SPIN_MAX) __trap();
        }
        float d[4][4] = {};
#pragma unroll
        for (int j = 0; j < 6; j++) { mma(d[(2 * j) & 3], wd[2 * j], hv[j].x, hv[j].y); mma(d[(2 * j + 1) & 3], wd[2 * j + 1], hv[j].z, hv[j].w); }
        sts128f(po, (d[0][0] + d[1][0]) + (d[2][0] + d[3][0]), (d[0][1] + d[1][1]) + (d[2][1] + d[3][1]), (d[0][2] + d[1][2]) + (d[2][2] + d[3][2]), (d[0][3] + d[1][3]) + (d[2][3] + d[3][3]));
        if (!first) bar_arrive<B_DN, NTHR>();
        else {
            bar_sync<B_DN, NTHR>();
            float v[8];
#pragma unroll
            for (int i = 0; i < 8; i++) v[i] = lds32(pi + i * SCR);
            unsigned gw, res;
            asm volatile("ld.shared.u16 %0, [%1];" : "=r"(gw) : "r"(gi) : "memory"); asm volatile("ld.shared.u16 %0, [%1];" : "=r"(res) : "r"(gi + 256) : "memory");
            asm volatile("st.global.u16 [%0], %1;" :: "l"(op), "h"((unsigned short)add2(res, mul2(gw, pack2(((v[0] + v[1]) + (v[2] + v[3])) + ((v[4] + v[5]) + (v[6] + v[7])), 0.f)))) : "memory");
        }
    }
}

typedef CUresult (*EncodeFn)(CUtensorMap*, CUtensorMapDataType, cuuint32_t, void*, const cuuint64_t*, const cuuint64_t*, const cuuint32_t*,
                             const cuuint32_t*, CUtensorMapInterleave, CUtensorMapSwizzle, CUtensorMapL2promotion, CUtensorMapFloatOOBfill);

void make2d(EncodeFn enc, CUtensorMap* m, const void* p, int rows, int cols, int brows, int bcols, CUtensorMapSwizzle sw) {
    cuuint64_t dims[2] = {(cuuint64_t)cols, (cuuint64_t)rows}, strides[1] = {(cuuint64_t)cols * 2};
    cuuint32_t box[2] = {(cuuint32_t)bcols, (cuuint32_t)brows}, es[2] = {1, 1};
    enc(m, CU_TENSOR_MAP_DATA_TYPE_BFLOAT16, 2, (void*)p, dims, strides, box, es, CU_TENSOR_MAP_INTERLEAVE_NONE, sw,
        CU_TENSOR_MAP_L2_PROMOTION_L2_128B, CU_TENSOR_MAP_FLOAT_OOB_FILL_NONE);
}
void make5d(EncodeFn enc, CUtensorMap* m, const void* p, int cols, const unsigned (&n)[4], const unsigned (&s)[4], unsigned nb) {
    const cuuint64_t rs = (cuuint64_t)cols * 2;
    cuuint64_t dims[5] = {(cuuint64_t)cols, n[0], n[1], n[2], n[3]}, strides[4] = {rs * s[0], rs * s[1], rs * s[2], rs * s[3]};
    cuuint32_t box[5] = {16, n[0], n[1], n[2], nb}, es[5] = {1, 1, 1, 1, 1};
    enc(m, CU_TENSOR_MAP_DATA_TYPE_BFLOAT16, 5, (void*)p, dims, strides, box, es, CU_TENSOR_MAP_INTERLEAVE_NONE, CU_TENSOR_MAP_SWIZZLE_32B,
        CU_TENSOR_MAP_L2_PROMOTION_L2_128B, CU_TENSOR_MAP_FLOAT_OOB_FILL_NONE);
}
void makekv(EncodeFn enc, CUtensorMap* m, const void* p) {
    cuuint64_t dims[3] = {64, (cuuint64_t)NB * NH * SK, 2}, strides[2] = {256, 128};
    cuuint32_t box[3] = {64, 16, 2}, es[3] = {1, 1, 1};
    enc(m, CU_TENSOR_MAP_DATA_TYPE_BFLOAT16, 3, (void*)p, dims, strides, box, es, CU_TENSOR_MAP_INTERLEAVE_NONE, CU_TENSOR_MAP_SWIZZLE_128B,
        CU_TENSOR_MAP_L2_PROMOTION_NONE, CU_TENSOR_MAP_FLOAT_OOB_FILL_NONE);
}

}

extern "C" void kernel_launch(void* const* d_in, const int* in_sizes, int n_in, void* d_out, int out_size) {
    (void)in_sizes; (void)n_in; (void)out_size;
    static EncodeFn enc = nullptr;
    static void* raw = nullptr;
    if (!enc) {
        void* fn = nullptr; cudaDriverEntryPointQueryResult qr;
        cudaGetDriverEntryPoint("cuTensorMapEncodeTiled", &fn, cudaEnableDefault, &qr);
        enc = (EncodeFn)fn;
        cudaFuncSetAttribute(fused_kernel, cudaFuncAttributeMaxDynamicSharedMemorySize, SM_TOTAL);
        cudaGetSymbolAddress(&raw, g_raw);
    }
    Params P;
    makekv(enc, &P.k, d_in[1]);
    makekv(enc, &P.v, d_in[2]);
    make2d(enc, &P.wq, d_in[3], DM, NH * DH, 64, 32, CU_TENSOR_MAP_SWIZZLE_64B);
    make2d(enc, &P.wo, d_in[4], NH * DH, DM, 32, 64, CU_TENSOR_MAP_SWIZZLE_128B);
    make2d(enc, &P.wm, d_in[10], DM, 6 * DM, 256, 8, CU_TENSOR_MAP_SWIZZLE_NONE);
    make2d(enc, &P.wn, d_in[10], DM, 6 * DM, 256, 16, CU_TENSOR_MAP_SWIZZLE_32B);
    make5d(enc, &P.wg, d_in[6], FF, {4, 2, 4, 16}, {1, 16, 4, 32}, 4);
    make5d(enc, &P.wu, d_in[7], FF, {4, 2, 4, 16}, {1, 16, 4, 32}, 4);
    make5d(enc, &P.wd, d_in[8], DM, {8, 4, 1, 43}, {4, 1, 1, 32}, 43);
    P.out = (__nv_bfloat16*)d_out;
    typedef const __nv_bfloat16* W;
    fused_kernel<<<NCTA, NALL, SM_TOTAL>>>((W)d_in[0], (W)d_in[9], (W)d_in[1], (W)d_in[10], (W)d_in[3], (char*)(((size_t)raw + X_ALIGN - 1) & ~(size_t)(X_ALIGN - 1)), P);
}
```

```cpp
#include <cuda_runtime.h>
#include <cuda_bf16.h>
#include <cuda.h>
#include <stdint.h>

namespace {

constexpr int NB = 8, DM = 512, NH = 32, DH = 128, SK = 4096, WIN = 1024, FF = 1376;
constexpr int NCTA = 128, NTHR = 288, NALL = 320;
constexpr int NT = 16;
constexpr int NF1 = 86, DN0 = 96;
constexpr unsigned SENT = 0xFFFFFFFFu;
constexpr int SPIN_MAX = 1 << 20;

constexpr int PWIN0 = 12;
constexpr int PWIN = 16;
constexpr int PSW = 22;
constexpr int NTRK = 8;
constexpr int PFK = 2;
constexpr int QN = 7;
constexpr int TAU = 166;
constexpr int ANCH0 = 176;
constexpr int LEAD = 1600;
constexpr int PACE0 = 7000;
constexpr int PNAP = 200;
constexpr int WOA_ISSUE = 3;
constexpr int WO_GAP = 2;
constexpr int WOA_READ = 8;
constexpr int NPRE = 9;
constexpr int W0 = 850;
constexpr int WS = 180;
constexpr int WD0 = 1700;
constexpr int RT0 = 1700;
constexpr int HD0 = 1000;
constexpr int XDW = 30;
constexpr int HDW = 45;
constexpr int XC = 2;

constexpr int UNIT = 4096, REG = 8 * UNIT;
constexpr int SM_SCR = 6 * REG;
constexpr int SCR = 2048;
constexpr int SM_MN = SM_SCR + 8 * SCR;
constexpr int SM_SC = SM_MN + 8192;
constexpr int SM_BAR = SM_SC + 8192;
constexpr int SM_BM = SM_BAR + 512, SM_BT = SM_BM + 8, SM_BN = SM_BM + 16, SM_BG = SM_BM + 24;
constexpr int SM_AN = SM_BM + 32, SM_SIDE = SM_BM + 36, SM_TAG = SM_BM + 40, SM_MASK = SM_BM + 44;
constexpr int SM_ST = SM_BAR + 576;
constexpr int SM_ML = SM_ST + 512;
constexpr int SM_PR = SM_ML + 96;
constexpr int SM_TOTAL = SM_PR + 512;
constexpr int SC_M = 0, SC_Q = 256;
constexpr int SC_F1 = 0, SC_DN = 0, SC_RX = 1536;
constexpr int B_INIT = 0, B_ALL = 2, B_MOD = 3, B_WQ = 4, B_LAST = 5, B_RDY = 6, B_DN = 7, B_PRE = 8, B_FIN = 9, B_STG = 10, B_SIDE = 11, B_Q = 12, B_ML = 13;

constexpr unsigned HOME = 0xB3000;
constexpr int X_PART = 0;
constexpr int X_Q = 0x100000;
constexpr int X_M1 = 0x140000;
constexpr int X_X1 = 0x150000;
constexpr int X_HM = 0x160000;
constexpr int X_MOD = 0x170000;
constexpr int X_SIDE = 0x176000;
constexpr int X_EPOCH = 0x176400;
constexpr int X_READY = 0x176480;
constexpr int X_LAG = 0x178000;
constexpr int X_ANC = 0x158000;
constexpr int X_PRB = 0x180000;
constexpr int X_ALIGN = 0x200000;
static_assert(XC == 2, "one store writes all copies of x1");
__device__ uint4 g_raw[2 * X_ALIGN / 16];
__device__ __forceinline__ unsigned blk(unsigned base, unsigned k, unsigned s) { const unsigned o = base + k * 8192; return o + ((__popc(o & HOME) ^ s) & 1) * 4096; }

struct Params {
    CUtensorMap wm, wq, k, v, wn, wo, wg, wu, wd;
    __nv_bfloat16* out;
};

__device__ __forceinline__ int tile_key(int i) { return (i & 1) * 128 + (i & 2) * 32 + (i & 12) * 64; }

__device__ __forceinline__ uint32_t smem_u32(const void* p) { return (uint32_t)__cvta_generic_to_shared(p); }
__device__ __forceinline__ void mbar_init(uint32_t a, uint32_t c) { asm volatile("mbarrier.init.shared::cta.b64 [%0], %1;" :: "r"(a), "r"(c) : "memory"); }
__device__ __forceinline__ void mbar_expect(uint32_t a, uint32_t b) { asm volatile("mbarrier.arrive.expect_tx.shared::cta.b64 _, [%0], %1;" :: "r"(a), "r"(b) : "memory"); }
__device__ __forceinline__ void mbar_wait(uint32_t a, uint32_t par) {
    uint32_t ok; int n = 0;
    do {
        asm volatile("{\n.reg .pred p;\nmbarrier.try_wait.parity.shared::cta.b64 p, [%1], %2, 2000;\nselp.u32 %0, 1, 0, p;\n}" : "=r"(ok) : "r"(a), "r"(par) : "memory");
        if (++n > SPIN_MAX) __trap();
    } while (!ok);
}
__device__ __forceinline__ bool mbar_test(uint32_t a, uint32_t par) {
    uint32_t ok; asm volatile("{\n.reg .pred p;\nmbarrier.test_wait.parity.shared::cta.b64 p, [%1], %2;\nselp.u32 %0, 1, 0, p;\n}" : "=r"(ok) : "r"(a), "r"(par) : "memory"); return ok;
}
__device__ __forceinline__ void tma2d(uint32_t dst, const CUtensorMap* m, int x, int y, uint32_t bar) {
    asm volatile("cp.async.bulk.tensor.2d.shared::cluster.global.mbarrier::complete_tx::bytes [%0], [%1, {%3, %4}], [%2];"
                 :: "r"(dst), "l"(m), "r"(bar), "r"(x), "r"(y) : "memory");
}
__device__ __forceinline__ void tma5d(uint32_t dst, const CUtensorMap* m, int x, int y, uint32_t bar) {
    asm volatile("cp.async.bulk.tensor.5d.shared::cluster.global.mbarrier::complete_tx::bytes [%0], [%1, {%3, 0, 0, 0, %4}], [%2];"
                 :: "r"(dst), "l"(m), "r"(bar), "r"(x), "r"(y) : "memory");
}
__device__ __forceinline__ void tma_kv(uint32_t dst, const CUtensorMap* m, int row, uint32_t bar, uint64_t pol) {
    asm volatile("cp.async.bulk.tensor.3d.shared::cluster.global.mbarrier::complete_tx::bytes.L2::cache_hint [%0], [%1, {0, %3, 0}], [%2], %4;"
                 :: "r"(dst), "l"(m), "r"(bar), "r"(row), "l"(pol) : "memory");
}
__device__ __forceinline__ void pf_bulk(const void* p, uint32_t n) { asm volatile("cp.async.bulk.prefetch.L2.global [%0], %1;" :: "l"(p), "r"(n) : "memory"); }
__device__ __forceinline__ void pf_if(const void* p, unsigned i, unsigned n) { asm volatile("{\n.reg .pred p;\nsetp.lt.u32 p, %1, %2;\n@p prefetch.global.L2 [%0];\n}" :: "l"(p), "r"(i), "r"(n) : "memory"); }
__device__ __forceinline__ uint4 ldg_nc(const void* p) { uint4 v; asm volatile("ld.global.nc.v4.u32 {%0,%1,%2,%3}, [%4];" : "=r"(v.x), "=r"(v.y), "=r"(v.z), "=r"(v.w) : "l"(p)); return v; }
__device__ __forceinline__ bool elect() { uint32_t p; asm volatile("{\n.reg .pred p;\nelect.sync _|p, -1;\nselp.u32 %0, 1, 0, p;\n}" : "=r"(p)); return p; }
__device__ __forceinline__ void pf_map(const CUtensorMap* m) { asm volatile("prefetch.tensormap [%0];" :: "l"(m) : "memory"); }
__device__ __forceinline__ void ldsm(uint32_t (&r)[4], uint32_t a) {
    asm volatile("ldmatrix.sync.aligned.m8n8.x4.shared.b16 {%0,%1,%2,%3}, [%4];" : "=r"(r[0]), "=r"(r[1]), "=r"(r[2]), "=r"(r[3]) : "r"(a) : "memory");
}
__device__ __forceinline__ void ldsm_t(uint32_t (&r)[4], uint32_t a) {
    asm volatile("ldmatrix.sync.aligned.m8n8.x4.trans.shared.b16 {%0,%1,%2,%3}, [%4];" : "=r"(r[0]), "=r"(r[1]), "=r"(r[2]), "=r"(r[3]) : "r"(a) : "memory");
}
__device__ __forceinline__ void mma(float (&c)[4], uint32_t a0, uint32_t a1, uint32_t a2, uint32_t a3, uint32_t b0, uint32_t b1) {
    asm("mma.sync.aligned.m16n8k16.row.col.f32.bf16.bf16.f32 {%0,%1,%2,%3}, {%4,%5,%6,%7}, {%8,%9}, {%0,%1,%2,%3};"
        : "+f"(c[0]), "+f"(c[1]), "+f"(c[2]), "+f"(c[3]) : "r"(a0), "r"(a1), "r"(a2), "r"(a3), "r"(b0), "r"(b1));
}
__device__ __forceinline__ void mma(float (&c)[4], const uint32_t (&a)[4], uint32_t b0, uint32_t b1) { mma(c, a[0], a[1], a[2], a[3], b0, b1); }
__device__ __forceinline__ uint32_t pin(uint32_t v) { asm volatile("shfl.sync.bfly.b32 %0, %0, 0, 31, -1;" : "+r"(v)); return v; }
template <class T> __device__ __forceinline__ T* pin(T* p) { const size_t a = (size_t)p; return (T*)(pin((uint32_t)a) | (size_t)pin((uint32_t)(a >> 32)) << 32); }
__device__ __forceinline__ uint32_t movm(uint32_t a) { uint32_t r; asm volatile("movmatrix.sync.aligned.m8n8.trans.b16 %0, %1;" : "=r"(r) : "r"(a)); return r; }
__device__ __forceinline__ uint32_t pack2(float lo, float hi) { uint32_t r; asm("cvt.rn.bf16x2.f32 %0, %1, %2;" : "=r"(r) : "f"(hi), "f"(lo)); return r; }
__device__ __forceinline__ float blo(uint32_t w) { return __uint_as_float(w << 16); }
__device__ __forceinline__ float bhi(uint32_t w) { return __uint_as_float(w & 0xFFFF0000u); }
__device__ __forceinline__ float rbf(float x) { return blo(pack2(x, 0.f)); }
__device__ __forceinline__ uint32_t add2(uint32_t a, uint32_t b) { uint32_t r; asm("add.rn.bf16x2 %0, %1, %2;" : "=r"(r) : "r"(a), "r"(b)); return r; }
__device__ __forceinline__ uint32_t sub2(uint32_t a, uint32_t b) { uint32_t r; asm("sub.rn.bf16x2 %0, %1, %2;" : "=r"(r) : "r"(a), "r"(b)); return r; }
__device__ __forceinline__ uint32_t mul2(uint32_t a, uint32_t b) { uint32_t r; asm("mul.rn.bf16x2 %0, %1, %2;" : "=r"(r) : "r"(a), "r"(b)); return r; }
constexpr uint32_t ONE2 = 0x3F803F80u;
constexpr float LOG2E = 1.4426950408889634f, SCALE = 0.08838834764831845f;
__device__ __forceinline__ float ex2(float x) { float y; asm("ex2.approx.ftz.f32 %0, %1;" : "=f"(y) : "f"(x)); return y; }
__device__ __forceinline__ uint4 ldg_rlx128(const void* p) {
    uint4 v; asm volatile("ld.relaxed.gpu.global.v4.u32 {%0,%1,%2,%3}, [%4];" : "=r"(v.x), "=r"(v.y), "=r"(v.z), "=r"(v.w) : "l"(p) : "memory"); return v;
}
__device__ __forceinline__ uint4 ldg_rlx2x64(const void* p) {
    unsigned long long a, b; asm volatile("ld.relaxed.gpu.global.v2.u64 {%0,%1}, [%2];" : "=l"(a), "=l"(b) : "l"(p) : "memory");
    return make_uint4((unsigned)a, (unsigned)(a >> 32), (unsigned)b, (unsigned)(b >> 32));
}
__device__ __forceinline__ uint2 ldg_rlx64(const void* p) {
    unsigned long long a; asm volatile("ld.relaxed.gpu.global.u64 %0, [%1];" : "=l"(a) : "l"(p) : "memory"); return make_uint2((unsigned)a, (unsigned)(a >> 32));
}
__device__ __forceinline__ unsigned ldg_acq32(const void* p) { unsigned v; asm volatile("ld.acquire.gpu.global.u32 %0, [%1];" : "=r"(v) : "l"(p) : "memory"); return v; }
__device__ __forceinline__ void red_add(void* p, unsigned v) { asm volatile("red.relaxed.gpu.global.add.u32 [%0], %1;" :: "l"(p), "r"(v) : "memory"); }
__device__ __forceinline__ unsigned now_ns() { unsigned t; asm volatile("mov.u32 %0, %%globaltimer_lo;" : "=r"(t)); return t; }
__device__ __forceinline__ void nap(unsigned ns) { asm volatile("nanosleep.u32 %0;" :: "r"(ns)); }
__device__ __forceinline__ unsigned ldg_rlx32(const void* p) { unsigned v; asm volatile("ld.relaxed.gpu.global.u32 %0, [%1];" : "=r"(v) : "l"(p) : "memory"); return v; }
__device__ __forceinline__ void stg_rlx32(void* p, unsigned v) { asm volatile("st.relaxed.gpu.global.u32 [%0], %1;" :: "l"(p), "r"(v) : "memory"); }
__device__ __forceinline__ void stg_rlx16(void* p, unsigned v) { asm volatile("st.relaxed.gpu.global.u16 [%0], %1;" :: "l"(p), "h"((unsigned short)v) : "memory"); }
__device__ __forceinline__ uint4 ldg_b128(const void* p) {
    unsigned long long a, b; asm volatile("{\n.reg .b128 x;\nld.relaxed.gpu.global.b128 x, [%2];\nmov.b128 {%0,%1}, x;\n}" : "=l"(a), "=l"(b) : "l"(p) : "memory");
    return make_uint4((unsigned)a, (unsigned)(a >> 32), (unsigned)b, (unsigned)(b >> 32));
}
__device__ __forceinline__ void stg_b128(void* p, uint4 v) {
    asm volatile("{\n.reg .b128 x;\nmov.b128 x, {%1,%2};\nst.relaxed.gpu.global.b128 [%0], x;\n}" :: "l"(p), "l"(v.x | ((unsigned long long)v.y << 32)), "l"(v.z | ((unsigned long long)v.w << 32)) : "memory");
}
__device__ __forceinline__ int rowoff(int b, int c) { return ((c >> 6) * 2 + ((c >> 2) & 1)) * 512 + b * 64 + (c & 3) * 16 + ((c >> 3) & 1) * 8 + ((c >> 5) & 1) * 4 + ((c >> 4) & 1) * 2; }
__device__ __forceinline__ void stg_rlx64(void* p, unsigned lo, unsigned hi) {
    unsigned long long a = lo | ((unsigned long long)hi << 32); asm volatile("st.relaxed.gpu.global.u64 [%0], %1;" :: "l"(p), "l"(a) : "memory");
}
__device__ __forceinline__ void stg_rlx128(void* p, uint4 v) { asm volatile("st.relaxed.gpu.global.v4.u32 [%0], {%1,%2,%3,%4};" :: "l"(p), "r"(v.x), "r"(v.y), "r"(v.z), "r"(v.w) : "memory"); }
__device__ __forceinline__ void sts32u(uint32_t a, unsigned x) { asm volatile("st.volatile.shared.u32 [%0], %1;" :: "r"(a), "r"(x) : "memory"); }
__device__ __forceinline__ unsigned lds32u(uint32_t a) { unsigned v; asm volatile("ld.volatile.shared.u32 %0, [%1];" : "=r"(v) : "r"(a) : "memory"); return v; }
__device__ __forceinline__ void spin(unsigned c0, unsigned d) { if (d) while ((unsigned)clock() - c0 < d) {} }
__device__ __forceinline__ void fence_gpu() { asm volatile("fence.acq_rel.gpu;" ::: "memory"); }
template <int ID, int N> __device__ __forceinline__ void bar_sync() { asm volatile("bar.sync %0, %1;" :: "n"(ID), "n"(N) : "memory"); }
template <int ID, int N> __device__ __forceinline__ void bar_arrive() { asm volatile("bar.arrive %0, %1;" :: "n"(ID), "n"(N) : "memory"); }
__device__ __forceinline__ void sts64(uint32_t a, float x, float y) { asm volatile("st.shared.v2.f32 [%0], {%1,%2};" :: "r"(a), "f"(x), "f"(y) : "memory"); }
__device__ __forceinline__ void sts128(uint32_t a, uint4 v) { asm volatile("st.volatile.shared.v4.u32 [%0], {%1,%2,%3,%4};" :: "r"(a), "r"(v.x), "r"(v.y), "r"(v.z), "r"(v.w) : "memory"); }
__device__ __forceinline__ void sts128f(uint32_t a, float x, float y, float z, float w) { asm volatile("st.volatile.shared.v4.f32 [%0], {%1,%2,%3,%4};" :: "r"(a), "f"(x), "f"(y), "f"(z), "f"(w) : "memory"); }
__device__ __forceinline__ void sts32(uint32_t a, float x) { asm volatile("st.shared.f32 [%0], %1;" :: "r"(a), "f"(x) : "memory"); }
__device__ __forceinline__ float2 lds64(uint32_t a) { float2 v; asm volatile("ld.shared.v2.f32 {%0,%1}, [%2];" : "=f"(v.x), "=f"(v.y) : "r"(a) : "memory"); return v; }
__device__ __forceinline__ float lds32(uint32_t a) { float v; asm volatile("ld.shared.f32 %0, [%1];" : "=f"(v) : "r"(a) : "memory"); return v; }
__device__ __forceinline__ float4 lds128(uint32_t a) { float4 v; asm volatile("ld.shared.v4.f32 {%0,%1,%2,%3}, [%4];" : "=f"(v.x), "=f"(v.y), "=f"(v.z), "=f"(v.w) : "r"(a) : "memory"); return v; }
__device__ __forceinline__ float2 sum8(uint32_t a) {
    float2 v[8];
#pragma unroll
    for (int i = 0; i < 8; i++) v[i] = lds64(a + i * SCR);
    return make_float2(((v[0].x + v[1].x) + (v[2].x + v[3].x)) + ((v[4].x + v[5].x) + (v[6].x + v[7].x)),
                       ((v[0].y + v[1].y) + (v[2].y + v[3].y)) + ((v[4].y + v[5].y) + (v[6].y + v[7].y)));
}
template <int STRIDE> __device__ __forceinline__ float4 sum8x4(uint32_t a) {
    float4 v[8];
#pragma unroll
    for (int i = 0; i < 8; i++) v[i] = lds128(a + i * STRIDE);
    return make_float4(((v[0].x + v[1].x) + (v[2].x + v[3].x)) + ((v[4].x + v[5].x) + (v[6].x + v[7].x)), ((v[0].y + v[1].y) + (v[2].y + v[3].y)) + ((v[4].y + v[5].y) + (v[6].y + v[7].y)),
                       ((v[0].z + v[1].z) + (v[2].z + v[3].z)) + ((v[4].z + v[5].z) + (v[6].z + v[7].z)), ((v[0].w + v[1].w) + (v[2].w + v[3].w)) + ((v[4].w + v[5].w) + (v[6].w + v[7].w)));
}
__device__ __forceinline__ float rcp(float x) { float y; asm("rcp.approx.ftz.f32 %0, %1;" : "=f"(y) : "f"(x)); return y; }
__device__ __forceinline__ float sigmoid_f(float x) { return rcp(1.0f + ex2(x * -LOG2E)); }
__device__ __forceinline__ uint32_t silu2(uint32_t c) { const float a = blo(c), b = bhi(c); return pack2(a * sigmoid_f(a), b * sigmoid_f(b)); }
__device__ __forceinline__ void ln_consts(float mean, float var, uint32_t& mu2, float& rs) {
    mu2 = pack2(mean, mean);
    float sd; asm("sqrt.approx.ftz.f32 %0, %1;" : "=f"(sd) : "f"(rbf(rbf(var) + 1e-5f)));
    rs = rcp(rbf(sd));
}
__device__ __forceinline__ uint32_t ln_norm(uint32_t x2, uint32_t mu2, float rs) { const uint32_t d = sub2(x2, mu2); return pack2(blo(d) * rs, bhi(d) * rs); }

__global__ void __launch_bounds__(NALL, 1) fused_kernel(const __nv_bfloat16* const px, const __nv_bfloat16* const pc, const __nv_bfloat16* const pk, const __nv_bfloat16* const pwm,
                                                        const __nv_bfloat16* const pwq, char* const X, const __grid_constant__ Params P) {
    extern __shared__ __align__(1024) unsigned char smem[];
    const uint32_t sb = smem_u32(smem);
    const int tid = threadIdx.x, w = tid >> 5, lane = tid & 31, g = lane >> 2, t = lane & 3;
    const int cta = blockIdx.x, head = cta >> 2, bat = (cta & 3) * 2 + (w >> 2);
    const uint32_t s0 = sb + w * UNIT, s2 = s0 + 4 * REG;
    const uint32_t bar0 = sb + SM_BAR + w * 64;
    const uint32_t barC = bar0 + 32;
    const uint32_t scr = sb + SM_SCR, myscr = scr + w * SCR;
    pf_if((const char*)pwm + ((cta * 4 + (lane >> 3)) * (6 * DM * 2) + w * 1024 + (lane & 7) * 128), w, 5);
    pf_if((const char*)pk + (unsigned)(((((cta & 3) * 2 + (w & 1)) * NH + head) * SK + (SK - WIN - 48) + tile_key(2) + (w >> 1) * 16) * (DH * 2) + lane * 128), w - 6, PFK);
    const int rid = !(cta & 1) ? cta >> 1 : (cta >> 2) + (cta & 2 ? 64 : 96);
    const unsigned t_start = now_ns();
    uint64_t pol;
    asm volatile("createpolicy.fractional.L2::evict_first.b64 %0, 1.0;" : "=l"(pol));
    auto go_first = [&](uint32_t wbar, uint32_t par) {
        for (int n = 0;; n++) {
            if (__all_sync(~0u, mbar_test(wbar, par))) return false;
            if (__all_sync(~0u, mbar_test(sb + SM_BG, 0))) return true;
            if (n > SPIN_MAX * 4) __trap();
            nap(20);
        }
    };
    if (w == 9) {
        const uint32_t sl = sb + SM_PR + lane * 16;
        char* const pl = X + blk(X_PRB, cta >> 1, lane & 1) + (lane >> 1) * 256 + (cta & 1) * 128;
        {
            char* const ps = X + X_PRB + (cta >> 1) * 8192 + g * 256 + (cta & 1) * 128 + t * 16;
            sts32u(sl, 0);
#pragma unroll
            for (int i = 0; i < 4; i++) stg_rlx128(ps + i * 2048, make_uint4(1, 1, 1, 1));
            __syncwarp();
        }
        unsigned v; asm volatile("atom.relaxed.gpu.global.add.u32 %0, [%1], 1;" : "=r"(v) : "l"(pl) : "memory");
        unsigned tag = ldg_rlx32(X + X_EPOCH);
        if (lane == 0) pf_bulk(pwq + (size_t)cta * QN * 1024, QN * 2048);
        if (lane == 0) sts32u(sb + SM_AN, t_start + ANCH0);
        if (lane < 8) sts32u(sb + SM_BAR + lane * 64 + 56, 0);
        unsigned side;
        {
            int d, n = 0;
#pragma unroll 1
            for (int r = 0; r < 4; r++) {
                if (v == SENT) __trap();
                asm volatile("cp.async.cg.shared.global [%0], [%1], 16;" :: "r"(sl), "l"(pl) : "memory");
                unsigned m;
                do {
                    m = __ballot_sync(~0u, lds32u(sl));
                    d = __popc(m & 0xAAAAAAAAu) - __popc(m & 0x55555555u);
                    if (++n > SPIN_MAX) __trap();
                } while (abs(d) < 6 && m != ~0u);
                if (abs(d) >= 6) break;
                asm volatile("cp.async.wait_all;" ::: "memory");
                sts32u(sl, 0);
                asm volatile("atom.relaxed.gpu.global.add.u32 %0, [%1], 1;" : "=r"(v) : "l"(pl) : "memory");
            }
            side = d > 0;
            tag++;
            if (lane == 0) { sts32u(sb + SM_SIDE, side); sts32u(sb + SM_TAG, tag); }
            bar_arrive<B_SIDE, NTHR>();
        }
        asm volatile("cp.async.wait_all;" ::: "memory");
        while (now_ns() - t_start < PACE0) nap(200);
        for (int n = 0; n < SPIN_MAX; n++) {
            const uint32_t wb = sb + SM_BAR + (lane & 7) * 64;
            const unsigned seen = lds32u(wb + 56), u = seen + ((lane >> 3) & 1), t1 = now_ns();
            const unsigned more = mbar_test(wb + (u < 6 ? u : (~u & 2) + (u & 1)) * 8, u < 6 ? 0 : ((u - 2) >> 2) & 1);
            const unsigned lo = __reduce_min_sync(~0u, seen), sum = __reduce_add_sync(~0u, lane < 8 ? seen + more : lane < 16 ? more : 0);
            if (lo == 30) break;
            if (lo && lane < 2) stg_rlx64(X + X_LAG + (cta >> 5) * 8192 + lane * 4096 + (cta & 31) * 128, t1 - sum * TAU, tag);
            uint2 a = make_uint2(0, 0);
            if (cta == 0) {
                uint2 u[4];
#pragma unroll
                for (int i = 0; i < 4; i++) u[i] = ldg_rlx64(X + blk(X_LAG, i, side) + lane * 128);
                const int s = __reduce_add_sync(~0u, (int)(u[0].x + u[1].x + u[2].x + u[3].x - 4 * t_start));
                if (__all_sync(~0u, (u[0].y == tag) & (u[1].y == tag) & (u[2].y == tag) & (u[3].y == tag)) && lane < 2) {
                    a = make_uint2(t_start + s / NCTA, tag);
                    stg_rlx64(X + X_ANC + lane * 4096, a.x, tag);
                }
            } else if (lane == 0) a = ldg_rlx64(X + blk(X_ANC, 0, side));
            if (lane == 0 && a.y == tag) sts32u(sb + SM_AN, a.x - LEAD);
            __syncwarp();
            nap(PNAP);
        }
        {
            bar_sync<B_ML, NTHR>();
            const float2 ml = lds64(sb + SM_ML + (lane & 7) * 8);
            float M = fmaxf(ml.x, __shfl_xor_sync(~0u, ml.x, 1)); M = fmaxf(M, __shfl_xor_sync(~0u, M, 2));
            const float e = ex2((ml.x - M) * LOG2E);
            float L = e * ml.y; L += __shfl_xor_sync(~0u, L, 1); L += __shfl_xor_sync(~0u, L, 2);
            if (lane < 8) sts32(sb + SM_ML + 64 + lane * 4, e * rcp(L));
        }
        bar_arrive<B_RDY, NALL>();
        bar_sync<B_STG, 64>();
        {
            const char* const pp = pin(X + blk(X_PART, cta, side) + lane * 16);
            char* const xo = pin(X + (lane >> 4) * 16384 + blk(X_X1, (cta >> 3) & 1, lane >> 3) + (cta & 7) * 512 + (cta >> 4) * 64 + (lane & 7) * 8);
            const float4 gx = lds128(scr + SC_RX + (lane & 7) * 16);
            const unsigned t0 = lds32u(sb + SM_AN) + 256 * TAU + RT0 + (cta & 7) * (TAU / 8);
            while ((int)(now_ns() - t0) < 0) nap(20);
            uint4 v[8]; int n = 0;
            float a[4];
#pragma unroll
            for (int j = 0; j < 8; j++) v[j] = ldg_b128(pp + j * 512);
            while (true) {
#define RSUM(f) (((__uint_as_float(v[0].f) + __uint_as_float(v[1].f)) + (__uint_as_float(v[2].f) + __uint_as_float(v[3].f))) + ((__uint_as_float(v[4].f) + __uint_as_float(v[5].f)) + (__uint_as_float(v[6].f) + __uint_as_float(v[7].f))))
                const bool ok = __all_sync(~0u, max(max(max(v[0].x, v[1].x), max(v[2].x, v[3].x)), max(max(v[4].x, v[5].x), max(v[6].x, v[7].x))) != SENT);
                a[0] = RSUM(x); a[1] = RSUM(y); a[2] = RSUM(z); a[3] = RSUM(w);
                asm volatile("" : "+f"(a[0]), "+f"(a[1]), "+f"(a[2]), "+f"(a[3]));
                if (ok) break;
#pragma unroll
                for (int j = 0; j < 8; j++) if (v[j].x == SENT) v[j] = ldg_b128(pp + j * 512);
                if (++n > SPIN_MAX) __trap();
            }
#pragma unroll
            for (int i = 0; i < 4; i++) a[i] += __shfl_xor_sync(~0u, a[i], 8);
#pragma unroll
            for (int i = 0; i < 4; i++) a[i] += __shfl_xor_sync(~0u, a[i], 16);
            stg_rlx64(xo, add2(__float_as_uint(gx.z), mul2(__float_as_uint(gx.x), pack2(a[0], a[1]))), add2(__float_as_uint(gx.w), mul2(__float_as_uint(gx.y), pack2(a[2], a[3]))));
        }
        if (rid >= DN0) {
            const unsigned c1 = clock();
            const int f = rid - DN0;
            const char* const rp = X + (rid & (XC - 1)) * 16384 + blk(X_X1, f >> 4, side) + (rowoff(g, f * 16 + t * 4) & 4092);
            unsigned r[4]; int n = 0;
            spin(c1, HD0 - 450);
            do {
#pragma unroll
                for (int i = 0; i < 4; i++) r[i] = ldg_rlx32(rp + i * 16);
                if (++n > SPIN_MAX) __trap();
            } while (max(max(r[0], r[1]), max(r[2], r[3])) == SENT);
            const unsigned sel = (f & 1) ? 0x7632 : 0x5410;
            sts64(sb + SM_MN + 256 + lane * 8, __uint_as_float(__byte_perm(r[0], r[1], sel)), __uint_as_float(__byte_perm(r[2], r[3], sel)));
            __syncwarp();
            spin(c1, HD0);
        }
        if (lane == 0) asm volatile("mbarrier.arrive.shared::cta.b64 _, [%0];" :: "r"(sb + SM_BG) : "memory");
    } else if (w == 8) {
        const int row0 = ((cta & 3) * 2 * NH + head) * SK + (SK - WIN);
        auto kv_unit = [&](int u) {
            const uint32_t b = sb + SM_BAR + (u & 7) * 64 + (u >> 3) * 8;
            mbar_expect(b, UNIT);
            tma_kv(sb + (u >> 3) * REG + (u & 7) * UNIT, (u & 8) ? &P.v : &P.k, row0 + ((u >> 2) & 1) * NH * SK + (u & 3) * 16 + tile_key(u >> 4), b, pol);
        };
        if (elect()) {
            mbar_init(sb + SM_BM, 1);
#pragma unroll
            for (int i = 0; i < 8; i++) mbar_init(sb + SM_BAR + i * 64 + 48, 1);
            asm volatile("fence.mbarrier_init.release.cluster;" ::: "memory");
            mbar_expect(sb + SM_BM, 512 * 16);
            tma2d(sb + 4 * REG, &P.wm, cta * 8, 0, sb + SM_BM); tma2d(sb + 4 * REG + 256 * 16, &P.wm, cta * 8, 256, sb + SM_BM);
#pragma unroll
            for (int i = 0; i < 8; i++) { const uint32_t b = sb + SM_BAR + i * 64 + 48; mbar_expect(b, UNIT); tma2d(sb + 5 * REG + i * UNIT, &P.wq, cta * 32, i * 64, b); }
            mbar_init(sb + SM_BN, 1); mbar_init(sb + SM_BT, 1); mbar_init(sb + SM_BG, 1);
#pragma unroll
            for (int i = 0; i < 48; i++) mbar_init(sb + SM_BAR + (i & 7) * 64 + (i >> 3) * 8, 1);
            asm volatile("fence.mbarrier_init.release.cluster;" ::: "memory");
        }
        __syncwarp();
        bar_arrive<B_INIT, NTHR>();
        {
            uint32_t mine = lane >= NTRK ? 0 : lane < 8 ? sb + SM_BAR + lane * 64 + 48 : sb + SM_BM;
            int next = 0, lim = 32, n = 0;
            while (next < 48) {
                const bool idle = lane < (next < PSW ? PWIN0 : PWIN) && (mine == 0 || mbar_test(mine, 0));
                const unsigned m = __ballot_sync(~0u, idle);
                const int u = next + __popc(m & ((1u << lane) - 1));
                if (idle) {
                    mine = 0;
                    if (u < lim) { kv_unit(u); mine = sb + SM_BAR + (u & 7) * 64 + (u >> 3) * 8; }
                }
                next = min(next + __popc(m), lim);
                if (next == lim) {
                    if (lim == 32) { bar_sync<B_MOD, NTHR>(); } else if (lim == 40) { bar_sync<B_WQ, NTHR>(); }
                    lim += 8;
                }
                if (!m) nap(30);
                if (++n > SPIN_MAX) __trap();
            }
        }
        if (lane < 5) pf_map(&P.wn + lane);
        float m[4][4] = {};
        auto late_mod = [&](uint32_t a, int h) {
            const int lrow = (lane & 7) + ((lane >> 4) << 3), lch = (lane >> 3) & 1;
            const uint32_t a0 = a + lrow * 32 + ((lch ^ ((lrow >> 2) & 1)) << 4);
            const uint32_t c0 = sb + SM_SC + h * 4096 + (lane & 7) * 128 + (((lane >> 3) ^ (lane & 7)) << 4);
#pragma unroll
            for (int j = 0; j < 8; j++) {
                uint32_t c[4], r[4], u[4];
                ldsm(c, (c0 + (j >> 1) * 1024) ^ ((j & 1) << 6)); ldsm_t(r, a0 + j * 1024); ldsm_t(u, a0 + j * 1024 + 512);
                mma(m[(j & 1) * 2], r, c[0], c[1]); mma(m[(j & 1) * 2 + 1], u, c[2], c[3]);
            }
        };
        if (rid < 96) {
#pragma unroll 1
            for (int h = 0; h < 2; h++) {
                if (lane == 0) { mbar_expect(sb + SM_BN, 8192); tma2d(sb + SM_MN, &P.wn, 2 * DM + rid * 16, h * 256, sb + SM_BN); }
                mbar_wait(sb + SM_BN, h);
                late_mod(sb + SM_MN, h);
                asm volatile("" :: "f"(m[0][0]), "f"(m[1][0]), "f"(m[2][0]), "f"(m[3][0]) : "memory");
                __syncwarp();
            }
#pragma unroll
            for (int e = 0; e < 4; e++) {
                float v = rbf((m[0][e] + m[1][e]) + (m[2][e] + m[3][e]));
                if (rid >= 64) v += 1.0f;
                stg_rlx16(X + X_MOD + (rid >> 5) * 8192 + rowoff(2 * t + (e & 1), (rid & 31) * 16 + g + (e >> 1) * 8), pack2(v, 0.f));
            }
        }
        {
            const unsigned side = lds32u(sb + SM_SIDE);
#pragma unroll
            for (int i = 0; i < 8; i++) stg_rlx128(X + blk(X_PART, cta, side) + i * 512 + lane * 16, make_uint4(SENT, SENT, SENT, SENT));
            if (lane == 0) stg_rlx32(X + X_SIDE + cta * 4, side);
        }
        bar_sync<B_Q, NTHR>();
        if (lane == 0) {
            const unsigned tag = lds32u(sb + SM_TAG);
            fence_gpu();
            red_add(X + X_READY, 1);
            int n = 0;
            while ((int)(ldg_acq32(X + X_READY) - tag * NCTA) < 0) { nap(1000); if (++n > SPIN_MAX) __trap(); }
            if (cta == 0) stg_rlx32(X + X_EPOCH, tag);
        }
        __syncwarp();
        {
            stg_rlx128(X + blk(X_Q, head >> 1, 0) + (head & 1) * 2048 + g * 256 + (cta & 3) * 64 + t * 16, make_uint4(0, 0, 0, 0));
            stg_rlx128(X + blk(X_Q, head >> 1, 1) + (head & 1) * 2048 + g * 256 + (cta & 3) * 64 + t * 16, make_uint4(0, 0, 0, 0));
            stg_rlx64(X + blk(X_M1, cta >> 5, lane >> 4) + (cta & 31) * 128 + (lane & 15) * 8, 0, 0);
            const int wt = (cta & 3) * 32 + lane;
            const unsigned mask = __ballot_sync(~0u, blk(X_PART, wt, ldg_rlx32(X + X_SIDE + wt * 4)) & 4096);
            if (lane == 0) sts32u(sb + SM_MASK, mask);
            if (lane < 8) {
                const int task = cta;
                const int rb = task >> 4, c = ((task & 15) >> 1) * 64 + (task & 1) * 4 + ((lane & 7) >> 1) + (lane & 1) * 8;
                const uint2 ga = ldg_rlx64(X + X_MOD + rowoff(rb, c));
                const unsigned short* const xp = (const unsigned short*)px + rb * DM + c;
                sts128(scr + (lane >> 3) * SCR + SC_RX + (lane & 7) * 16, make_uint4(ga.x, ga.y, xp[0] | (xp[16] << 16), xp[32] | (xp[48] << 16)));
            }
            if (rid < NF1) {
#pragma unroll 1
                for (int i = 0; i < 4; i++) {
                    uint4 v[8];
#pragma unroll
                    for (int j = 0; j < 8; j++) v[j] = ldg_rlx128(X + X_MOD + 8192 + (i * 8 + j) * 512 + lane * 16);
#pragma unroll
                    for (int j = 0; j < 8; j++) sts128(sb + SM_MN + (i * 8 + j) * 512 + lane * 16, v[j]);
                }
            }
        }
        bar_arrive<B_RDY, NALL>();
        bar_arrive<B_STG, 64>();
        unsigned t_ref = 0;
        auto until = [&](int x) { while ((int)(now_ns() - t_ref) < x) nap(20); };
        if (elect()) {
#pragma unroll 1
            for (int i = 0; i < 8; i++) { int n = 0; while (lds32u(sb + SM_BAR + i * 64 + 56) < 30) { nap(100); if (++n > SPIN_MAX) __trap(); } }
            t_ref = lds32u(sb + SM_AN) + 256 * TAU + (cta & 7) * (TAU / 8);
            if (rid < NF1) {
#pragma unroll
                for (int i = 0; i < 4; i++) mbar_expect(sb + SM_BAR + i * 64 + 48, 2 * UNIT);
#pragma unroll 1
                for (int i = 0; i < 4; i++) {
                    const uint32_t b = sb + SM_BAR + i * 64 + 48;
                    until(W0 + i * WS);
                    tma5d(sb + 2 * REG + i * UNIT, &P.wg, rid * 16, i * 4, b); tma5d(sb + 2 * REG + 16384 + i * UNIT, &P.wu, rid * 16, i * 4, b);
                }
            }
        }
        if (rid >= DN0) {
            bar_sync<B_LAST, NTHR>();
            if (elect()) {
                mbar_expect(sb + SM_BN, 16384); mbar_expect(sb + SM_BT, FF * 32);
                until(WD0);
                tma5d(sb + 2 * REG + 16384, &P.wd, (rid - DN0) * 16, 0, sb + SM_BT);
                tma2d(sb + 2 * REG, &P.wn, 2 * DM + rid * 16, 0, sb + SM_BN); tma2d(sb + 2 * REG + 8192, &P.wn, 2 * DM + rid * 16, 256, sb + SM_BN);
            }
        }
        __syncwarp();
        if (rid >= DN0) {
            mbar_wait(sb + SM_BN, 0);
            late_mod(sb + 2 * REG, 0); late_mod(sb + 2 * REG + 8192, 1);
#pragma unroll
            for (int e = 0; e < 2; e++)
                sts32u(sb + SM_MN + g * 32 + e * 16 + t * 4, movm(pack2((m[0][2 * e] + m[1][2 * e]) + (m[2][2 * e] + m[3][2 * e]), (m[0][2 * e + 1] + m[1][2 * e + 1]) + (m[2][2 * e + 1] + m[3][2 * e + 1]))));
            bar_arrive<B_DN, NTHR>();
        }
    }
    if (w >= 8) {
        if (rid < NF1) {
            const int b = (tid - 256) >> 3, c = tid & 7;
            char* const ho = pin(X + X_HM + (rid >> 4) * 8192 + ((rid >> 1) & 7) * 512 + b * 64 + (rid & 1) * 32 + c * 4);
            const uint32_t pi = pin(scr + SC_F1 + c * 144 + b * 16), si = pin(sb + SM_ST + b * 64);
            bar_sync<B_PRE, NALL>();
            float4 C = sum8x4<UNIT>(sb + REG + c * 144 + b * 16), S = sum8x4<UNIT>(sb + REG + 1152 + c * 144 + b * 16);
            S.x *= -LOG2E; S.y *= -LOG2E; C.x *= LOG2E; C.y *= LOG2E;
            sts128f(sb + SM_PR + lane * 16, C.x, C.y, C.z, C.w); sts128f(sb + SM_PR + lane * 16, S.x, S.y, S.z, S.w);
            sts128(sb + SM_PR + lane * 16, make_uint4(pi, si, (uint32_t)(size_t)ho, (uint32_t)((size_t)ho >> 32)));
            bar_sync<B_FIN, NALL>();
            const float4 s0_ = lds128(si), s1_ = lds128(si + 16), s2_ = lds128(si + 32), s3_ = lds128(si + 48);
            const float4 p = sum8x4<SCR>(pi);
            const float mean = (((s0_.x + s0_.z) + (s1_.x + s1_.z)) + ((s2_.x + s2_.z) + (s3_.x + s3_.z))) * (1.0f / DM);
            const float sq = (((s0_.y + s0_.w) + (s1_.y + s1_.w)) + ((s2_.y + s2_.w) + (s3_.y + s3_.w))) * (1.0f / DM);
            float rs; asm("rsqrt.approx.ftz.f32 %0, %1;" : "=f"(rs) : "f"(fmaxf(sq - mean * mean, 0.f) + 1e-5f));
            const float e0 = rs * (mean * C.x - LOG2E * p.x) + S.x, e1 = rs * (mean * C.y - LOG2E * p.y) + S.y;
            const float u0 = rs * (p.z - mean * C.z) + S.z, u1 = rs * (p.w - mean * C.w) + S.w;
            const unsigned hw = pack2(rcp(1.0f + ex2(e0)) * u0, rcp(1.0f + ex2(e1)) * u1);
            stg_rlx32(ho, hw); stg_rlx32(ho + 4096, hw);
        }
        return;
    }
    const unsigned ce = (lane >> 3) * (DM * 2) + w * 128 + (lane & 7) * 16;
    const uint4 ca = ldg_nc((const char*)pc + ce), cb = ldg_nc((const char*)pc + ce + 4 * DM * 2);
    const uint4 xa = ldg_nc((const char*)px + w * (DM * 2) + lane * 16), xb = ldg_nc((const char*)px + w * (DM * 2) + lane * 16 + 512);
    const uint4 xc = ldg_nc((const char*)px + ce), xd = ldg_nc((const char*)px + ce + 4 * DM * 2);
    if (w >= 4) pf_map(&P.wm + (w & 3));
    char* const qout = X + blk(X_Q, head >> 1, tid >> 7) + (head & 1) * 2048 + ((tid >> 4) & 7) * 256 + (cta & 3) * 64 + (tid & 3) * 16 + ((tid >> 2) & 3) * 4;
    char* const mout = X + blk(X_M1, cta >> 5, w) + (cta & 31) * 128 + lane * 4;
    stg_rlx32(qout, 0);
    if (w < 2) stg_rlx32(mout, 0);
    uint32_t sc[8], xf[8];
    {
        const uint32_t a = (lane >> 3) * 128 + (((lane & 7) ^ (lane >> 3)) << 4), b = (lane & 7) * 128 + (((lane >> 3) ^ (lane & 7)) << 4);
        const uint32_t cs = sb + SM_SC + w * 1024;
        sts128(cs + a, make_uint4(silu2(ca.x), silu2(ca.y), silu2(ca.z), silu2(ca.w)));
        sts128(cs + 512 + (a ^ 64), make_uint4(silu2(cb.x), silu2(cb.y), silu2(cb.z), silu2(cb.w)));
        sts128(myscr + a, xc); sts128(myscr + 512 + (a ^ 64), xd);
        __syncwarp();
        ldsm(*(uint32_t(*)[4])&sc[0], cs + b); ldsm(*(uint32_t(*)[4])&sc[4], cs + (b ^ 64));
        ldsm(*(uint32_t(*)[4])&xf[0], myscr + b); ldsm(*(uint32_t(*)[4])&xf[4], myscr + (b ^ 64));
        __syncwarp();
    }
    {
        float v[16] = {blo(xa.x), bhi(xa.x), blo(xa.y), bhi(xa.y), blo(xa.z), bhi(xa.z), blo(xa.w), bhi(xa.w),
                       blo(xb.x), bhi(xb.x), blo(xb.y), bhi(xb.y), blo(xb.z), bhi(xb.z), blo(xb.w), bhi(xb.w)};
        float s = 0;
#pragma unroll
        for (int i = 0; i < 16; i++) s += v[i];
#pragma unroll
        for (int o = 16; o; o >>= 1) s += __shfl_xor_sync(~0u, s, o);
        s *= (1.0f / DM);
        float q2 = 0;
#pragma unroll
        for (int i = 0; i < 16; i++) q2 += (v[i] - s) * (v[i] - s);
#pragma unroll
        for (int o = 16; o; o >>= 1) q2 += __shfl_xor_sync(~0u, q2, o);
        uint32_t mu2; float rs; ln_consts(s, q2 * (1.0f / DM), mu2, rs);
        if (lane == 0) sts64(sb + SM_ST + w * 8, __uint_as_float(mu2), rs);
    }
    const int lrow = (lane & 7) + ((lane >> 4) << 3), lch = (lane >> 3) & 1;
    const uint32_t off64 = lrow * 64 + ((lch ^ ((lrow >> 1) & 3)) << 4);
    const uint32_t off128 = lrow * 128 + ((lch ^ (lane & 7)) << 4);
    bar_sync<B_INIT, NTHR>();
    mbar_wait(sb + SM_BM, 0);
    {
        float a[4] = {0, 0, 0, 0}, b[4] = {0, 0, 0, 0};
        uint32_t r[4], u[4];
        ldsm_t(r, sb + 4 * REG + (w * 64 + lane) * 16); ldsm_t(u, sb + 4 * REG + (w * 64 + 32 + lane) * 16);
        mma(a, sc[0], 0, sc[1], 0, r[0], r[1]); mma(b, sc[4], 0, sc[5], 0, u[0], u[1]);
        mma(a, sc[2], 0, sc[3], 0, r[2], r[3]); mma(b, sc[6], 0, sc[7], 0, u[2], u[3]);
        sts64(myscr + SC_M + lane * 8, a[0] + b[0], a[1] + b[1]);
    }
    bar_arrive<B_MOD, NTHR>();
    bar_sync<B_ALL, 256>();
    if (w < 2) {
        const float2 m = sum8(scr + SC_M + lane * 8);
        stg_rlx32(mout, ~pack2(m.x, m.y));
    }
    if (tid < 8 * XC) stg_rlx128(X + X_X1 + (cta * 8 * XC + tid) * 16, make_uint4(SENT, SENT, SENT, SENT));
    else if (tid >= 232) stg_rlx128(X + X_HM + (cta * 24 + tid - 232) * 16, make_uint4(SENT, SENT, SENT, SENT));
    {
        const float2 st = lds64(sb + SM_ST + g * 8);
#pragma unroll
        for (int i = 0; i < 8; i++) xf[i] = ln_norm(xf[i], __float_as_uint(st.x), st.y);
    }
    {
        unsigned sv[8], cv[8]; int n = 0;
        bar_sync<B_SIDE, NTHR>();
        const char* const mp = X + blk(X_M1, w >> 2, lds32u(sb + SM_SIDE)) + (w & 3) * 1024 + lane * 4;
        if (lane == 0) while (!ldg_rlx32(mp + 16384 + 7 * 128)) { nap(40); if (++n > SPIN_MAX) __trap(); }
        __syncwarp();
#pragma unroll
        for (int j = 0; j < 8; j++) { sv[j] = ldg_rlx32(mp + j * 128); cv[j] = ldg_rlx32(mp + 16384 + j * 128); }
        while (true) {
            unsigned m = ~0u;
#pragma unroll
            for (int j = 0; j < 8; j++) m = min(m, min(sv[j], cv[j]));
            if (__all_sync(~0u, m)) break;
#pragma unroll
            for (int j = 0; j < 8; j++) { if (!sv[j]) sv[j] = ldg_rlx32(mp + j * 128); if (!cv[j]) cv[j] = ldg_rlx32(mp + 16384 + j * 128); }
            if (++n > SPIN_MAX) __trap();
        }
#pragma unroll
        for (int j = 0; j < 8; j++) xf[j] = add2(mul2(xf[j], add2(~cv[j], ONE2)), ~sv[j]);
        mbar_wait(bar0 + 48, 0);
        float acc[4][4] = {};
#pragma unroll
        for (int j = 0; j < 4; j++) {
            uint32_t r[4], u[4];
            ldsm_t(r, s2 + REG + j * 1024 + off64); ldsm_t(u, s2 + REG + j * 1024 + (off64 ^ 32));
            mma(acc[0], xf[2 * j], 0, xf[2 * j + 1], 0, r[0], r[2]); mma(acc[1], xf[2 * j], 0, xf[2 * j + 1], 0, r[1], r[3]);
            mma(acc[2], xf[2 * j], 0, xf[2 * j + 1], 0, u[0], u[2]); mma(acc[3], xf[2 * j], 0, xf[2 * j + 1], 0, u[1], u[3]);
        }
#pragma unroll
        for (int n2 = 0; n2 < 4; n2++) sts64(myscr + SC_Q + g * 160 + n2 * 32 + t * 8, acc[n2][0], acc[n2][1]);
    }
    bar_arrive<B_WQ, NTHR>();
    bar_sync<B_ALL, 256>();
    {
        const float2 s = sum8(scr + SC_Q + ((tid >> 4) & 7) * 160 + (tid & 15) * 8);
        stg_rlx32(qout, ~pack2(s.x, s.y));
    }
    uint32_t q[16];
    {
        int n = 0;
        const char* const qp = X + blk(X_Q, head >> 1, lds32u(sb + SM_SIDE)) + (head & 1) * 2048 + bat * 256 + t * 16;
        uint4 v[4];
#pragma unroll
        for (int j = 0; j < 4; j++) v[j] = ldg_rlx128(qp + j * 64);
        while (true) {
            bool bad[4];
#pragma unroll
            for (int j = 0; j < 4; j++) bad[j] = !min(min(v[j].x, v[j].y), min(v[j].z, v[j].w));
            if (!__any_sync(~0u, bad[0] | bad[1] | bad[2] | bad[3])) break;
#pragma unroll
            for (int j = 0; j < 4; j++) if (bad[j]) v[j] = ldg_rlx128(qp + j * 64);
            if (++n > SPIN_MAX) __trap();
        }
#pragma unroll
        for (int j = 0; j < 4; j++) { q[4 * j] = ~v[j].x; q[4 * j + 1] = ~v[j].y; q[4 * j + 2] = ~v[j].z; q[4 * j + 3] = ~v[j].w; }
    }
    bar_arrive<B_Q, NTHR>();

    float o[2][4] = {};
    float mrun = -3.0e38f, lrun = 0.f;
    uint32_t wa[16][4], pb[2];
#pragma unroll
    for (int i = 0; i < 16; i++) wa[i][0] = wa[i][1] = wa[i][2] = wa[i][3] = 0;
    const uint32_t offk = (lane & 15) * 128 + (((lane >> 4) ^ (lane & 7)) << 4);
    float p0, p1;
    auto scores = [&](uint32_t a0) {
        uint32_t kf[8][4];
#pragma unroll
        for (int j = 0; j < 8; j++) ldsm(kf[j], ((a0 + offk) ^ ((j & 3) << 5)) + (j >> 2) * 2048);
        float sa[4] = {0, 0, 0, 0}, sb2[4] = {0, 0, 0, 0};
#pragma unroll
        for (int j = 0; j < 8; j += 2) { mma(sa, kf[j], q[2 * j], q[2 * j + 1]); mma(sb2, kf[j + 1], q[2 * j + 2], q[2 * j + 3]); }
        uint32_t u = pack2(sa[0] + sb2[0], sa[2] + sb2[2]);
        u = pack2(blo(u) * SCALE, bhi(u) * SCALE);
        const float z0 = blo(u), z1 = bhi(u);
        float mx = fmaxf(z0, z1);
        mx = fmaxf(mx, __shfl_xor_sync(~0u, mx, 4)); mx = fmaxf(mx, __shfl_xor_sync(~0u, mx, 8)); mx = fmaxf(mx, __shfl_xor_sync(~0u, mx, 16));
        mx = fmaxf(mx, mrun);
        const float f = ex2((mrun - mx) * LOG2E);
        p0 = ex2((z0 - mx) * LOG2E); p1 = ex2((z1 - mx) * LOG2E);
        mrun = mx; lrun = lrun * f + (p0 + p1);
#pragma unroll
        for (int j = 0; j < 4; j++) { o[0][j] *= f; o[1][j] *= f; }
    };
    const int kvrow = (bat * NH + head) * SK + (SK - WIN) + (w & 3) * 16;
    const int wofs = (w * 8 + (cta & 7)) * TAU / 8;
    auto request = [&](int u) {
        sts32u(bar0 + 56, u - 1);
        while ((int)(now_ns() - lds32u(sb + SM_AN) - u * 8 * TAU - wofs) < 0) nap(20);
        const int sl = (~u & 2) + (u & 1);
        mbar_expect(bar0 + sl * 8, UNIT); tma_kv(s0 + sl * REG, &P.k + (u & 1), kvrow + tile_key(u >> 1), bar0 + sl * 8, pol);
    };
#pragma unroll 1
    for (int it = 0; it < NT - 1; it++) {
        const int si = it < 3 ? it : (it + 1) & 1;
        const uint32_t bar = bar0 + si * 16, a0 = s0 + si * 2 * REG;
        const uint32_t par = it < 3 ? 0 : ((it - 1) >> 1) & 1;
        const bool refill = lane == 0 && it >= 2;
        mbar_wait(bar, par);
        if (refill) {
            request(2 * it + 2);
            const int e = it - (it > WOA_READ ? WOA_READ + 1 : WOA_ISSUE);
            if (e == 0) mbar_expect(barC, 2 * UNIT);
            if (e == 0 || e == WO_GAP) tma2d(s2 + (e ? REG : 0), &P.wo, w * 64, head * 128 + (it > WOA_READ ? 64 : 0) + (e ? 32 : 0), barC);
        }
        __syncwarp();
        if (it == WOA_READ) {
            mbar_wait(barC, 1);
#pragma unroll
            for (int j = 0; j < 16; j++) ldsm_t(wa[j], s2 + (j >> 3) * REG + ((j >> 2) & 1) * 2048 + (off128 ^ ((j & 3) << 5)));
        }
        scores(a0);
        pb[0] = movm(pack2(p0, p0)); pb[1] = movm(pack2(p1, p1));
        mbar_wait(bar + 8, par);
        if (refill) request(2 * it + 3);
        __syncwarp();
        uint32_t vf[8][4];
#pragma unroll
        for (int j = 0; j < 8; j++) ldsm_t(vf[j], ((a0 + off128) ^ ((j & 3) << 5)) + (j >> 2) * 2048 + REG);
#pragma unroll
        for (int j = 0; j < 8; j++) { const bool on = (g >> 1) == (j >> 1); mma(o[j & 1], vf[j], on ? pb[0] : 0, on ? pb[1] : 0); }
    }
    {
        uint32_t wb[16][4];
        mbar_wait(bar0, 1);
        if (rid >= DN0) bar_arrive<B_LAST, NTHR>();
        scores(s0);
        lrun += __shfl_xor_sync(~0u, lrun, 4); lrun += __shfl_xor_sync(~0u, lrun, 8); lrun += __shfl_xor_sync(~0u, lrun, 16);
        if (lane == 0) sts64(sb + SM_ML + w * 8, mrun, lrun);
        bar_arrive<B_ML, NTHR>();
        pb[0] = movm(pack2(p0, p0)); pb[1] = movm(pack2(p1, p1));
        const uint32_t va = pin(s0 + REG + off128);
        auto load_wb = [&](int j) { ldsm_t(wb[j], (va ^ ((j & 3) << 5)) + (3 + (j >> 3)) * REG + ((j >> 2) & 1) * 2048); };
        mbar_wait(barC, 0);
#pragma unroll
        for (int j = 0; j < NPRE; j++) load_wb(j);
        const uint32_t ho = pin(s0 + w * 16 + ((lane & 7) >> 1) * 64 + ((lane >> 3) & 1) * 32 + (lane & 1) * 16), oa = pin(sb + (lane & 7) * (UNIT + 16) + (lane >> 3) * 16);
        const uint32_t rd = pin((t >> 1) * 16 + w * 2 + (g >> 2));
        char* const pp = pin(X + X_PART + ((cta & 3) * 32 + rd) * 8192 + head * 128 + (g & 3) * 32 + (t & 1) * 16);
        const uint32_t ln = pin(lane);
        mbar_wait(bar0 + 8, 1);
        {
            uint32_t vf[8][4];
            float o2[2][4] = {};
#pragma unroll
            for (int j = 0; j < 8; j++) ldsm_t(vf[j], (va ^ ((j & 3) << 5)) + (j >> 2) * 2048);
#pragma unroll
            for (int j = 0; j < 8; j++) { const bool on = (ln >> 3) == (j >> 1); mma((j & 2) ? o2[j & 1] : o[j & 1], vf[j], on ? pb[0] : 0, on ? pb[1] : 0); }
            asm volatile("stmatrix.sync.aligned.m8n8.x2.trans.shared.b16 [%0], {%1,%2};" :: "r"(ho), "r"(pack2(o[0][0] + o2[0][0], o[0][2] + o2[0][2])), "r"(pack2(o[1][0] + o2[1][0], o[1][2] + o2[1][2])) : "memory");
        }
        bar_sync<B_RDY, NALL>();
        float y[4][4] = {};
        uint32_t ob[4][4];
#pragma unroll
        for (int i2 = 0; i2 < 4; i2++) ldsm(ob[i2], oa + i2 * 64);
        const float2 f = lds64(sb + SM_ML + 64 + (ln & 3) * 8);
        const unsigned half = (lds32u(sb + SM_MASK) >> rd & 1) * 4096;
#pragma unroll
        for (int j = NPRE; j < 16; j++) load_wb(j);
#pragma unroll
        for (int j = 0; j < 8; j++)
#pragma unroll
            for (int i = 0; i < 4; i++) mma(y[i], j < 4 ? wa[j * 4 + i] : wb[(j - 4) * 4 + i], ob[j >> 1][2 * (j & 1)], ob[j >> 1][2 * (j & 1) + 1]);
        uint32_t r[4];
#pragma unroll
        for (int i = 0; i < 4; i++) {
            const float lo = f.x * y[i][0] + f.y * y[i][1], hi = f.x * y[i][2] + f.y * y[i][3];
            r[i] = __float_as_uint(((ln & 1) ? hi : lo) + __shfl_xor_sync(~0u, (ln & 1) ? lo : hi, 1));
        }
        asm("min.u32 %0, %0, 0xFFFFFFFE;" : "+r"(r[0]));
        stg_b128(pp + half, make_uint4(r[0], r[1], r[2], r[3]));
    }
    const unsigned side = lds32u(sb + SM_SIDE);
    const char* const x1p = X + (rid & (XC - 1)) * 16384;
    if (rid < NF1) {
        uint32_t wg[4][4], wu[4][4];
        const char* const xp = pin(x1p + blk(X_X1, w >> 2, side) + (w & 3) * 1024 + lane * 16);
        float4 c1[2], sv[2];
#pragma unroll
        for (int h = 0; h < 2; h++) { sv[h] = lds128(sb + SM_MN + (w * 2 + h) * 512 + lane * 16); c1[h] = lds128(sb + SM_MN + 8192 + (w * 2 + h) * 512 + lane * 16); }
        const uint32_t po = pin(myscr + SC_F1 + g * 144 + t * 32), so = pin(t == (g >> 1) ? sb + SM_ST + g * 64 + w * 8 : myscr + 1792 + lane * 8), odd = pin(g & 1);
        const uint32_t wbar = sb + SM_BAR + (w >> 1) * 64 + 48;
        uint4 x0, x1;
        const bool early = go_first(wbar, 1);
        if (early) { spin(clock(), (7 - w) * XDW); x0 = ldg_rlx2x64(xp); x1 = ldg_rlx2x64(xp + 512); mbar_wait(wbar, 1); }
#pragma unroll
        for (int j = 0; j < 4; j++) {
            const uint32_t a = sb + 2 * REG + w * 2048 + (((lane & 7) >> 1) + (lane & 1) * 4 + j * 8 + (lane >> 4) * 32) * 32 + ((lch ^ (lane & 1)) << 4);
            ldsm_t(wg[j], a); ldsm_t(wu[j], a + 16384);
        }
        {
            float cg[4] = {}, cu[4] = {}, sg[4] = {}, su[4] = {};
#pragma unroll
            for (int j = 0; j < 4; j++) {
                const float4 a = c1[j & 1], b = sv[j & 1];
                const uint32_t a0 = __float_as_uint(j >> 1 ? a.z : a.x), a1 = __float_as_uint(j >> 1 ? a.w : a.y), b0 = __float_as_uint(j >> 1 ? b.z : b.x), b1 = __float_as_uint(j >> 1 ? b.w : b.y);
                mma(cg, wg[j], a0, a1); mma(cu, wu[j], a0, a1); mma(sg, wg[j], b0, b1); mma(su, wu[j], b0, b1);
            }
            const uint32_t d = s0 + REG + g * 144 + t * 32;
            sts128f(d, cg[0], cg[2], cu[0], cu[2]); sts128f(d + 16, cg[1], cg[3], cu[1], cu[3]);
            sts128f(d + 1152, sg[0], sg[2], su[0], su[2]); sts128f(d + 1168, sg[1], sg[3], su[1], su[3]);
            bar_arrive<B_PRE, NALL>();
        }
        if (!early) { mbar_wait(sb + SM_BG, 0); spin(clock(), (7 - w) * XDW); x0 = ldg_rlx2x64(xp); x1 = ldg_rlx2x64(xp + 512); }
        int n = 0;
        while (true) {
            const bool b0 = max(x0.x, x0.z) == SENT, b1 = max(x1.x, x1.z) == SENT;
            if (!__any_sync(~0u, b0 | b1)) break;
            if (b0) x0 = ldg_rlx2x64(xp);
            if (b1) x1 = ldg_rlx2x64(xp + 512);
            if (++n > SPIN_MAX) __trap();
        }
        float sm[4] = {}, q0[4] = {}, q1[4] = {}, ag[2][4] = {}, au[2][4] = {};
        {
            const uint32_t a0[4] = {x0.x, x0.y, x0.z, x0.w}, a1[4] = {x1.x, x1.y, x1.z, x1.w};
            mma(sm, a0, ONE2, ONE2); mma(q0, a0, x0.x, x0.z); mma(q1, a0, x0.y, x0.w);
            mma(sm, a1, ONE2, ONE2); mma(q0, a1, x1.x, x1.z); mma(q1, a1, x1.y, x1.w);
#pragma unroll
            for (int j = 0; j < 4; j++) {
                const uint4 xv = (j & 1) ? x1 : x0; const float4 a = c1[j & 1];
                const uint32_t h0 = mul2(j >> 1 ? xv.z : xv.x, __float_as_uint(j >> 1 ? a.z : a.x)), h1 = mul2(j >> 1 ? xv.w : xv.y, __float_as_uint(j >> 1 ? a.w : a.y));
                mma(ag[j & 1], wg[j], h0, h1); mma(au[j & 1], wu[j], h0, h1);
            }
        }
        sts64(so, sm[0] + sm[2], odd ? q0[1] + q1[3] : q0[0] + q1[2]);
        sts128f(po, ag[0][0] + ag[1][0], ag[0][2] + ag[1][2], au[0][0] + au[1][0], au[0][2] + au[1][2]);
        sts128f(po + 16, ag[0][1] + ag[1][1], ag[0][3] + ag[1][3], au[0][1] + au[1][1], au[0][3] + au[1][3]);
        bar_arrive<B_FIN, NALL>();
    } else if (rid >= DN0) {
        const int f = rid - DN0;
        uint32_t wd[12][4];
        const char* const hp0 = pin(X + blk(X_HM, 0, side) + w * 512 + lane * 16);
        const char* const hp1 = pin(X + blk(X_HM, 1, side) + w * 512 + lane * 16);
        auto hm = [&](int j) { return ldg_rlx128((j & 1 ? hp1 : hp0) + (j >> 1) * 16384); };
        __nv_bfloat16* const op = pin(P.out + ((tid >> 4) & 7) * DM + f * 16 + (tid & 15));
        const uint32_t po = pin(myscr + SC_DN + t * 160 + g * 16), pi = pin(scr + SC_DN + (w & 3) * 160 + (tid & 7) * 16 + (tid & 8) + ((tid >> 4) & 1) * 4), gi = pin(sb + SM_MN + tid * 2), first = pin(w < 4);
        uint4 hv[6]; int n = 0;
        auto first_poll = [&]() {
            spin(clock(), w * HDW);
#pragma unroll
            for (int j = 0; j < 6; j++) hv[j] = (j < 5 || w < 3) ? hm(j) : make_uint4(0, 0, 0, 0);
        };
        const bool early = go_first(sb + SM_BT, 0);
        if (early) { first_poll(); mbar_wait(sb + SM_BT, 0); }
#pragma unroll
        for (int j = 0; j < 12; j++)
            if (j < 10 || w < 3) ldsm_t(wd[j], sb + 2 * REG + 16384 + (w + (j >> 1) * 8) * 1024 + (j & 1) * 512 + (((lane >> 1) & 1) + (lane & 1) * 2 + (lane & 4) + (lane >> 4) * 8) * 32 + ((lch ^ ((lane >> 2) & 1)) << 4));
            else wd[j][0] = wd[j][1] = wd[j][2] = wd[j][3] = 0;
        if (!early) { mbar_wait(sb + SM_BG, 0); first_poll(); }
        while (true) {
            unsigned m[6];
#pragma unroll
            for (int j = 0; j < 6; j++) m[j] = max(max(hv[j].x, hv[j].y), max(hv[j].z, hv[j].w));
            if (__all_sync(~0u, max(max(max(m[0], m[1]), m[2]), max(max(m[3], m[4]), m[5])) != SENT)) break;
#pragma unroll
            for (int j = 0; j < 6; j++) if (m[j] == SENT) hv[j] = hm(j);
            if (++n > SPIN_MAX) __trap();
        }
        float d[4][4] = {};
#pragma unroll
        for (int j = 0; j < 6; j++) { mma(d[(2 * j) & 3], wd[2 * j], hv[j].x, hv[j].y); mma(d[(2 * j + 1) & 3], wd[2 * j + 1], hv[j].z, hv[j].w); }
        sts128f(po, (d[0][0] + d[1][0]) + (d[2][0] + d[3][0]), (d[0][1] + d[1][1]) + (d[2][1] + d[3][1]), (d[0][2] + d[1][2]) + (d[2][2] + d[3][2]), (d[0][3] + d[1][3]) + (d[2][3] + d[3][3]));
        if (!first) bar_arrive<B_DN, NTHR>();
        else {
            bar_sync<B_DN, NTHR>();
            float v[8];
#pragma unroll
            for (int i = 0; i < 8; i++) v[i] = lds32(pi + i * SCR);
            unsigned gw, res;
            asm volatile("ld.shared.u16 %0, [%1];" : "=r"(gw) : "r"(gi) : "memory"); asm volatile("ld.shared.u16 %0, [%1];" : "=r"(res) : "r"(gi + 256) : "memory");
            asm volatile("st.global.u16 [%0], %1;" :: "l"(op), "h"((unsigned short)add2(res, mul2(gw, pack2(((v[0] + v[1]) + (v[2] + v[3])) + ((v[4] + v[5]) + (v[6] + v[7])), 0.f)))) : "memory");
        }
    }
}

typedef CUresult (*EncodeFn)(CUtensorMap*, CUtensorMapDataType, cuuint32_t, void*, const cuuint64_t*, const cuuint64_t*, const cuuint32_t*,
                             const cuuint32_t*, CUtensorMapInterleave, CUtensorMapSwizzle, CUtensorMapL2promotion, CUtensorMapFloatOOBfill);

void make2d(EncodeFn enc, CUtensorMap* m, const void* p, int rows, int cols, int brows, int bcols, CUtensorMapSwizzle sw) {
    cuuint64_t dims[2] = {(cuuint64_t)cols, (cuuint64_t)rows}, strides[1] = {(cuuint64_t)cols * 2};
    cuuint32_t box[2] = {(cuuint32_t)bcols, (cuuint32_t)brows}, es[2] = {1, 1};
    enc(m, CU_TENSOR_MAP_DATA_TYPE_BFLOAT16, 2, (void*)p, dims, strides, box, es, CU_TENSOR_MAP_INTERLEAVE_NONE, sw,
        CU_TENSOR_MAP_L2_PROMOTION_L2_128B, CU_TENSOR_MAP_FLOAT_OOB_FILL_NONE);
}
void make5d(EncodeFn enc, CUtensorMap* m, const void* p, int cols, const unsigned (&n)[4], const unsigned (&s)[4], unsigned nb) {
    const cuuint64_t rs = (cuuint64_t)cols * 2;
    cuuint64_t dims[5] = {(cuuint64_t)cols, n[0], n[1], n[2], n[3]}, strides[4] = {rs * s[0], rs * s[1], rs * s[2], rs * s[3]};
    cuuint32_t box[5] = {16, n[0], n[1], n[2], nb}, es[5] = {1, 1, 1, 1, 1};
    enc(m, CU_TENSOR_MAP_DATA_TYPE_BFLOAT16, 5, (void*)p, dims, strides, box, es, CU_TENSOR_MAP_INTERLEAVE_NONE, CU_TENSOR_MAP_SWIZZLE_32B,
        CU_TENSOR_MAP_L2_PROMOTION_L2_128B, CU_TENSOR_MAP_FLOAT_OOB_FILL_NONE);
}
void makekv(EncodeFn enc, CUtensorMap* m, const void* p) {
    cuuint64_t dims[3] = {64, (cuuint64_t)NB * NH * SK, 2}, strides[2] = {256, 128};
    cuuint32_t box[3] = {64, 16, 2}, es[3] = {1, 1, 1};
    enc(m, CU_TENSOR_MAP_DATA_TYPE_BFLOAT16, 3, (void*)p, dims, strides, box, es, CU_TENSOR_MAP_INTERLEAVE_NONE, CU_TENSOR_MAP_SWIZZLE_128B,
        CU_TENSOR_MAP_L2_PROMOTION_NONE, CU_TENSOR_MAP_FLOAT_OOB_FILL_NONE);
}

}

extern "C" void kernel_launch(void* const* d_in, const int* in_sizes, int n_in, void* d_out, int out_size) {
    (void)in_sizes; (void)n_in; (void)out_size;
    static EncodeFn enc = nullptr;
    static void* raw = nullptr;
    if (!enc) {
        void* fn = nullptr; cudaDriverEntryPointQueryResult qr;
        cudaGetDriverEntryPoint("cuTensorMapEncodeTiled", &fn, cudaEnableDefault, &qr);
        enc = (EncodeFn)fn;
        cudaFuncSetAttribute(fused_kernel, cudaFuncAttributeMaxDynamicSharedMemorySize, SM_TOTAL);
        cudaGetSymbolAddress(&raw, g_raw);
    }
    Params P;
    makekv(enc, &P.k, d_in[1]);
    makekv(enc, &P.v, d_in[2]);
    make2d(enc, &P.wq, d_in[3], DM, NH * DH, 64, 32, CU_TENSOR_MAP_SWIZZLE_64B);
    make2d(enc, &P.wo, d_in[4], NH * DH, DM, 32, 64, CU_TENSOR_MAP_SWIZZLE_128B);
    make2d(enc, &P.wm, d_in[10], DM, 6 * DM, 256, 8, CU_TENSOR_MAP_SWIZZLE_NONE);
    make2d(enc, &P.wn, d_in[10], DM, 6 * DM, 256, 16, CU_TENSOR_MAP_SWIZZLE_32B);
    make5d(enc, &P.wg, d_in[6], FF, {4, 2, 4, 16}, {1, 16, 4, 32}, 4);
    make5d(enc, &P.wu, d_in[7], FF, {4, 2, 4, 16}, {1, 16, 4, 32}, 4);
    make5d(enc, &P.wd, d_in[8], DM, {8, 4, 1, 43}, {4, 1, 1, 32}, 43);
    P.out = (__nv_bfloat16*)d_out;
    typedef const __nv_bfloat16* W;
    fused_kernel<<<NCTA, NALL, SM_TOTAL>>>((W)d_in[0], (W)d_in[9], (W)d_in[1], (W)d_in[10], (W)d_in[3], (char*)(((size_t)raw + X_ALIGN - 1) & ~(size_t)(X_ALIGN - 1)), P);
}
```

```cpp
#include <cuda_runtime.h>
#include <cuda_bf16.h>
#include <cuda.h>
#include <stdint.h>

namespace {

constexpr int NB = 8, DM = 512, NH = 32, DH = 128, SK = 4096, WIN = 1024, FF = 1376;
constexpr int NCTA = 128, NTHR = 288, NALL = 320;
constexpr int NT = 16;
constexpr int NF1 = 86, DN0 = 96;
constexpr unsigned SENT = 0xFFFFFFFFu;
constexpr int SPIN_MAX = 1 << 20;

constexpr int PWIN0 = 12;
constexpr int PWIN = 16;
constexpr int PSW = 22;
constexpr int NTRK = 8;
constexpr int PFK = 2;
constexpr int QN = 7;
constexpr int TAU = 166;
constexpr int ANCH0 = 176;
constexpr int LEAD = 1600;
constexpr int PACE0 = 7000;
constexpr int PNAP = 200;
constexpr int WOA_ISSUE = 3;
constexpr int WO_GAP = 2;
constexpr int WOA_READ = 8;
constexpr int NPRE = 9;
constexpr int W0 = 850;
constexpr int WS = 180;
constexpr int WD0 = 1700;
constexpr int RT0 = 1700;
constexpr int HD0 = 1000;
constexpr int XDW = 30;
constexpr int HDW = 45;
constexpr int XC = 2;

constexpr int UNIT = 4096, REG = 8 * UNIT;
constexpr int SM_SCR = 6 * REG;
constexpr int SCR = 2048;
constexpr int SM_MN = SM_SCR + 8 * SCR;
constexpr int SM_SC = SM_MN + 8192;
constexpr int SM_BAR = SM_SC + 8192;
constexpr int SM_BM = SM_BAR + 512, SM_BT = SM_BM + 8, SM_BN = SM_BM + 16, SM_BG = SM_BM + 24;
constexpr int SM_AN = SM_BM + 32, SM_SIDE = SM_BM + 36, SM_TAG = SM_BM + 40, SM_MASK = SM_BM + 44;
constexpr int SM_ST = SM_BAR + 576;
constexpr int SM_ML = SM_ST + 512;
constexpr int SM_PR = SM_ML + 96;
constexpr int SM_TOTAL = SM_PR + 512;
constexpr int SC_M = 0, SC_Q = 256;
constexpr int SC_F1 = 0, SC_DN = 0, SC_RX = 1536;
constexpr int B_INIT = 0, B_ALL = 2, B_MOD = 3, B_WQ = 4, B_LAST = 5, B_RDY = 6, B_DN = 7, B_PRE = 8, B_FIN = 9, B_STG = 10, B_SIDE = 11, B_Q = 12, B_ML = 13;

constexpr unsigned HOME = 0xB3000;
constexpr int X_PART = 0;
constexpr int X_Q = 0x100000;
constexpr int X_M1 = 0x140000;
constexpr int X_X1 = 0x150000;
constexpr int X_HM = 0x160000;
constexpr int X_MOD = 0x170000;
constexpr int X_SIDE = 0x176000;
constexpr int X_EPOCH = 0x176400;
constexpr int X_READY = 0x176480;
constexpr int X_LAG = 0x178000;
constexpr int X_ANC = 0x158000;
constexpr int X_PRB = 0x180000;
constexpr int X_ALIGN = 0x200000;
static_assert(XC == 2, "one store writes all copies of x1");
__device__ uint4 g_raw[2 * X_ALIGN / 16];
__device__ __forceinline__ unsigned blk(unsigned base, unsigned k, unsigned s) { const unsigned o = base + k * 8192; return o + ((__popc(o & HOME) ^ s) & 1) * 4096; }

struct Params {
    CUtensorMap wm, wq, k, v, wn, wo, wg, wu, wd;
    __nv_bfloat16* out;
};

__device__ __forceinline__ int tile_key(int i) { return (i & 1) * 128 + (i & 2) * 32 + (i & 12) * 64; }

__device__ __forceinline__ uint32_t smem_u32(const void* p) { return (uint32_t)__cvta_generic_to_shared(p); }
__device__ __forceinline__ void mbar_init(uint32_t a, uint32_t c) { asm volatile("mbarrier.init.shared::cta.b64 [%0], %1;" :: "r"(a), "r"(c) : "memory"); }
__device__ __forceinline__ void mbar_expect(uint32_t a, uint32_t b) { asm volatile("mbarrier.arrive.expect_tx.shared::cta.b64 _, [%0], %1;" :: "r"(a), "r"(b) : "memory"); }
__device__ __forceinline__ void mbar_wait(uint32_t a, uint32_t par) {
    uint32_t ok; int n = 0;
    do {
        asm volatile("{\n.reg .pred p;\nmbarrier.try_wait.parity.shared::cta.b64 p, [%1], %2, 2000;\nselp.u32 %0, 1, 0, p;\n}" : "=r"(ok) : "r"(a), "r"(par) : "memory");
        if (++n > SPIN_MAX) __trap();
    } while (!ok);
}
__device__ __forceinline__ bool mbar_test(uint32_t a, uint32_t par) {
    uint32_t ok; asm volatile("{\n.reg .pred p;\nmbarrier.test_wait.parity.shared::cta.b64 p, [%1], %2;\nselp.u32 %0, 1, 0, p;\n}" : "=r"(ok) : "r"(a), "r"(par) : "memory"); return ok;
}
__device__ __forceinline__ void tma2d(uint32_t dst, const CUtensorMap* m, int x, int y, uint32_t bar) {
    asm volatile("cp.async.bulk.tensor.2d.shared::cluster.global.mbarrier::complete_tx::bytes [%0], [%1, {%3, %4}], [%2];"
                 :: "r"(dst), "l"(m), "r"(bar), "r"(x), "r"(y) : "memory");
}
__device__ __forceinline__ void tma5d(uint32_t dst, const CUtensorMap* m, int x, int y, uint32_t bar) {
    asm volatile("cp.async.bulk.tensor.5d.shared::cluster.global.mbarrier::complete_tx::bytes [%0], [%1, {%3, 0, 0, 0, %4}], [%2];"
                 :: "r"(dst), "l"(m), "r"(bar), "r"(x), "r"(y) : "memory");
}
__device__ __forceinline__ void tma_kv(uint32_t dst, const CUtensorMap* m, int row, uint32_t bar, uint64_t pol) {
    asm volatile("cp.async.bulk.tensor.3d.shared::cluster.global.mbarrier::complete_tx::bytes.L2::cache_hint [%0], [%1, {0, %3, 0}], [%2], %4;"
                 :: "r"(dst), "l"(m), "r"(bar), "r"(row), "l"(pol) : "memory");
}
__device__ __forceinline__ void pf_bulk(const void* p, uint32_t n) { asm volatile("cp.async.bulk.prefetch.L2.global [%0], %1;" :: "l"(p), "r"(n) : "memory"); }
__device__ __forceinline__ void pf_if(const void* p, unsigned i, unsigned n) { asm volatile("{\n.reg .pred p;\nsetp.lt.u32 p, %1, %2;\n@p prefetch.global.L2 [%0];\n}" :: "l"(p), "r"(i), "r"(n) : "memory"); }
__device__ __forceinline__ uint4 ldg_nc(const void* p) { uint4 v; asm volatile("ld.global.nc.v4.u32 {%0,%1,%2,%3}, [%4];" : "=r"(v.x), "=r"(v.y), "=r"(v.z), "=r"(v.w) : "l"(p)); return v; }
__device__ __forceinline__ bool elect() { uint32_t p; asm volatile("{\n.reg .pred p;\nelect.sync _|p, -1;\nselp.u32 %0, 1, 0, p;\n}" : "=r"(p)); return p; }
__device__ __forceinline__ void pf_map(const CUtensorMap* m) { asm volatile("prefetch.tensormap [%0];" :: "l"(m) : "memory"); }
__device__ __forceinline__ void ldsm(uint32_t (&r)[4], uint32_t a) {
    asm volatile("ldmatrix.sync.aligned.m8n8.x4.shared.b16 {%0,%1,%2,%3}, [%4];" : "=r"(r[0]), "=r"(r[1]), "=r"(r[2]), "=r"(r[3]) : "r"(a) : "memory");
}
__device__ __forceinline__ void ldsm_t(uint32_t (&r)[4], uint32_t a) {
    asm volatile("ldmatrix.sync.aligned.m8n8.x4.trans.shared.b16 {%0,%1,%2,%3}, [%4];" : "=r"(r[0]), "=r"(r[1]), "=r"(r[2]), "=r"(r[3]) : "r"(a) : "memory");
}
__device__ __forceinline__ void mma(float (&c)[4], uint32_t a0, uint32_t a1, uint32_t a2, uint32_t a3, uint32_t b0, uint32_t b1) {
    asm("mma.sync.aligned.m16n8k16.row.col.f32.bf16.bf16.f32 {%0,%1,%2,%3}, {%4,%5,%6,%7}, {%8,%9}, {%0,%1,%2,%3};"
        : "+f"(c[0]), "+f"(c[1]), "+f"(c[2]), "+f"(c[3]) : "r"(a0), "r"(a1), "r"(a2), "r"(a3), "r"(b0), "r"(b1));
}
__device__ __forceinline__ void mma(float (&c)[4], const uint32_t (&a)[4], uint32_t b0, uint32_t b1) { mma(c, a[0], a[1], a[2], a[3], b0, b1); }
__device__ __forceinline__ uint32_t pin(uint32_t v) { asm volatile("shfl.sync.bfly.b32 %0, %0, 0, 31, -1;" : "+r"(v)); return v; }
template <class T> __device__ __forceinline__ T* pin(T* p) { const size_t a = (size_t)p; return (T*)(pin((uint32_t)a) | (size_t)pin((uint32_t)(a >> 32)) << 32); }
__device__ __forceinline__ uint32_t movm(uint32_t a) { uint32_t r; asm volatile("movmatrix.sync.aligned.m8n8.trans.b16 %0, %1;" : "=r"(r) : "r"(a)); return r; }
__device__ __forceinline__ uint32_t pack2(float lo, float hi) { uint32_t r; asm("cvt.rn.bf16x2.f32 %0, %1, %2;" : "=r"(r) : "f"(hi), "f"(lo)); return r; }
__device__ __forceinline__ float blo(uint32_t w) { return __uint_as_float(w << 16); }
__device__ __forceinline__ float bhi(uint32_t w) { return __uint_as_float(w & 0xFFFF0000u); }
__device__ __forceinline__ float rbf(float x) { return blo(pack2(x, 0.f)); }
__device__ __forceinline__ uint32_t add2(uint32_t a, uint32_t b) { uint32_t r; asm("add.rn.bf16x2 %0, %1, %2;" : "=r"(r) : "r"(a), "r"(b)); return r; }
__device__ __forceinline__ uint32_t sub2(uint32_t a, uint32_t b) { uint32_t r; asm("sub.rn.bf16x2 %0, %1, %2;" : "=r"(r) : "r"(a), "r"(b)); return r; }
__device__ __forceinline__ uint32_t mul2(uint32_t a, uint32_t b) { uint32_t r; asm("mul.rn.bf16x2 %0, %1, %2;" : "=r"(r) : "r"(a), "r"(b)); return r; }
constexpr uint32_t ONE2 = 0x3F803F80u;
constexpr float LOG2E = 1.4426950408889634f, SCALE = 0.08838834764831845f;
__device__ __forceinline__ float ex2(float x) { float y; asm("ex2.approx.ftz.f32 %0, %1;" : "=f"(y) : "f"(x)); return y; }
__device__ __forceinline__ uint4 ldg_rlx128(const void* p) {
    uint4 v; asm volatile("ld.relaxed.gpu.global.v4.u32 {%0,%1,%2,%3}, [%4];" : "=r"(v.x), "=r"(v.y), "=r"(v.z), "=r"(v.w) : "l"(p) : "memory"); return v;
}
__device__ __forceinline__ uint4 ldg_rlx2x64(const void* p) {
    unsigned long long a, b; asm volatile("ld.relaxed.gpu.global.v2.u64 {%0,%1}, [%2];" : "=l"(a), "=l"(b) : "l"(p) : "memory");
    return make_uint4((unsigned)a, (unsigned)(a >> 32), (unsigned)b, (unsigned)(b >> 32));
}
__device__ __forceinline__ uint2 ldg_rlx64(const void* p) {
    unsigned long long a; asm volatile("ld.relaxed.gpu.global.u64 %0, [%1];" : "=l"(a) : "l"(p) : "memory"); return make_uint2((unsigned)a, (unsigned)(a >> 32));
}
__device__ __forceinline__ unsigned ldg_acq32(const void* p) { unsigned v; asm volatile("ld.acquire.gpu.global.u32 %0, [%1];" : "=r"(v) : "l"(p) : "memory"); return v; }
__device__ __forceinline__ void red_add(void* p, unsigned v) { asm volatile("red.relaxed.gpu.global.add.u32 [%0], %1;" :: "l"(p), "r"(v) : "memory"); }
__device__ __forceinline__ unsigned now_ns() { unsigned t; asm volatile("mov.u32 %0, %%globaltimer_lo;" : "=r"(t)); return t; }
__device__ __forceinline__ void nap(unsigned ns) { asm volatile("nanosleep.u32 %0;" :: "r"(ns)); }
__device__ __forceinline__ unsigned ldg_rlx32(const void* p) { unsigned v; asm volatile("ld.relaxed.gpu.global.u32 %0, [%1];" : "=r"(v) : "l"(p) : "memory"); return v; }
__device__ __forceinline__ void stg_rlx32(void* p, unsigned v) { asm volatile("st.relaxed.gpu.global.u32 [%0], %1;" :: "l"(p), "r"(v) : "memory"); }
__device__ __forceinline__ void stg_rlx16(void* p, unsigned v) { asm volatile("st.relaxed.gpu.global.u16 [%0], %1;" :: "l"(p), "h"((unsigned short)v) : "memory"); }
__device__ __forceinline__ uint4 ldg_b128(const void* p) {
    unsigned long long a, b; asm volatile("{\n.reg .b128 x;\nld.relaxed.gpu.global.b128 x, [%2];\nmov.b128 {%0,%1}, x;\n}" : "=l"(a), "=l"(b) : "l"(p) : "memory");
    return make_uint4((unsigned)a, (unsigned)(a >> 32), (unsigned)b, (unsigned)(b >> 32));
}
__device__ __forceinline__ void stg_b128(void* p, uint4 v) {
    asm volatile("{\n.reg .b128 x;\nmov.b128 x, {%1,%2};\nst.relaxed.gpu.global.b128 [%0], x;\n}" :: "l"(p), "l"(v.x | ((unsigned long long)v.y << 32)), "l"(v.z | ((unsigned long long)v.w << 32)) : "memory");
}
__device__ __forceinline__ int rowoff(int b, int c) { return ((c >> 6) * 2 + ((c >> 2) & 1)) * 512 + b * 64 + (c & 3) * 16 + ((c >> 3) & 1) * 8 + ((c >> 5) & 1) * 4 + ((c >> 4) & 1) * 2; }
__device__ __forceinline__ void stg_rlx64(void* p, unsigned lo, unsigned hi) {
    unsigned long long a = lo | ((unsigned long long)hi << 32); asm volatile("st.relaxed.gpu.global.u64 [%0], %1;" :: "l"(p), "l"(a) : "memory");
}
__device__ __forceinline__ void stg_rlx128(void* p, uint4 v) { asm volatile("st.relaxed.gpu.global.v4.u32 [%0], {%1,%2,%3,%4};" :: "l"(p), "r"(v.x), "r"(v.y), "r"(v.z), "r"(v.w) : "memory"); }
__device__ __forceinline__ void sts32u(uint32_t a, unsigned x) { asm volatile("st.volatile.shared.u32 [%0], %1;" :: "r"(a), "r"(x) : "memory"); }
__device__ __forceinline__ unsigned lds32u(uint32_t a) { unsigned v; asm volatile("ld.volatile.shared.u32 %0, [%1];" : "=r"(v) : "r"(a) : "memory"); return v; }
__device__ __forceinline__ void spin(unsigned c0, unsigned d) { if (d) while ((unsigned)clock() - c0 < d) {} }
__device__ __forceinline__ void fence_gpu() { asm volatile("fence.acq_rel.gpu;" ::: "memory"); }
template <int ID, int N> __device__ __forceinline__ void bar_sync() { asm volatile("bar.sync %0, %1;" :: "n"(ID), "n"(N) : "memory"); }
template <int ID, int N> __device__ __forceinline__ void bar_arrive() { asm volatile("bar.arrive %0, %1;" :: "n"(ID), "n"(N) : "memory"); }
__device__ __forceinline__ void sts64(uint32_t a, float x, float y) { asm volatile("st.shared.v2.f32 [%0], {%1,%2};" :: "r"(a), "f"(x), "f"(y) : "memory"); }
__device__ __forceinline__ void sts128(uint32_t a, uint4 v) { asm volatile("st.volatile.shared.v4.u32 [%0], {%1,%2,%3,%4};" :: "r"(a), "r"(v.x), "r"(v.y), "r"(v.z), "r"(v.w) : "memory"); }
__device__ __forceinline__ void sts128f(uint32_t a, float x, float y, float z, float w) { asm volatile("st.volatile.shared.v4.f32 [%0], {%1,%2,%3,%4};" :: "r"(a), "f"(x), "f"(y), "f"(z), "f"(w) : "memory"); }
__device__ __forceinline__ void sts32(uint32_t a, float x) { asm volatile("st.shared.f32 [%0], %1;" :: "r"(a), "f"(x) : "memory"); }
__device__ __forceinline__ float2 lds64(uint32_t a) { float2 v; asm volatile("ld.shared.v2.f32 {%0,%1}, [%2];" : "=f"(v.x), "=f"(v.y) : "r"(a) : "memory"); return v; }
__device__ __forceinline__ float lds32(uint32_t a) { float v; asm volatile("ld.shared.f32 %0, [%1];" : "=f"(v) : "r"(a) : "memory"); return v; }
__device__ __forceinline__ float4 lds128(uint32_t a) { float4 v; asm volatile("ld.shared.v4.f32 {%0,%1,%2,%3}, [%4];" : "=f"(v.x), "=f"(v.y), "=f"(v.z), "=f"(v.w) : "r"(a) : "memory"); return v; }
__device__ __forceinline__ float2 sum8(uint32_t a) {
    float2 v[8];
#pragma unroll
    for (int i = 0; i < 8; i++) v[i] = lds64(a + i * SCR);
    return make_float2(((v[0].x + v[1].x) + (v[2].x + v[3].x)) + ((v[4].x + v[5].x) + (v[6].x + v[7].x)),
                       ((v[0].y + v[1].y) + (v[2].y + v[3].y)) + ((v[4].y + v[5].y) + (v[6].y + v[7].y)));
}
template <int STRIDE> __device__ __forceinline__ float4 sum8x4(uint32_t a) {
    float4 v[8];
#pragma unroll
    for (int i = 0; i < 8; i++) v[i] = lds128(a + i * STRIDE);
    return make_float4(((v[0].x + v[1].x) + (v[2].x + v[3].x)) + ((v[4].x + v[5].x) + (v[6].x + v[7].x)), ((v[0].y + v[1].y) + (v[2].y + v[3].y)) + ((v[4].y + v[5].y) + (v[6].y + v[7].y)),
                       ((v[0].z + v[1].z) + (v[2].z + v[3].z)) + ((v[4].z + v[5].z) + (v[6].z + v[7].z)), ((v[0].w + v[1].w) + (v[2].w + v[3].w)) + ((v[4].w + v[5].w) + (v[6].w + v[7].w)));
}
__device__ __forceinline__ float rcp(float x) { float y; asm("rcp.approx.ftz.f32 %0, %1;" : "=f"(y) : "f"(x)); return y; }
__device__ __forceinline__ float sigmoid_f(float x) { return rcp(1.0f + ex2(x * -LOG2E)); }
__device__ __forceinline__ uint32_t silu2(uint32_t c) { const float a = blo(c), b = bhi(c); return pack2(a * sigmoid_f(a), b * sigmoid_f(b)); }
__device__ __forceinline__ void ln_consts(float mean, float var, uint32_t& mu2, float& rs) {
    mu2 = pack2(mean, mean);
    float sd; asm("sqrt.approx.ftz.f32 %0, %1;" : "=f"(sd) : "f"(rbf(rbf(var) + 1e-5f)));
    rs = rcp(rbf(sd));
}
__device__ __forceinline__ uint32_t ln_norm(uint32_t x2, uint32_t mu2, float rs) { const uint32_t d = sub2(x2, mu2); return pack2(blo(d) * rs, bhi(d) * rs); }

__global__ void __launch_bounds__(NALL, 1) fused_kernel(const __nv_bfloat16* const px, const __nv_bfloat16* const pc, const __nv_bfloat16* const pk, const __nv_bfloat16* const pwm,
                                                        const __nv_bfloat16* const pwq, char* const X, const __grid_constant__ Params P) {
    extern __shared__ __align__(1024) unsigned char smem[];
    const uint32_t sb = smem_u32(smem);
    const int tid = threadIdx.x, w = tid >> 5, lane = tid & 31, g = lane >> 2, t = lane & 3;
    const int cta = blockIdx.x, head = cta >> 2, bat = (cta & 3) * 2 + (w >> 2);
    const uint32_t s0 = sb + w * UNIT, s2 = s0 + 4 * REG;
    const uint32_t bar0 = sb + SM_BAR + w * 64;
    const uint32_t barC = bar0 + 32;
    const uint32_t scr = sb + SM_SCR, myscr = scr + w * SCR;
    pf_if((const char*)pwm + ((cta * 4 + (lane >> 3)) * (6 * DM * 2) + w * 1024 + (lane & 7) * 128), w, 5);
    pf_if((const char*)pk + (unsigned)(((((cta & 3) * 2 + (w & 1)) * NH + head) * SK + (SK - WIN - 48) + tile_key(2) + (w >> 1) * 16) * (DH * 2) + lane * 128), w - 6, PFK);
    const int rid = !(cta & 1) ? cta >> 1 : (cta >> 2) + (cta & 2 ? 64 : 96);
    const unsigned t_start = now_ns();
    uint64_t pol;
    asm volatile("createpolicy.fractional.L2::evict_first.b64 %0, 1.0;" : "=l"(pol));
    auto go_first = [&](uint32_t wbar, uint32_t par) {
        for (int n = 0;; n++) {
            if (__all_sync(~0u, mbar_test(wbar, par))) return false;
            if (__all_sync(~0u, mbar_test(sb + SM_BG, 0))) return true;
            if (n > SPIN_MAX * 4) __trap();
            nap(20);
        }
    };
    if (w == 9) {
        const uint32_t sl = sb + SM_PR + lane * 16;
        char* const pl = X + blk(X_PRB, cta >> 1, lane & 1) + (lane >> 1) * 256 + (cta & 1) * 128;
        {
            char* const ps = X + X_PRB + (cta >> 1) * 8192 + g * 256 + (cta & 1) * 128 + t * 16;
            sts32u(sl, 0);
#pragma unroll
            for (int i = 0; i < 4; i++) stg_rlx128(ps + i * 2048, make_uint4(1, 1, 1, 1));
            __syncwarp();
        }
        unsigned v; asm volatile("atom.relaxed.gpu.global.add.u32 %0, [%1], 1;" : "=r"(v) : "l"(pl) : "memory");
        unsigned tag = ldg_rlx32(X + X_EPOCH);
        if (lane == 0) pf_bulk(pwq + (size_t)cta * QN * 1024, QN * 2048);
        if (lane == 0) sts32u(sb + SM_AN, t_start + ANCH0);
        if (lane < 8) sts32u(sb + SM_BAR + lane * 64 + 56, 0);
        unsigned side;
        {
            int d, n = 0;
#pragma unroll 1
            for (int r = 0; r < 4; r++) {
                if (v == SENT) __trap();
                asm volatile("cp.async.cg.shared.global [%0], [%1], 16;" :: "r"(sl), "l"(pl) : "memory");
                unsigned m;
                do {
                    m = __ballot_sync(~0u, lds32u(sl));
                    d = __popc(m & 0xAAAAAAAAu) - __popc(m & 0x55555555u);
                    if (++n > SPIN_MAX) __trap();
                } while (abs(d) < 6 && m != ~0u);
                if (abs(d) >= 6) break;
                asm volatile("cp.async.wait_all;" ::: "memory");
                sts32u(sl, 0);
                asm volatile("atom.relaxed.gpu.global.add.u32 %0, [%1], 1;" : "=r"(v) : "l"(pl) : "memory");
            }
            side = d > 0;
            tag++;
            if (lane == 0) { sts32u(sb + SM_SIDE, side); sts32u(sb + SM_TAG, tag); }
            bar_arrive<B_SIDE, NTHR>();
        }
        asm volatile("cp.async.wait_all;" ::: "memory");
        while (now_ns() - t_start < PACE0) nap(200);
        for (int n = 0; n < SPIN_MAX; n++) {
            const uint32_t wb = sb + SM_BAR + (lane & 7) * 64;
            const unsigned seen = lds32u(wb + 56), u = seen + ((lane >> 3) & 1), t1 = now_ns();
            const unsigned more = seen && mbar_test(wb + (u < 6 ? u : (~u & 2) + (u & 1)) * 8, u < 6 ? 0 : ((u - 2) >> 2) & 1);
            const unsigned lo = __reduce_min_sync(~0u, seen), sum = __reduce_add_sync(~0u, lane < 8 ? seen + more : lane < 16 ? more : 0);
            if (lo == 30) break;
            if (lo && lane < 2) stg_rlx64(X + X_LAG + (cta >> 5) * 8192 + lane * 4096 + (cta & 31) * 128, t1 - sum * TAU, tag);
            uint2 a = make_uint2(0, 0);
            if (cta == 0) {
                uint2 u[4];
#pragma unroll
                for (int i = 0; i < 4; i++) u[i] = ldg_rlx64(X + blk(X_LAG, i, side) + lane * 128);
                const int s = __reduce_add_sync(~0u, (int)(u[0].x + u[1].x + u[2].x + u[3].x - 4 * t_start));
                if (__all_sync(~0u, (u[0].y == tag) & (u[1].y == tag) & (u[2].y == tag) & (u[3].y == tag)) && lane < 2) {
                    a = make_uint2(t_start + s / NCTA, tag);
                    stg_rlx64(X + X_ANC + lane * 4096, a.x, tag);
                }
            } else if (lane == 0) a = ldg_rlx64(X + blk(X_ANC, 0, side));
            if (lane == 0 && a.y == tag) sts32u(sb + SM_AN, a.x - LEAD);
            __syncwarp();
            nap(PNAP);
        }
        {
            bar_sync<B_ML, NTHR>();
            const float2 ml = lds64(sb + SM_ML + (lane & 7) * 8);
            float M = fmaxf(ml.x, __shfl_xor_sync(~0u, ml.x, 1)); M = fmaxf(M, __shfl_xor_sync(~0u, M, 2));
            const float e = ex2((ml.x - M) * LOG2E);
            float L = e * ml.y; L += __shfl_xor_sync(~0u, L, 1); L += __shfl_xor_sync(~0u, L, 2);
            if (lane < 8) sts32(sb + SM_ML + 64 + lane * 4, e * rcp(L));
        }
        bar_arrive<B_RDY, NALL>();
        bar_sync<B_STG, 64>();
        {
            const char* const pp = pin(X + blk(X_PART, cta, side) + lane * 16);
            char* const xo = pin(X + (lane >> 4) * 16384 + blk(X_X1, (cta >> 3) & 1, lane >> 3) + (cta & 7) * 512 + (cta >> 4) * 64 + (lane & 7) * 8);
            const float4 gx = lds128(scr + SC_RX + (lane & 7) * 16);
            const unsigned t0 = lds32u(sb + SM_AN) + 256 * TAU + RT0 + (cta & 7) * (TAU / 8);
            while ((int)(now_ns() - t0) < 0) nap(20);
            uint4 v[8]; int n = 0;
            float a[4];
#pragma unroll
            for (int j = 0; j < 8; j++) v[j] = ldg_b128(pp + j * 512);
            while (true) {
#define RSUM(f) (((__uint_as_float(v[0].f) + __uint_as_float(v[1].f)) + (__uint_as_float(v[2].f) + __uint_as_float(v[3].f))) + ((__uint_as_float(v[4].f) + __uint_as_float(v[5].f)) + (__uint_as_float(v[6].f) + __uint_as_float(v[7].f))))
                const bool ok = __all_sync(~0u, max(max(max(v[0].x, v[1].x), max(v[2].x, v[3].x)), max(max(v[4].x, v[5].x), max(v[6].x, v[7].x))) != SENT);
                a[0] = RSUM(x); a[1] = RSUM(y); a[2] = RSUM(z); a[3] = RSUM(w);
                asm volatile("" : "+f"(a[0]), "+f"(a[1]), "+f"(a[2]), "+f"(a[3]));
                if (ok) break;
#pragma unroll
                for (int j = 0; j < 8; j++) if (v[j].x == SENT) v[j] = ldg_b128(pp + j * 512);
                if (++n > SPIN_MAX) __trap();
            }
#pragma unroll
            for (int i = 0; i < 4; i++) a[i] += __shfl_xor_sync(~0u, a[i], 8);
#pragma unroll
            for (int i = 0; i < 4; i++) a[i] += __shfl_xor_sync(~0u, a[i], 16);
            stg_rlx64(xo, add2(__float_as_uint(gx.z), mul2(__float_as_uint(gx.x), pack2(a[0], a[1]))), add2(__float_as_uint(gx.w), mul2(__float_as_uint(gx.y), pack2(a[2], a[3]))));
        }
        if (rid >= DN0) {
            const unsigned c1 = clock();
            const int f = rid - DN0;
            const char* const rp = X + (rid & (XC - 1)) * 16384 + blk(X_X1, f >> 4, side) + (rowoff(g, f * 16 + t * 4) & 4092);
            unsigned r[4]; int n = 0;
            spin(c1, HD0 - 450);
            do {
#pragma unroll
                for (int i = 0; i < 4; i++) r[i] = ldg_rlx32(rp + i * 16);
                if (++n > SPIN_MAX) __trap();
            } while (max(max(r[0], r[1]), max(r[2], r[3])) == SENT);
            const unsigned sel = (f & 1) ? 0x7632 : 0x5410;
            sts64(sb + SM_MN + 256 + lane * 8, __uint_as_float(__byte_perm(r[0], r[1], sel)), __uint_as_float(__byte_perm(r[2], r[3], sel)));
            __syncwarp();
            spin(c1, HD0);
        }
        if (lane == 0) asm volatile("mbarrier.arrive.shared::cta.b64 _, [%0];" :: "r"(sb + SM_BG) : "memory");
    } else if (w == 8) {
        const int row0 = ((cta & 3) * 2 * NH + head) * SK + (SK - WIN);
        auto kv_unit = [&](int u) {
            const uint32_t b = sb + SM_BAR + (u & 7) * 64 + (u >> 3) * 8;
            mbar_expect(b, UNIT);
            tma_kv(sb + (u >> 3) * REG + (u & 7) * UNIT, (u & 8) ? &P.v : &P.k, row0 + ((u >> 2) & 1) * NH * SK + (u & 3) * 16 + tile_key(u >> 4), b, pol);
        };
        if (elect()) {
            mbar_init(sb + SM_BM, 1);
#pragma unroll
            for (int i = 0; i < 8; i++) mbar_init(sb + SM_BAR + i * 64 + 48, 1);
            asm volatile("fence.mbarrier_init.release.cluster;" ::: "memory");
            mbar_expect(sb + SM_BM, 512 * 16);
            tma2d(sb + 4 * REG, &P.wm, cta * 8, 0, sb + SM_BM); tma2d(sb + 4 * REG + 256 * 16, &P.wm, cta * 8, 256, sb + SM_BM);
#pragma unroll
            for (int i = 0; i < 8; i++) { const uint32_t b = sb + SM_BAR + i * 64 + 48; mbar_expect(b, UNIT); tma2d(sb + 5 * REG + i * UNIT, &P.wq, cta * 32, i * 64, b); }
            mbar_init(sb + SM_BN, 1); mbar_init(sb + SM_BT, 1); mbar_init(sb + SM_BG, 1);
#pragma unroll
            for (int i = 0; i < 48; i++) mbar_init(sb + SM_BAR + (i & 7) * 64 + (i >> 3) * 8, 1);
            asm volatile("fence.mbarrier_init.release.cluster;" ::: "memory");
        }
        __syncwarp();
        bar_arrive<B_INIT, NTHR>();
        {
            uint32_t mine = lane >= NTRK ? 0 : lane < 8 ? sb + SM_BAR + lane * 64 + 48 : sb + SM_BM;
            int next = 0, lim = 32, n = 0;
            while (next < 48) {
                const bool idle = lane < (next < PSW ? PWIN0 : PWIN) && (mine == 0 || mbar_test(mine, 0));
                const unsigned m = __ballot_sync(~0u, idle);
                const int u = next + __popc(m & ((1u << lane) - 1));
                if (idle) {
                    mine = 0;
                    if (u < lim) { kv_unit(u); mine = sb + SM_BAR + (u & 7) * 64 + (u >> 3) * 8; }
                }
                next = min(next + __popc(m), lim);
                if (next == lim) {
                    if (lim == 32) { bar_sync<B_MOD, NTHR>(); } else if (lim == 40) { bar_sync<B_WQ, NTHR>(); }
                    lim += 8;
                }
                if (!m) nap(30);
                if (++n > SPIN_MAX) __trap();
            }
        }
        if (lane < 5) pf_map(&P.wn + lane);
        float m[4][4] = {};
        auto late_mod = [&](uint32_t a, int h) {
            const int lrow = (lane & 7) + ((lane >> 4) << 3), lch = (lane >> 3) & 1;
            const uint32_t a0 = a + lrow * 32 + ((lch ^ ((lrow >> 2) & 1)) << 4);
            const uint32_t c0 = sb + SM_SC + h * 4096 + (lane & 7) * 128 + (((lane >> 3) ^ (lane & 7)) << 4);
#pragma unroll
            for (int j = 0; j < 8; j++) {
                uint32_t c[4], r[4], u[4];
                ldsm(c, (c0 + (j >> 1) * 1024) ^ ((j & 1) << 6)); ldsm_t(r, a0 + j * 1024); ldsm_t(u, a0 + j * 1024 + 512);
                mma(m[(j & 1) * 2], r, c[0], c[1]); mma(m[(j & 1) * 2 + 1], u, c[2], c[3]);
            }
        };
        if (rid < 96) {
#pragma unroll 1
            for (int h = 0; h < 2; h++) {
                if (lane == 0) { mbar_expect(sb + SM_BN, 8192); tma2d(sb + SM_MN, &P.wn, 2 * DM + rid * 16, h * 256, sb + SM_BN); }
                mbar_wait(sb + SM_BN, h);
                late_mod(sb + SM_MN, h);
                asm volatile("" :: "f"(m[0][0]), "f"(m[1][0]), "f"(m[2][0]), "f"(m[3][0]) : "memory");
                __syncwarp();
            }
#pragma unroll
            for (int e = 0; e < 4; e++) {
                float v = rbf((m[0][e] + m[1][e]) + (m[2][e] + m[3][e]));
                if (rid >= 64) v += 1.0f;
                stg_rlx16(X + X_MOD + (rid >> 5) * 8192 + rowoff(2 * t + (e & 1), (rid & 31) * 16 + g + (e >> 1) * 8), pack2(v, 0.f));
            }
        }
        {
            const unsigned side = lds32u(sb + SM_SIDE);
#pragma unroll
            for (int i = 0; i < 8; i++) stg_rlx128(X + blk(X_PART, cta, side) + i * 512 + lane * 16, make_uint4(SENT, SENT, SENT, SENT));
            if (lane == 0) stg_rlx32(X + X_SIDE + cta * 4, side);
        }
        bar_sync<B_Q, NTHR>();
        if (lane == 0) {
            const unsigned tag = lds32u(sb + SM_TAG);
            fence_gpu();
            red_add(X + X_READY, 1);
            int n = 0;
            while ((int)(ldg_acq32(X + X_READY) - tag * NCTA) < 0) { nap(1000); if (++n > SPIN_MAX) __trap(); }
            if (cta == 0) stg_rlx32(X + X_EPOCH, tag);
        }
        __syncwarp();
        {
            stg_rlx128(X + blk(X_Q, head >> 1, 0) + (head & 1) * 2048 + g * 256 + (cta & 3) * 64 + t * 16, make_uint4(0, 0, 0, 0));
            stg_rlx128(X + blk(X_Q, head >> 1, 1) + (head & 1) * 2048 + g * 256 + (cta & 3) * 64 + t * 16, make_uint4(0, 0, 0, 0));
            stg_rlx64(X + blk(X_M1, cta >> 5, lane >> 4) + (cta & 31) * 128 + (lane & 15) * 8, 0, 0);
            const int wt = (cta & 3) * 32 + lane;
            const unsigned mask = __ballot_sync(~0u, blk(X_PART, wt, ldg_rlx32(X + X_SIDE + wt * 4)) & 4096);
            if (lane == 0) sts32u(sb + SM_MASK, mask);
            if (lane < 8) {
                const int rb = cta >> 4, c = ((cta & 15) >> 1) * 64 + (cta & 1) * 4 + (lane >> 1) + (lane & 1) * 8;
                const uint2 ga = ldg_rlx64(X + X_MOD + rowoff(rb, c));
                const unsigned short* const xp = (const unsigned short*)px + rb * DM + c;
                sts128(scr + SC_RX + lane * 16, make_uint4(ga.x, ga.y, xp[0] | (xp[16] << 16), xp[32] | (xp[48] << 16)));
            }
            if (rid < NF1) {
#pragma unroll 1
                for (int i = 0; i < 4; i++) {
                    uint4 v[8];
#pragma unroll
                    for (int j = 0; j < 8; j++) v[j] = ldg_rlx128(X + X_MOD + 8192 + (i * 8 + j) * 512 + lane * 16);
#pragma unroll
                    for (int j = 0; j < 8; j++) sts128(sb + SM_MN + (i * 8 + j) * 512 + lane * 16, v[j]);
                }
            }
        }
        bar_arrive<B_RDY, NALL>();
        bar_arrive<B_STG, 64>();
        for (int n = 0; __any_sync(~0u, lds32u(sb + SM_BAR + (lane & 7) * 64 + 56) < 30); n++) { nap(100); if (n > SPIN_MAX) __trap(); }
        const unsigned t_ref = lds32u(sb + SM_AN) + 256 * TAU + (cta & 7) * (TAU / 8);
        auto until = [&](int x) { while ((int)(now_ns() - t_ref) < x) nap(20); };
        if (rid < NF1) {
            if (elect()) {
#pragma unroll
                for (int i = 0; i < 4; i++) mbar_expect(sb + SM_BAR + i * 64 + 48, 2 * UNIT);
#pragma unroll 1
                for (int i = 0; i < 4; i++) {
                    const uint32_t b = sb + SM_BAR + i * 64 + 48;
                    until(W0 + i * WS);
                    tma5d(sb + 2 * REG + i * UNIT, &P.wg, rid * 16, i * 4, b); tma5d(sb + 2 * REG + 16384 + i * UNIT, &P.wu, rid * 16, i * 4, b);
                }
            }
        } else if (rid >= DN0) {
            bar_sync<B_LAST, NTHR>();
            if (elect()) {
                mbar_expect(sb + SM_BN, 16384); mbar_expect(sb + SM_BT, FF * 32);
                until(WD0);
                tma5d(sb + 2 * REG + 16384, &P.wd, (rid - DN0) * 16, 0, sb + SM_BT);
                tma2d(sb + 2 * REG, &P.wn, 2 * DM + rid * 16, 0, sb + SM_BN); tma2d(sb + 2 * REG + 8192, &P.wn, 2 * DM + rid * 16, 256, sb + SM_BN);
            }
        }
        __syncwarp();
        if (rid >= DN0) {
            mbar_wait(sb + SM_BN, 0);
            late_mod(sb + 2 * REG, 0); late_mod(sb + 2 * REG + 8192, 1);
#pragma unroll
            for (int e = 0; e < 2; e++)
                sts32u(sb + SM_MN + g * 32 + e * 16 + t * 4, movm(pack2((m[0][2 * e] + m[1][2 * e]) + (m[2][2 * e] + m[3][2 * e]), (m[0][2 * e + 1] + m[1][2 * e + 1]) + (m[2][2 * e + 1] + m[3][2 * e + 1]))));
            bar_arrive<B_DN, NTHR>();
        }
    }
    if (w >= 8) {
        if (rid < NF1) {
            const int b = (tid - 256) >> 3, c = tid & 7;
            char* const ho = pin(X + X_HM + (rid >> 4) * 8192 + ((rid >> 1) & 7) * 512 + b * 64 + (rid & 1) * 32 + c * 4);
            const uint32_t pi = pin(scr + SC_F1 + c * 144 + b * 16), si = pin(sb + SM_ST + b * 64);
            bar_sync<B_PRE, NALL>();
            float4 C = sum8x4<UNIT>(sb + REG + c * 144 + b * 16), S = sum8x4<UNIT>(sb + REG + 1152 + c * 144 + b * 16);
            S.x *= -LOG2E; S.y *= -LOG2E; C.x *= LOG2E; C.y *= LOG2E;
            sts128f(sb + SM_PR + lane * 16, C.x, C.y, C.z, C.w); sts128f(sb + SM_PR + lane * 16, S.x, S.y, S.z, S.w);
            sts128(sb + SM_PR + lane * 16, make_uint4(pi, si, (uint32_t)(size_t)ho, (uint32_t)((size_t)ho >> 32)));
            bar_sync<B_FIN, NALL>();
            const float4 s0_ = lds128(si), s1_ = lds128(si + 16), s2_ = lds128(si + 32), s3_ = lds128(si + 48);
            const float4 p = sum8x4<SCR>(pi);
            const float mean = (((s0_.x + s0_.z) + (s1_.x + s1_.z)) + ((s2_.x + s2_.z) + (s3_.x + s3_.z))) * (1.0f / DM);
            const float sq = (((s0_.y + s0_.w) + (s1_.y + s1_.w)) + ((s2_.y + s2_.w) + (s3_.y + s3_.w))) * (1.0f / DM);
            float rs; asm("rsqrt.approx.ftz.f32 %0, %1;" : "=f"(rs) : "f"(fmaxf(sq - mean * mean, 0.f) + 1e-5f));
            const float e0 = rs * (mean * C.x - LOG2E * p.x) + S.x, e1 = rs * (mean * C.y - LOG2E * p.y) + S.y;
            const float u0 = rs * (p.z - mean * C.z) + S.z, u1 = rs * (p.w - mean * C.w) + S.w;
            const unsigned hw = pack2(rcp(1.0f + ex2(e0)) * u0, rcp(1.0f + ex2(e1)) * u1);
            stg_rlx32(ho, hw); stg_rlx32(ho + 4096, hw);
        }
        return;
    }
    const unsigned ce = (lane >> 3) * (DM * 2) + w * 128 + (lane & 7) * 16;
    const uint4 ca = ldg_nc((const char*)pc + ce), cb = ldg_nc((const char*)pc + ce + 4 * DM * 2);
    const uint4 xa = ldg_nc((const char*)px + w * (DM * 2) + lane * 16), xb = ldg_nc((const char*)px + w * (DM * 2) + lane * 16 + 512);
    const uint4 xc = ldg_nc((const char*)px + ce), xd = ldg_nc((const char*)px + ce + 4 * DM * 2);
    if (w >= 4) pf_map(&P.wm + (w & 3));
    char* const qout = X + blk(X_Q, head >> 1, tid >> 7) + (head & 1) * 2048 + ((tid >> 4) & 7) * 256 + (cta & 3) * 64 + (tid & 3) * 16 + ((tid >> 2) & 3) * 4;
    char* const mout = X + blk(X_M1, cta >> 5, w) + (cta & 31) * 128 + lane * 4;
    stg_rlx32(qout, 0);
    if (w < 2) stg_rlx32(mout, 0);
    uint32_t sc[8], xf[8];
    {
        const uint32_t a = (lane >> 3) * 128 + (((lane & 7) ^ (lane >> 3)) << 4), b = (lane & 7) * 128 + (((lane >> 3) ^ (lane & 7)) << 4);
        const uint32_t cs = sb + SM_SC + w * 1024;
        sts128(cs + a, make_uint4(silu2(ca.x), silu2(ca.y), silu2(ca.z), silu2(ca.w)));
        sts128(cs + 512 + (a ^ 64), make_uint4(silu2(cb.x), silu2(cb.y), silu2(cb.z), silu2(cb.w)));
        sts128(myscr + a, xc); sts128(myscr + 512 + (a ^ 64), xd);
        __syncwarp();
        ldsm(*(uint32_t(*)[4])&sc[0], cs + b); ldsm(*(uint32_t(*)[4])&sc[4], cs + (b ^ 64));
        ldsm(*(uint32_t(*)[4])&xf[0], myscr + b); ldsm(*(uint32_t(*)[4])&xf[4], myscr + (b ^ 64));
        __syncwarp();
    }
    {
        float v[16] = {blo(xa.x), bhi(xa.x), blo(xa.y), bhi(xa.y), blo(xa.z), bhi(xa.z), blo(xa.w), bhi(xa.w),
                       blo(xb.x), bhi(xb.x), blo(xb.y), bhi(xb.y), blo(xb.z), bhi(xb.z), blo(xb.w), bhi(xb.w)};
        float s = 0;
#pragma unroll
        for (int i = 0; i < 16; i++) s += v[i];
#pragma unroll
        for (int o = 16; o; o >>= 1) s += __shfl_xor_sync(~0u, s, o);
        s *= (1.0f / DM);
        float q2 = 0;
#pragma unroll
        for (int i = 0; i < 16; i++) q2 += (v[i] - s) * (v[i] - s);
#pragma unroll
        for (int o = 16; o; o >>= 1) q2 += __shfl_xor_sync(~0u, q2, o);
        uint32_t mu2; float rs; ln_consts(s, q2 * (1.0f / DM), mu2, rs);
        if (lane == 0) sts64(sb + SM_ST + w * 8, __uint_as_float(mu2), rs);
    }
    const int lrow = (lane & 7) + ((lane >> 4) << 3), lch = (lane >> 3) & 1;
    const uint32_t off64 = lrow * 64 + ((lch ^ ((lrow >> 1) & 3)) << 4);
    const uint32_t off128 = lrow * 128 + ((lch ^ (lane & 7)) << 4);
    bar_sync<B_INIT, NTHR>();
    mbar_wait(sb + SM_BM, 0);
    {
        float a[4] = {0, 0, 0, 0}, b[4] = {0, 0, 0, 0};
        uint32_t r[4], u[4];
        ldsm_t(r, sb + 4 * REG + (w * 64 + lane) * 16); ldsm_t(u, sb + 4 * REG + (w * 64 + 32 + lane) * 16);
        mma(a, sc[0], 0, sc[1], 0, r[0], r[1]); mma(b, sc[4], 0, sc[5], 0, u[0], u[1]);
        mma(a, sc[2], 0, sc[3], 0, r[2], r[3]); mma(b, sc[6], 0, sc[7], 0, u[2], u[3]);
        sts64(myscr + SC_M + lane * 8, a[0] + b[0], a[1] + b[1]);
    }
    bar_arrive<B_MOD, NTHR>();
    bar_sync<B_ALL, 256>();
    if (w < 2) {
        const float2 m = sum8(scr + SC_M + lane * 8);
        stg_rlx32(mout, ~pack2(m.x, m.y));
    }
    if (tid < 8 * XC) stg_rlx128(X + X_X1 + (cta * 8 * XC + tid) * 16, make_uint4(SENT, SENT, SENT, SENT));
    else if (tid >= 232) stg_rlx128(X + X_HM + (cta * 24 + tid - 232) * 16, make_uint4(SENT, SENT, SENT, SENT));
    {
        const float2 st = lds64(sb + SM_ST + g * 8);
#pragma unroll
        for (int i = 0; i < 8; i++) xf[i] = ln_norm(xf[i], __float_as_uint(st.x), st.y);
    }
    {
        unsigned sv[8], cv[8]; int n = 0;
        bar_sync<B_SIDE, NTHR>();
        const char* const mp = X + blk(X_M1, w >> 2, lds32u(sb + SM_SIDE)) + (w & 3) * 1024 + lane * 4;
        if (lane == 0) while (!ldg_rlx32(mp + 16384 + 7 * 128)) { nap(40); if (++n > SPIN_MAX) __trap(); }
        __syncwarp();
#pragma unroll
        for (int j = 0; j < 8; j++) { sv[j] = ldg_rlx32(mp + j * 128); cv[j] = ldg_rlx32(mp + 16384 + j * 128); }
        while (true) {
            unsigned m = ~0u;
#pragma unroll
            for (int j = 0; j < 8; j++) m = min(m, min(sv[j], cv[j]));
            if (__all_sync(~0u, m)) break;
#pragma unroll
            for (int j = 0; j < 8; j++) { if (!sv[j]) sv[j] = ldg_rlx32(mp + j * 128); if (!cv[j]) cv[j] = ldg_rlx32(mp + 16384 + j * 128); }
            if (++n > SPIN_MAX) __trap();
        }
#pragma unroll
        for (int j = 0; j < 8; j++) xf[j] = add2(mul2(xf[j], add2(~cv[j], ONE2)), ~sv[j]);
        mbar_wait(bar0 + 48, 0);
        float acc[4][4] = {};
#pragma unroll
        for (int j = 0; j < 4; j++) {
            uint32_t r[4], u[4];
            ldsm_t(r, s2 + REG + j * 1024 + off64); ldsm_t(u, s2 + REG + j * 1024 + (off64 ^ 32));
            mma(acc[0], xf[2 * j], 0, xf[2 * j + 1], 0, r[0], r[2]); mma(acc[1], xf[2 * j], 0, xf[2 * j + 1], 0, r[1], r[3]);
            mma(acc[2], xf[2 * j], 0, xf[2 * j + 1], 0, u[0], u[2]); mma(acc[3], xf[2 * j], 0, xf[2 * j + 1], 0, u[1], u[3]);
        }
#pragma unroll
        for (int n2 = 0; n2 < 4; n2++) sts64(myscr + SC_Q + g * 160 + n2 * 32 + t * 8, acc[n2][0], acc[n2][1]);
    }
    bar_arrive<B_WQ, NTHR>();
    bar_sync<B_ALL, 256>();
    {
        const float2 s = sum8(scr + SC_Q + ((tid >> 4) & 7) * 160 + (tid & 15) * 8);
        stg_rlx32(qout, ~pack2(s.x, s.y));
    }
    uint32_t q[16];
    {
        int n = 0;
        const char* const qp = X + blk(X_Q, head >> 1, lds32u(sb + SM_SIDE)) + (head & 1) * 2048 + bat * 256 + t * 16;
        uint4 v[4];
#pragma unroll
        for (int j = 0; j < 4; j++) v[j] = ldg_rlx128(qp + j * 64);
        while (true) {
            bool bad[4];
#pragma unroll
            for (int j = 0; j < 4; j++) bad[j] = !min(min(v[j].x, v[j].y), min(v[j].z, v[j].w));
            if (!__any_sync(~0u, bad[0] | bad[1] | bad[2] | bad[3])) break;
#pragma unroll
            for (int j = 0; j < 4; j++) if (bad[j]) v[j] = ldg_rlx128(qp + j * 64);
            if (++n > SPIN_MAX) __trap();
        }
#pragma unroll
        for (int j = 0; j < 4; j++) { q[4 * j] = ~v[j].x; q[4 * j + 1] = ~v[j].y; q[4 * j + 2] = ~v[j].z; q[4 * j + 3] = ~v[j].w; }
    }
    bar_arrive<B_Q, NTHR>();

    float o[2][4] = {};
    float mrun = -3.0e38f, lrun = 0.f;
    uint32_t wa[16][4], pb[2];
#pragma unroll
    for (int i = 0; i < 16; i++) wa[i][0] = wa[i][1] = wa[i][2] = wa[i][3] = 0;
    const uint32_t offk = (lane & 15) * 128 + (((lane >> 4) ^ (lane & 7)) << 4);
    float p0, p1;
    auto scores = [&](uint32_t a0) {
        uint32_t kf[8][4];
#pragma unroll
        for (int j = 0; j < 8; j++) ldsm(kf[j], ((a0 + offk) ^ ((j & 3) << 5)) + (j >> 2) * 2048);
        float sa[4] = {0, 0, 0, 0}, sb2[4] = {0, 0, 0, 0};
#pragma unroll
        for (int j = 0; j < 8; j += 2) { mma(sa, kf[j], q[2 * j], q[2 * j + 1]); mma(sb2, kf[j + 1], q[2 * j + 2], q[2 * j + 3]); }
        uint32_t u = pack2(sa[0] + sb2[0], sa[2] + sb2[2]);
        u = pack2(blo(u) * SCALE, bhi(u) * SCALE);
        const float z0 = blo(u), z1 = bhi(u);
        float mx = fmaxf(z0, z1);
        mx = fmaxf(mx, __shfl_xor_sync(~0u, mx, 4)); mx = fmaxf(mx, __shfl_xor_sync(~0u, mx, 8)); mx = fmaxf(mx, __shfl_xor_sync(~0u, mx, 16));
        mx = fmaxf(mx, mrun);
        const float f = ex2((mrun - mx) * LOG2E);
        p0 = ex2((z0 - mx) * LOG2E); p1 = ex2((z1 - mx) * LOG2E);
        mrun = mx; lrun = lrun * f + (p0 + p1);
#pragma unroll
        for (int j = 0; j < 4; j++) { o[0][j] *= f; o[1][j] *= f; }
    };
    const int kvrow = (bat * NH + head) * SK + (SK - WIN) + (w & 3) * 16;
    const int wofs = (w * 8 + (cta & 7)) * TAU / 8;
    auto request = [&](int u) {
        sts32u(bar0 + 56, u - 1);
        while ((int)(now_ns() - lds32u(sb + SM_AN) - u * 8 * TAU - wofs) < 0) nap(20);
        const int sl = (~u & 2) + (u & 1);
        mbar_expect(bar0 + sl * 8, UNIT); tma_kv(s0 + sl * REG, &P.k + (u & 1), kvrow + tile_key(u >> 1), bar0 + sl * 8, pol);
    };
#pragma unroll 1
    for (int it = 0; it < NT - 1; it++) {
        const int si = it < 3 ? it : (it + 1) & 1;
        const uint32_t bar = bar0 + si * 16, a0 = s0 + si * 2 * REG;
        const uint32_t par = it < 3 ? 0 : ((it - 1) >> 1) & 1;
        const bool refill = lane == 0 && it >= 2;
        mbar_wait(bar, par);
        if (refill) {
            request(2 * it + 2);
            const int e = it - (it > WOA_READ ? WOA_READ + 1 : WOA_ISSUE);
            if (e == 0) mbar_expect(barC, 2 * UNIT);
            if (e == 0 || e == WO_GAP) tma2d(s2 + (e ? REG : 0), &P.wo, w * 64, head * 128 + (it > WOA_READ ? 64 : 0) + (e ? 32 : 0), barC);
        }
        __syncwarp();
        if (it == WOA_READ) {
            mbar_wait(barC, 1);
#pragma unroll
            for (int j = 0; j < 16; j++) ldsm_t(wa[j], s2 + (j >> 3) * REG + ((j >> 2) & 1) * 2048 + (off128 ^ ((j & 3) << 5)));
        }
        scores(a0);
        pb[0] = movm(pack2(p0, p0)); pb[1] = movm(pack2(p1, p1));
        mbar_wait(bar + 8, par);
        if (refill) request(2 * it + 3);
        __syncwarp();
        uint32_t vf[8][4];
#pragma unroll
        for (int j = 0; j < 8; j++) ldsm_t(vf[j], ((a0 + off128) ^ ((j & 3) << 5)) + (j >> 2) * 2048 + REG);
#pragma unroll
        for (int j = 0; j < 8; j++) { const bool on = (g >> 1) == (j >> 1); mma(o[j & 1], vf[j], on ? pb[0] : 0, on ? pb[1] : 0); }
    }
    {
        uint32_t wb[16][4];
        mbar_wait(bar0, 1);
        if (rid >= DN0) bar_arrive<B_LAST, NTHR>();
        scores(s0);
        lrun += __shfl_xor_sync(~0u, lrun, 4); lrun += __shfl_xor_sync(~0u, lrun, 8); lrun += __shfl_xor_sync(~0u, lrun, 16);
        if (lane == 0) sts64(sb + SM_ML + w * 8, mrun, lrun);
        bar_arrive<B_ML, NTHR>();
        pb[0] = movm(pack2(p0, p0)); pb[1] = movm(pack2(p1, p1));
        const uint32_t va = pin(s0 + REG + off128);
        auto load_wb = [&](int j) { ldsm_t(wb[j], (va ^ ((j & 3) << 5)) + (3 + (j >> 3)) * REG + ((j >> 2) & 1) * 2048); };
        mbar_wait(barC, 0);
#pragma unroll
        for (int j = 0; j < NPRE; j++) load_wb(j);
        const uint32_t ho = pin(s0 + w * 16 + ((lane & 7) >> 1) * 64 + ((lane >> 3) & 1) * 32 + (lane & 1) * 16), oa = pin(sb + (lane & 7) * (UNIT + 16) + (lane >> 3) * 16);
        const uint32_t rd = pin((t >> 1) * 16 + w * 2 + (g >> 2));
        char* const pp = pin(X + X_PART + ((cta & 3) * 32 + rd) * 8192 + head * 128 + (g & 3) * 32 + (t & 1) * 16);
        const uint32_t ln = pin(lane);
        mbar_wait(bar0 + 8, 1);
        {
            uint32_t vf[8][4];
            float o2[2][4] = {};
#pragma unroll
            for (int j = 0; j < 8; j++) ldsm_t(vf[j], (va ^ ((j & 3) << 5)) + (j >> 2) * 2048);
#pragma unroll
            for (int j = 0; j < 8; j++) { const bool on = (ln >> 3) == (j >> 1); mma((j & 2) ? o2[j & 1] : o[j & 1], vf[j], on ? pb[0] : 0, on ? pb[1] : 0); }
            asm volatile("stmatrix.sync.aligned.m8n8.x2.trans.shared.b16 [%0], {%1,%2};" :: "r"(ho), "r"(pack2(o[0][0] + o2[0][0], o[0][2] + o2[0][2])), "r"(pack2(o[1][0] + o2[1][0], o[1][2] + o2[1][2])) : "memory");
        }
        bar_sync<B_RDY, NALL>();
        float y[4][4] = {};
        uint32_t ob[4][4];
#pragma unroll
        for (int i2 = 0; i2 < 4; i2++) ldsm(ob[i2], oa + i2 * 64);
        const float2 f = lds64(sb + SM_ML + 64 + (ln & 3) * 8);
        const unsigned half = (lds32u(sb + SM_MASK) >> rd & 1) * 4096;
#pragma unroll
        for (int j = NPRE; j < 16; j++) load_wb(j);
#pragma unroll
        for (int j = 0; j < 8; j++)
#pragma unroll
            for (int i = 0; i < 4; i++) mma(y[i], j < 4 ? wa[j * 4 + i] : wb[(j - 4) * 4 + i], ob[j >> 1][2 * (j & 1)], ob[j >> 1][2 * (j & 1) + 1]);
        uint32_t r[4];
#pragma unroll
        for (int i = 0; i < 4; i++) {
            const float lo = f.x * y[i][0] + f.y * y[i][1], hi = f.x * y[i][2] + f.y * y[i][3];
            r[i] = __float_as_uint(((ln & 1) ? hi : lo) + __shfl_xor_sync(~0u, (ln & 1) ? lo : hi, 1));
        }
        asm("min.u32 %0, %0, 0xFFFFFFFE;" : "+r"(r[0]));
        stg_b128(pp + half, make_uint4(r[0], r[1], r[2], r[3]));
    }
    const unsigned side = lds32u(sb + SM_SIDE);
    const char* const x1p = X + (rid & (XC - 1)) * 16384;
    if (rid < NF1) {
        uint32_t wg[4][4], wu[4][4];
        const char* const xp = pin(x1p + blk(X_X1, w >> 2, side) + (w & 3) * 1024 + lane * 16);
        float4 c1[2], sv[2];
#pragma unroll
        for (int h = 0; h < 2; h++) { sv[h] = lds128(sb + SM_MN + (w * 2 + h) * 512 + lane * 16); c1[h] = lds128(sb + SM_MN + 8192 + (w * 2 + h) * 512 + lane * 16); }
        const uint32_t po = pin(myscr + SC_F1 + g * 144 + t * 32), so = pin(t == (g >> 1) ? sb + SM_ST + g * 64 + w * 8 : myscr + 1792 + lane * 8), odd = pin(g & 1);
        const uint32_t wbar = sb + SM_BAR + (w >> 1) * 64 + 48;
        uint4 x0, x1;
        const bool early = go_first(wbar, 1);
        if (early) { spin(clock(), (7 - w) * XDW); x0 = ldg_rlx2x64(xp); x1 = ldg_rlx2x64(xp + 512); mbar_wait(wbar, 1); }
#pragma unroll
        for (int j = 0; j < 4; j++) {
            const uint32_t a = sb + 2 * REG + w * 2048 + (((lane & 7) >> 1) + (lane & 1) * 4 + j * 8 + (lane >> 4) * 32) * 32 + ((lch ^ (lane & 1)) << 4);
            ldsm_t(wg[j], a); ldsm_t(wu[j], a + 16384);
        }
        {
            float cg[4] = {}, cu[4] = {}, sg[4] = {}, su[4] = {};
#pragma unroll
            for (int j = 0; j < 4; j++) {
                const float4 a = c1[j & 1], b = sv[j & 1];
                const uint32_t a0 = __float_as_uint(j >> 1 ? a.z : a.x), a1 = __float_as_uint(j >> 1 ? a.w : a.y), b0 = __float_as_uint(j >> 1 ? b.z : b.x), b1 = __float_as_uint(j >> 1 ? b.w : b.y);
                mma(cg, wg[j], a0, a1); mma(cu, wu[j], a0, a1); mma(sg, wg[j], b0, b1); mma(su, wu[j], b0, b1);
            }
            const uint32_t d = s0 + REG + g * 144 + t * 32;
            sts128f(d, cg[0], cg[2], cu[0], cu[2]); sts128f(d + 16, cg[1], cg[3], cu[1], cu[3]);
            sts128f(d + 1152, sg[0], sg[2], su[0], su[2]); sts128f(d + 1168, sg[1], sg[3], su[1], su[3]);
            bar_arrive<B_PRE, NALL>();
        }
        if (!early) { mbar_wait(sb + SM_BG, 0); spin(clock(), (7 - w) * XDW); x0 = ldg_rlx2x64(xp); x1 = ldg_rlx2x64(xp + 512); }
        int n = 0;
        while (true) {
            const bool b0 = max(x0.x, x0.z) == SENT, b1 = max(x1.x, x1.z) == SENT;
            if (!__any_sync(~0u, b0 | b1)) break;
            if (b0) x0 = ldg_rlx2x64(xp);
            if (b1) x1 = ldg_rlx2x64(xp + 512);
            if (++n > SPIN_MAX) __trap();
        }
        float sm[4] = {}, q0[4] = {}, q1[4] = {}, ag[2][4] = {}, au[2][4] = {};
        {
            const uint32_t a0[4] = {x0.x, x0.y, x0.z, x0.w}, a1[4] = {x1.x, x1.y, x1.z, x1.w};
            mma(sm, a0, ONE2, ONE2); mma(q0, a0, x0.x, x0.z); mma(q1, a0, x0.y, x0.w);
            mma(sm, a1, ONE2, ONE2); mma(q0, a1, x1.x, x1.z); mma(q1, a1, x1.y, x1.w);
#pragma unroll
            for (int j = 0; j < 4; j++) {
                const uint4 xv = (j & 1) ? x1 : x0; const float4 a = c1[j & 1];
                const uint32_t h0 = mul2(j >> 1 ? xv.z : xv.x, __float_as_uint(j >> 1 ? a.z : a.x)), h1 = mul2(j >> 1 ? xv.w : xv.y, __float_as_uint(j >> 1 ? a.w : a.y));
                mma(ag[j & 1], wg[j], h0, h1); mma(au[j & 1], wu[j], h0, h1);
            }
        }
        sts64(so, sm[0] + sm[2], odd ? q0[1] + q1[3] : q0[0] + q1[2]);
        sts128f(po, ag[0][0] + ag[1][0], ag[0][2] + ag[1][2], au[0][0] + au[1][0], au[0][2] + au[1][2]);
        sts128f(po + 16, ag[0][1] + ag[1][1], ag[0][3] + ag[1][3], au[0][1] + au[1][1], au[0][3] + au[1][3]);
        bar_arrive<B_FIN, NALL>();
    } else if (rid >= DN0) {
        const int f = rid - DN0;
        uint32_t wd[12][4];
        const char* const hp0 = pin(X + blk(X_HM, 0, side) + w * 512 + lane * 16);
        const char* const hp1 = pin(X + blk(X_HM, 1, side) + w * 512 + lane * 16);
        auto hm = [&](int j) { return ldg_rlx128((j & 1 ? hp1 : hp0) + (j >> 1) * 16384); };
        __nv_bfloat16* const op = pin(P.out + ((tid >> 4) & 7) * DM + f * 16 + (tid & 15));
        const uint32_t po = pin(myscr + SC_DN + t * 160 + g * 16), pi = pin(scr + SC_DN + (w & 3) * 160 + (tid & 7) * 16 + (tid & 8) + ((tid >> 4) & 1) * 4), gi = pin(sb + SM_MN + tid * 2), first = pin(w < 4);
        uint4 hv[6]; int n = 0;
        auto first_poll = [&]() {
            spin(clock(), w * HDW);
#pragma unroll
            for (int j = 0; j < 6; j++) hv[j] = (j < 5 || w < 3) ? hm(j) : make_uint4(0, 0, 0, 0);
        };
        const bool early = go_first(sb + SM_BT, 0);
        if (early) { first_poll(); mbar_wait(sb + SM_BT, 0); }
#pragma unroll
        for (int j = 0; j < 12; j++)
            if (j < 10 || w < 3) ldsm_t(wd[j], sb + 2 * REG + 16384 + (w + (j >> 1) * 8) * 1024 + (j & 1) * 512 + (((lane >> 1) & 1) + (lane & 1) * 2 + (lane & 4) + (lane >> 4) * 8) * 32 + ((lch ^ ((lane >> 2) & 1)) << 4));
            else wd[j][0] = wd[j][1] = wd[j][2] = wd[j][3] = 0;
        if (!early) { mbar_wait(sb + SM_BG, 0); first_poll(); }
        while (true) {
            unsigned m[6];
#pragma unroll
            for (int j = 0; j < 6; j++) m[j] = max(max(hv[j].x, hv[j].y), max(hv[j].z, hv[j].w));
            if (__all_sync(~0u, max(max(max(m[0], m[1]), m[2]), max(max(m[3], m[4]), m[5])) != SENT)) break;
#pragma unroll
            for (int j = 0; j < 6; j++) if (m[j] == SENT) hv[j] = hm(j);
            if (++n > SPIN_MAX) __trap();
        }
        float d[4][4] = {};
#pragma unroll
        for (int j = 0; j < 6; j++) { mma(d[(2 * j) & 3], wd[2 * j], hv[j].x, hv[j].y); mma(d[(2 * j + 1) & 3], wd[2 * j + 1], hv[j].z, hv[j].w); }
        sts128f(po, (d[0][0] + d[1][0]) + (d[2][0] + d[3][0]), (d[0][1] + d[1][1]) + (d[2][1] + d[3][1]), (d[0][2] + d[1][2]) + (d[2][2] + d[3][2]), (d[0][3] + d[1][3]) + (d[2][3] + d[3][3]));
        if (!first) bar_arrive<B_DN, NTHR>();
        else {
            bar_sync<B_DN, NTHR>();
            float v[8];
#pragma unroll
            for (int i = 0; i < 8; i++) v[i] = lds32(pi + i * SCR);
            unsigned gw, res;
            asm volatile("ld.shared.u16 %0, [%1];" : "=r"(gw) : "r"(gi) : "memory"); asm volatile("ld.shared.u16 %0, [%1];" : "=r"(res) : "r"(gi + 256) : "memory");
            asm volatile("st.global.u16 [%0], %1;" :: "l"(op), "h"((unsigned short)add2(res, mul2(gw, pack2(((v[0] + v[1]) + (v[2] + v[3])) + ((v[4] + v[5]) + (v[6] + v[7])), 0.f)))) : "memory");
        }
    }
}

typedef CUresult (*EncodeFn)(CUtensorMap*, CUtensorMapDataType, cuuint32_t, void*, const cuuint64_t*, const cuuint64_t*, const cuuint32_t*,
                             const cuuint32_t*, CUtensorMapInterleave, CUtensorMapSwizzle, CUtensorMapL2promotion, CUtensorMapFloatOOBfill);

void make2d(EncodeFn enc, CUtensorMap* m, const void* p, int rows, int cols, int brows, int bcols, CUtensorMapSwizzle sw) {
    cuuint64_t dims[2] = {(cuuint64_t)cols, (cuuint64_t)rows}, strides[1] = {(cuuint64_t)cols * 2};
    cuuint32_t box[2] = {(cuuint32_t)bcols, (cuuint32_t)brows}, es[2] = {1, 1};
    enc(m, CU_TENSOR_MAP_DATA_TYPE_BFLOAT16, 2, (void*)p, dims, strides, box, es, CU_TENSOR_MAP_INTERLEAVE_NONE, sw,
        CU_TENSOR_MAP_L2_PROMOTION_L2_128B, CU_TENSOR_MAP_FLOAT_OOB_FILL_NONE);
}
void make5d(EncodeFn enc, CUtensorMap* m, const void* p, int cols, const unsigned (&n)[4], const unsigned (&s)[4], unsigned nb) {
    const cuuint64_t rs = (cuuint64_t)cols * 2;
    cuuint64_t dims[5] = {(cuuint64_t)cols, n[0], n[1], n[2], n[3]}, strides[4] = {rs * s[0], rs * s[1], rs * s[2], rs * s[3]};
    cuuint32_t box[5] = {16, n[0], n[1], n[2], nb}, es[5] = {1, 1, 1, 1, 1};
    enc(m, CU_TENSOR_MAP_DATA_TYPE_BFLOAT16, 5, (void*)p, dims, strides, box, es, CU_TENSOR_MAP_INTERLEAVE_NONE, CU_TENSOR_MAP_SWIZZLE_32B,
        CU_TENSOR_MAP_L2_PROMOTION_L2_128B, CU_TENSOR_MAP_FLOAT_OOB_FILL_NONE);
}
void makekv(EncodeFn enc, CUtensorMap* m, const void* p) {
    cuuint64_t dims[3] = {64, (cuuint64_t)NB * NH * SK, 2}, strides[2] = {256, 128};
    cuuint32_t box[3] = {64, 16, 2}, es[3] = {1, 1, 1};
    enc(m, CU_TENSOR_MAP_DATA_TYPE_BFLOAT16, 3, (void*)p, dims, strides, box, es, CU_TENSOR_MAP_INTERLEAVE_NONE, CU_TENSOR_MAP_SWIZZLE_128B,
        CU_TENSOR_MAP_L2_PROMOTION_NONE, CU_TENSOR_MAP_FLOAT_OOB_FILL_NONE);
}

}

extern "C" void kernel_launch(void* const* d_in, const int* in_sizes, int n_in, void* d_out, int out_size) {
    (void)in_sizes; (void)n_in; (void)out_size;
    static EncodeFn enc = nullptr;
    static void* raw = nullptr;
    if (!enc) {
        void* fn = nullptr; cudaDriverEntryPointQueryResult qr;
        cudaGetDriverEntryPoint("cuTensorMapEncodeTiled", &fn, cudaEnableDefault, &qr);
        enc = (EncodeFn)fn;
        cudaFuncSetAttribute(fused_kernel, cudaFuncAttributeMaxDynamicSharedMemorySize, SM_TOTAL);
        cudaGetSymbolAddress(&raw, g_raw);
    }
    Params P;
    makekv(enc, &P.k, d_in[1]);
    makekv(enc, &P.v, d_in[2]);
    make2d(enc, &P.wq, d_in[3], DM, NH * DH, 64, 32, CU_TENSOR_MAP_SWIZZLE_64B);
    make2d(enc, &P.wo, d_in[4], NH * DH, DM, 32, 64, CU_TENSOR_MAP_SWIZZLE_128B);
    make2d(enc, &P.wm, d_in[10], DM, 6 * DM, 256, 8, CU_TENSOR_MAP_SWIZZLE_NONE);
    make2d(enc, &P.wn, d_in[10], DM, 6 * DM, 256, 16, CU_TENSOR_MAP_SWIZZLE_32B);
    make5d(enc, &P.wg, d_in[6], FF, {4, 2, 4, 16}, {1, 16, 4, 32}, 4);
    make5d(enc, &P.wu, d_in[7], FF, {4, 2, 4, 16}, {1, 16, 4, 32}, 4);
    make5d(enc, &P.wd, d_in[8], DM, {8, 4, 1, 43}, {4, 1, 1, 32}, 43);
    P.out = (__nv_bfloat16*)d_out;
    typedef const __nv_bfloat16* W;
    fused_kernel<<<NCTA, NALL, SM_TOTAL>>>((W)d_in[0], (W)d_in[9], (W)d_in[1], (W)d_in[10], (W)d_in[3], (char*)(((size_t)raw + X_ALIGN - 1) & ~(size_t)(X_ALIGN - 1)), P);
}
```

```cpp
#include <cuda_runtime.h>
#include <cuda_bf16.h>
#include <cuda.h>
#include <stdint.h>

namespace {

constexpr int NB = 8, DM = 512, NH = 32, DH = 128, SK = 4096, WIN = 1024, FF = 1376;
constexpr int NCTA = 128, NTHR = 288, NALL = 320;
constexpr int NT = 16;
constexpr int NF1 = 86, DN0 = 96;
constexpr unsigned SENT = 0xFFFFFFFFu;
constexpr int SPIN_MAX = 1 << 20;

constexpr int PWIN0 = 12;
constexpr int PWIN = 16;
constexpr int PSW = 22;
constexpr int NTRK = 8;
constexpr int PFK = 2;
constexpr int QN = 7;
constexpr int TAU = 166;
constexpr int ANCH0 = 176;
constexpr int LEAD = 1600;
constexpr int PACE0 = 7000;
constexpr int PNAP = 200;
constexpr int WOA_ISSUE = 3;
constexpr int WO_GAP = 2;
constexpr int WOA_READ = 8;
constexpr int NPRE = 9;
constexpr int W0 = 850;
constexpr int WS = 180;
constexpr int WD0 = 1700;
constexpr int RT0 = 1700;
constexpr int HD0 = 1000;
constexpr int XDW = 30;
constexpr int HDW = 45;
constexpr int XC = 2;

constexpr int UNIT = 4096, REG = 8 * UNIT;
constexpr int SM_SCR = 6 * REG;
constexpr int SCR = 2048;
constexpr int SM_MN = SM_SCR + 8 * SCR;
constexpr int SM_SC = SM_MN + 8192;
constexpr int SM_BAR = SM_SC + 8192;
constexpr int SM_BM = SM_BAR + 512, SM_BT = SM_BM + 8, SM_BN = SM_BM + 16, SM_BG = SM_BM + 24;
constexpr int SM_AN = SM_BM + 32, SM_SIDE = SM_BM + 36, SM_TAG = SM_BM + 40, SM_MASK = SM_BM + 44;
constexpr int SM_ST = SM_BAR + 576;
constexpr int SM_ML = SM_ST + 512;
constexpr int SM_PR = SM_ML + 96;
constexpr int SM_TOTAL = SM_PR + 512;
constexpr int SC_M = 0, SC_Q = 256;
constexpr int SC_F1 = 0, SC_DN = 0, SC_RX = 1536;
constexpr int B_INIT = 0, B_ALL = 2, B_MOD = 3, B_WQ = 4, B_LAST = 5, B_RDY = 6, B_DN = 7, B_PRE = 8, B_FIN = 9, B_STG = 10, B_SIDE = 11, B_Q = 12, B_ML = 13;

constexpr unsigned HOME = 0xB3000;
constexpr int X_PART = 0;
constexpr int X_Q = 0x100000;
constexpr int X_M1 = 0x140000;
constexpr int X_X1 = 0x150000;
constexpr int X_HM = 0x160000;
constexpr int X_MOD = 0x170000;
constexpr int X_SIDE = 0x176000;
constexpr int X_EPOCH = 0x176400;
constexpr int X_READY = 0x176480;
constexpr int X_LAG = 0x178000;
constexpr int X_ANC = 0x158000;
constexpr int X_PRB = 0x180000;
constexpr int X_ALIGN = 0x200000;
static_assert(XC == 2, "one store writes all copies of x1");
__device__ uint4 g_raw[2 * X_ALIGN / 16];
__device__ __forceinline__ unsigned blk(unsigned base, unsigned k, unsigned s) { const unsigned o = base + k * 8192; return o + ((__popc(o & HOME) ^ s) & 1) * 4096; }

struct Params {
    CUtensorMap wm, wq, k, v, wn, wo, wg, wu, wd;
    __nv_bfloat16* out;
};

__device__ __forceinline__ int tile_key(int i) { return (i & 1) * 128 + (i & 2) * 32 + (i & 12) * 64; }

__device__ __forceinline__ uint32_t smem_u32(const void* p) { return (uint32_t)__cvta_generic_to_shared(p); }
__device__ __forceinline__ void mbar_init(uint32_t a, uint32_t c) { asm volatile("mbarrier.init.shared::cta.b64 [%0], %1;" :: "r"(a), "r"(c) : "memory"); }
__device__ __forceinline__ void mbar_expect(uint32_t a, uint32_t b) { asm volatile("mbarrier.arrive.expect_tx.shared::cta.b64 _, [%0], %1;" :: "r"(a), "r"(b) : "memory"); }
__device__ __forceinline__ void mbar_wait(uint32_t a, uint32_t par) {
    uint32_t ok; int n = 0;
    do {
        asm volatile("{\n.reg .pred p;\nmbarrier.try_wait.parity.shared::cta.b64 p, [%1], %2, 2000;\nselp.u32 %0, 1, 0, p;\n}" : "=r"(ok) : "r"(a), "r"(par) : "memory");
        if (++n > SPIN_MAX) __trap();
    } while (!ok);
}
__device__ __forceinline__ bool mbar_test(uint32_t a, uint32_t par) {
    uint32_t ok; asm volatile("{\n.reg .pred p;\nmbarrier.test_wait.parity.shared::cta.b64 p, [%1], %2;\nselp.u32 %0, 1, 0, p;\n}" : "=r"(ok) : "r"(a), "r"(par) : "memory"); return ok;
}
__device__ __forceinline__ void tma2d(uint32_t dst, const CUtensorMap* m, int x, int y, uint32_t bar) {
    asm volatile("cp.async.bulk.tensor.2d.shared::cluster.global.mbarrier::complete_tx::bytes [%0], [%1, {%3, %4}], [%2];"
                 :: "r"(dst), "l"(m), "r"(bar), "r"(x), "r"(y) : "memory");
}
__device__ __forceinline__ void tma5d(uint32_t dst, const CUtensorMap* m, int x, int y, uint32_t bar) {
    asm volatile("cp.async.bulk.tensor.5d.shared::cluster.global.mbarrier::complete_tx::bytes [%0], [%1, {%3, 0, 0, 0, %4}], [%2];"
                 :: "r"(dst), "l"(m), "r"(bar), "r"(x), "r"(y) : "memory");
}
__device__ __forceinline__ void tma_kv(uint32_t dst, const CUtensorMap* m, int row, uint32_t bar, uint64_t pol) {
    asm volatile("cp.async.bulk.tensor.3d.shared::cluster.global.mbarrier::complete_tx::bytes.L2::cache_hint [%0], [%1, {0, %3, 0}], [%2], %4;"
                 :: "r"(dst), "l"(m), "r"(bar), "r"(row), "l"(pol) : "memory");
}
__device__ __forceinline__ void pf_bulk(const void* p, uint32_t n) { asm volatile("cp.async.bulk.prefetch.L2.global [%0], %1;" :: "l"(p), "r"(n) : "memory"); }
__device__ __forceinline__ void pf_if(const void* p, unsigned i, unsigned n) { asm volatile("{\n.reg .pred p;\nsetp.lt.u32 p, %1, %2;\n@p prefetch.global.L2 [%0];\n}" :: "l"(p), "r"(i), "r"(n) : "memory"); }
__device__ __forceinline__ uint4 ldg_nc(const void* p) { uint4 v; asm volatile("ld.global.nc.v4.u32 {%0,%1,%2,%3}, [%4];" : "=r"(v.x), "=r"(v.y), "=r"(v.z), "=r"(v.w) : "l"(p)); return v; }
__device__ __forceinline__ bool elect() { uint32_t p; asm volatile("{\n.reg .pred p;\nelect.sync _|p, -1;\nselp.u32 %0, 1, 0, p;\n}" : "=r"(p)); return p; }
__device__ __forceinline__ void pf_map(const CUtensorMap* m) { asm volatile("prefetch.tensormap [%0];" :: "l"(m) : "memory"); }
__device__ __forceinline__ void ldsm(uint32_t (&r)[4], uint32_t a) {
    asm volatile("ldmatrix.sync.aligned.m8n8.x4.shared.b16 {%0,%1,%2,%3}, [%4];" : "=r"(r[0]), "=r"(r[1]), "=r"(r[2]), "=r"(r[3]) : "r"(a) : "memory");
}
__device__ __forceinline__ void ldsm_t(uint32_t (&r)[4], uint32_t a) {
    asm volatile("ldmatrix.sync.aligned.m8n8.x4.trans.shared.b16 {%0,%1,%2,%3}, [%4];" : "=r"(r[0]), "=r"(r[1]), "=r"(r[2]), "=r"(r[3]) : "r"(a) : "memory");
}
__device__ __forceinline__ void mma(float (&c)[4], uint32_t a0, uint32_t a1, uint32_t a2, uint32_t a3, uint32_t b0, uint32_t b1) {
    asm("mma.sync.aligned.m16n8k16.row.col.f32.bf16.bf16.f32 {%0,%1,%2,%3}, {%4,%5,%6,%7}, {%8,%9}, {%0,%1,%2,%3};"
        : "+f"(c[0]), "+f"(c[1]), "+f"(c[2]), "+f"(c[3]) : "r"(a0), "r"(a1), "r"(a2), "r"(a3), "r"(b0), "r"(b1));
}
__device__ __forceinline__ void mma(float (&c)[4], const uint32_t (&a)[4], uint32_t b0, uint32_t b1) { mma(c, a[0], a[1], a[2], a[3], b0, b1); }
__device__ __forceinline__ uint32_t pin(uint32_t v) { asm volatile("shfl.sync.bfly.b32 %0, %0, 0, 31, -1;" : "+r"(v)); return v; }
template <class T> __device__ __forceinline__ T* pin(T* p) { const size_t a = (size_t)p; return (T*)(pin((uint32_t)a) | (size_t)pin((uint32_t)(a >> 32)) << 32); }
__device__ __forceinline__ uint32_t movm(uint32_t a) { uint32_t r; asm volatile("movmatrix.sync.aligned.m8n8.trans.b16 %0, %1;" : "=r"(r) : "r"(a)); return r; }
__device__ __forceinline__ uint32_t pack2(float lo, float hi) { uint32_t r; asm("cvt.rn.bf16x2.f32 %0, %1, %2;" : "=r"(r) : "f"(hi), "f"(lo)); return r; }
__device__ __forceinline__ float blo(uint32_t w) { return __uint_as_float(w << 16); }
__device__ __forceinline__ float bhi(uint32_t w) { return __uint_as_float(w & 0xFFFF0000u); }
__device__ __forceinline__ float rbf(float x) { return blo(pack2(x, 0.f)); }
__device__ __forceinline__ uint32_t add2(uint32_t a, uint32_t b) { uint32_t r; asm("add.rn.bf16x2 %0, %1, %2;" : "=r"(r) : "r"(a), "r"(b)); return r; }
__device__ __forceinline__ uint32_t sub2(uint32_t a, uint32_t b) { uint32_t r; asm("sub.rn.bf16x2 %0, %1, %2;" : "=r"(r) : "r"(a), "r"(b)); return r; }
__device__ __forceinline__ uint32_t mul2(uint32_t a, uint32_t b) { uint32_t r; asm("mul.rn.bf16x2 %0, %1, %2;" : "=r"(r) : "r"(a), "r"(b)); return r; }
constexpr uint32_t ONE2 = 0x3F803F80u;
constexpr float LOG2E = 1.4426950408889634f, SCALE = 0.08838834764831845f;
__device__ __forceinline__ float ex2(float x) { float y; asm("ex2.approx.ftz.f32 %0, %1;" : "=f"(y) : "f"(x)); return y; }
__device__ __forceinline__ uint4 ldg_rlx128(const void* p) {
    uint4 v; asm volatile("ld.relaxed.gpu.global.v4.u32 {%0,%1,%2,%3}, [%4];" : "=r"(v.x), "=r"(v.y), "=r"(v.z), "=r"(v.w) : "l"(p) : "memory"); return v;
}
__device__ __forceinline__ uint4 ldg_rlx2x64(const void* p) {
    unsigned long long a, b; asm volatile("ld.relaxed.gpu.global.v2.u64 {%0,%1}, [%2];" : "=l"(a), "=l"(b) : "l"(p) : "memory");
    return make_uint4((unsigned)a, (unsigned)(a >> 32), (unsigned)b, (unsigned)(b >> 32));
}
__device__ __forceinline__ uint2 ldg_rlx64(const void* p) {
    unsigned long long a; asm volatile("ld.relaxed.gpu.global.u64 %0, [%1];" : "=l"(a) : "l"(p) : "memory"); return make_uint2((unsigned)a, (unsigned)(a >> 32));
}
__device__ __forceinline__ unsigned ldg_acq32(const void* p) { unsigned v; asm volatile("ld.acquire.gpu.global.u32 %0, [%1];" : "=r"(v) : "l"(p) : "memory"); return v; }
__device__ __forceinline__ void red_add(void* p, unsigned v) { asm volatile("red.relaxed.gpu.global.add.u32 [%0], %1;" :: "l"(p), "r"(v) : "memory"); }
__device__ __forceinline__ unsigned now_ns() { unsigned t; asm volatile("mov.u32 %0, %%globaltimer_lo;" : "=r"(t)); return t; }
__device__ __forceinline__ void nap(unsigned ns) { asm volatile("nanosleep.u32 %0;" :: "r"(ns)); }
__device__ __forceinline__ unsigned ldg_rlx32(const void* p) { unsigned v; asm volatile("ld.relaxed.gpu.global.u32 %0, [%1];" : "=r"(v) : "l"(p) : "memory"); return v; }
__device__ __forceinline__ void stg_rlx32(void* p, unsigned v) { asm volatile("st.relaxed.gpu.global.u32 [%0], %1;" :: "l"(p), "r"(v) : "memory"); }
__device__ __forceinline__ void stg_rlx16(void* p, unsigned v) { asm volatile("st.relaxed.gpu.global.u16 [%0], %1;" :: "l"(p), "h"((unsigned short)v) : "memory"); }
__device__ __forceinline__ uint4 ldg_b128(const void* p) {
    unsigned long long a, b; asm volatile("{\n.reg .b128 x;\nld.relaxed.gpu.global.b128 x, [%2];\nmov.b128 {%0,%1}, x;\n}" : "=l"(a), "=l"(b) : "l"(p) : "memory");
    return make_uint4((unsigned)a, (unsigned)(a >> 32), (unsigned)b, (unsigned)(b >> 32));
}
__device__ __forceinline__ void stg_b128(void* p, uint4 v) {
    asm volatile("{\n.reg .b128 x;\nmov.b128 x, {%1,%2};\nst.relaxed.gpu.global.b128 [%0], x;\n}" :: "l"(p), "l"(v.x | ((unsigned long long)v.y << 32)), "l"(v.z | ((unsigned long long)v.w << 32)) : "memory");
}
__device__ __forceinline__ int rowoff(int b, int c) { return ((c >> 6) * 2 + ((c >> 2) & 1)) * 512 + b * 64 + (c & 3) * 16 + ((c >> 3) & 1) * 8 + ((c >> 5) & 1) * 4 + ((c >> 4) & 1) * 2; }
__device__ __forceinline__ void stg_rlx64(void* p, unsigned lo, unsigned hi) {
    unsigned long long a = lo | ((unsigned long long)hi << 32); asm volatile("st.relaxed.gpu.global.u64 [%0], %1;" :: "l"(p), "l"(a) : "memory");
}
__device__ __forceinline__ void stg_rlx128(void* p, uint4 v) { asm volatile("st.relaxed.gpu.global.v4.u32 [%0], {%1,%2,%3,%4};" :: "l"(p), "r"(v.x), "r"(v.y), "r"(v.z), "r"(v.w) : "memory"); }
__device__ __forceinline__ void sts32u(uint32_t a, unsigned x) { asm volatile("st.volatile.shared.u32 [%0], %1;" :: "r"(a), "r"(x) : "memory"); }
__device__ __forceinline__ unsigned lds32u(uint32_t a) { unsigned v; asm volatile("ld.volatile.shared.u32 %0, [%1];" : "=r"(v) : "r"(a) : "memory"); return v; }
__device__ __forceinline__ void spin(unsigned c0, unsigned d) { if (d) while ((unsigned)clock() - c0 < d) {} }
__device__ __forceinline__ void fence_gpu() { asm volatile("fence.acq_rel.gpu;" ::: "memory"); }
template <int ID, int N> __device__ __forceinline__ void bar_sync() { asm volatile("bar.sync %0, %1;" :: "n"(ID), "n"(N) : "memory"); }
template <int ID, int N> __device__ __forceinline__ void bar_arrive() { asm volatile("bar.arrive %0, %1;" :: "n"(ID), "n"(N) : "memory"); }
__device__ __forceinline__ void sts64(uint32_t a, float x, float y) { asm volatile("st.shared.v2.f32 [%0], {%1,%2};" :: "r"(a), "f"(x), "f"(y) : "memory"); }
__device__ __forceinline__ void sts128(uint32_t a, uint4 v) { asm volatile("st.volatile.shared.v4.u32 [%0], {%1,%2,%3,%4};" :: "r"(a), "r"(v.x), "r"(v.y), "r"(v.z), "r"(v.w) : "memory"); }
__device__ __forceinline__ void sts128f(uint32_t a, float x, float y, float z, float w) { asm volatile("st.volatile.shared.v4.f32 [%0], {%1,%2,%3,%4};" :: "r"(a), "f"(x), "f"(y), "f"(z), "f"(w) : "memory"); }
__device__ __forceinline__ void sts32(uint32_t a, float x) { asm volatile("st.shared.f32 [%0], %1;" :: "r"(a), "f"(x) : "memory"); }
__device__ __forceinline__ float2 lds64(uint32_t a) { float2 v; asm volatile("ld.shared.v2.f32 {%0,%1}, [%2];" : "=f"(v.x), "=f"(v.y) : "r"(a) : "memory"); return v; }
__device__ __forceinline__ float lds32(uint32_t a) { float v; asm volatile("ld.shared.f32 %0, [%1];" : "=f"(v) : "r"(a) : "memory"); return v; }
__device__ __forceinline__ float4 lds128(uint32_t a) { float4 v; asm volatile("ld.shared.v4.f32 {%0,%1,%2,%3}, [%4];" : "=f"(v.x), "=f"(v.y), "=f"(v.z), "=f"(v.w) : "r"(a) : "memory"); return v; }
__device__ __forceinline__ float2 sum8(uint32_t a) {
    float2 v[8];
#pragma unroll
    for (int i = 0; i < 8; i++) v[i] = lds64(a + i * SCR);
    return make_float2(((v[0].x + v[1].x) + (v[2].x + v[3].x)) + ((v[4].x + v[5].x) + (v[6].x + v[7].x)),
                       ((v[0].y + v[1].y) + (v[2].y + v[3].y)) + ((v[4].y + v[5].y) + (v[6].y + v[7].y)));
}
template <int STRIDE> __device__ __forceinline__ float4 sum8x4(uint32_t a) {
    float4 v[8];
#pragma unroll
    for (int i = 0; i < 8; i++) v[i] = lds128(a + i * STRIDE);
    return make_float4(((v[0].x + v[1].x) + (v[2].x + v[3].x)) + ((v[4].x + v[5].x) + (v[6].x + v[7].x)), ((v[0].y + v[1].y) + (v[2].y + v[3].y)) + ((v[4].y + v[5].y) + (v[6].y + v[7].y)),
                       ((v[0].z + v[1].z) + (v[2].z + v[3].z)) + ((v[4].z + v[5].z) + (v[6].z + v[7].z)), ((v[0].w + v[1].w) + (v[2].w + v[3].w)) + ((v[4].w + v[5].w) + (v[6].w + v[7].w)));
}
__device__ __forceinline__ float rcp(float x) { float y; asm("rcp.approx.ftz.f32 %0, %1;" : "=f"(y) : "f"(x)); return y; }
__device__ __forceinline__ float sigmoid_f(float x) { return rcp(1.0f + ex2(x * -LOG2E)); }
__device__ __forceinline__ uint32_t silu2(uint32_t c) { const float a = blo(c), b = bhi(c); return pack2(a * sigmoid_f(a), b * sigmoid_f(b)); }
__device__ __forceinline__ void ln_consts(float mean, float var, uint32_t& mu2, float& rs) {
    mu2 = pack2(mean, mean);
    float sd; asm("sqrt.approx.ftz.f32 %0, %1;" : "=f"(sd) : "f"(rbf(rbf(var) + 1e-5f)));
    rs = rcp(rbf(sd));
}
__device__ __forceinline__ uint32_t ln_norm(uint32_t x2, uint32_t mu2, float rs) { const uint32_t d = sub2(x2, mu2); return pack2(blo(d) * rs, bhi(d) * rs); }

__global__ void __launch_bounds__(NALL, 1) fused_kernel(const __nv_bfloat16* const px, const __nv_bfloat16* const pc, const __nv_bfloat16* const pk, const __nv_bfloat16* const pwm,
                                                        const __nv_bfloat16* const pwq, char* const X, const __grid_constant__ Params P) {
    extern __shared__ __align__(1024) unsigned char smem[];
    const uint32_t sb = smem_u32(smem);
    const int tid = threadIdx.x, w = tid >> 5, lane = tid & 31, g = lane >> 2, t = lane & 3;
    const int cta = blockIdx.x, head = cta >> 2, bat = (cta & 3) * 2 + (w >> 2);
    const uint32_t s0 = sb + w * UNIT, s2 = s0 + 4 * REG;
    const uint32_t bar0 = sb + SM_BAR + w * 64;
    const uint32_t barC = bar0 + 32;
    const uint32_t scr = sb + SM_SCR, myscr = scr + w * SCR;
    pf_if((const char*)pwm + ((cta * 4 + (lane >> 3)) * (6 * DM * 2) + w * 1024 + (lane & 7) * 128), w, 5);
    pf_if((const char*)pk + (unsigned)(((((cta & 3) * 2 + (w & 1)) * NH + head) * SK + (SK - WIN - 48) + tile_key(2) + (w >> 1) * 16) * (DH * 2) + lane * 128), w - 6, PFK);
    const int rid = !(cta & 1) ? cta >> 1 : (cta >> 2) + (cta & 2 ? 64 : 96);
    const unsigned t_start = now_ns();
    uint64_t pol;
    asm volatile("createpolicy.fractional.L2::evict_first.b64 %0, 1.0;" : "=l"(pol));
    auto go_first = [&](uint32_t wbar, uint32_t par) {
        for (int n = 0;; n++) {
            if (__all_sync(~0u, mbar_test(wbar, par))) return false;
            if (__all_sync(~0u, mbar_test(sb + SM_BG, 0))) return true;
            if (n > SPIN_MAX * 4) __trap();
            nap(20);
        }
    };
    if (w == 9) {
        const uint32_t sl = sb + SM_PR + lane * 16;
        char* const pl = X + blk(X_PRB, cta >> 1, lane & 1) + (lane >> 1) * 256 + (cta & 1) * 128;
        {
            char* const ps = X + X_PRB + (cta >> 1) * 8192 + g * 256 + (cta & 1) * 128 + t * 16;
            sts32u(sl, 0);
#pragma unroll
            for (int i = 0; i < 4; i++) stg_rlx128(ps + i * 2048, make_uint4(1, 1, 1, 1));
            __syncwarp();
        }
        unsigned v; asm volatile("atom.relaxed.gpu.global.add.u32 %0, [%1], 1;" : "=r"(v) : "l"(pl) : "memory");
        unsigned tag = ldg_rlx32(X + X_EPOCH);
        if (lane == 0) pf_bulk(pwq + (size_t)cta * QN * 1024, QN * 2048);
        if (lane == 0) sts32u(sb + SM_AN, t_start + ANCH0);
        if (lane < 8) sts32u(sb + SM_BAR + lane * 64 + 56, 0);
        unsigned side;
        {
            int d, n = 0;
#pragma unroll 1
            for (int r = 0; r < 4; r++) {
                if (v == SENT) __trap();
                asm volatile("cp.async.cg.shared.global [%0], [%1], 16;" :: "r"(sl), "l"(pl) : "memory");
                unsigned m;
                do {
                    m = __ballot_sync(~0u, lds32u(sl));
                    d = __popc(m & 0xAAAAAAAAu) - __popc(m & 0x55555555u);
                    if (++n > SPIN_MAX) __trap();
                } while (abs(d) < 6 && m != ~0u);
                if (abs(d) >= 6) break;
                asm volatile("cp.async.wait_all;" ::: "memory");
                sts32u(sl, 0);
                asm volatile("atom.relaxed.gpu.global.add.u32 %0, [%1], 1;" : "=r"(v) : "l"(pl) : "memory");
            }
            side = d > 0;
            tag++;
            if (lane == 0) { sts32u(sb + SM_SIDE, side); sts32u(sb + SM_TAG, tag); }
            bar_arrive<B_SIDE, NTHR>();
        }
        asm volatile("cp.async.wait_all;" ::: "memory");
        while (now_ns() - t_start < PACE0) nap(200);
        for (int n = 0; n < SPIN_MAX; n++) {
            const uint32_t wb = sb + SM_BAR + (lane & 7) * 64;
            const unsigned seen = lds32u(wb + 56), u = seen + ((lane >> 3) & 1), t1 = now_ns();
            const unsigned more = seen && mbar_test(wb + (u < 6 ? u : (~u & 2) + (u & 1)) * 8, u < 6 ? 0 : ((u - 2) >> 2) & 1);
            const unsigned lo = __reduce_min_sync(~0u, seen), sum = __reduce_add_sync(~0u, lane < 8 ? seen + more : lane < 16 ? more : 0);
            if (lo == 30) break;
            if (lo && lane < 2) stg_rlx64(X + X_LAG + (cta >> 5) * 8192 + lane * 4096 + (cta & 31) * 128, t1 - sum * TAU, tag);
            uint2 a = make_uint2(0, 0);
            if (cta == 0) {
                uint2 u[4];
#pragma unroll
                for (int i = 0; i < 4; i++) u[i] = ldg_rlx64(X + blk(X_LAG, i, side) + lane * 128);
                const int s = __reduce_add_sync(~0u, (int)(u[0].x + u[1].x + u[2].x + u[3].x - 4 * t_start));
                if (__all_sync(~0u, (u[0].y == tag) & (u[1].y == tag) & (u[2].y == tag) & (u[3].y == tag)) && lane < 2) {
                    a = make_uint2(t_start + s / NCTA, tag);
                    stg_rlx64(X + X_ANC + lane * 4096, a.x, tag);
                }
            } else if (lane == 0) a = ldg_rlx64(X + blk(X_ANC, 0, side));
            if (lane == 0 && a.y == tag) sts32u(sb + SM_AN, a.x - LEAD);
            __syncwarp();
            nap(PNAP);
        }
        {
            bar_sync<B_ML, NTHR>();
            const float2 ml = lds64(sb + SM_ML + (lane & 7) * 8);
            float M = fmaxf(ml.x, __shfl_xor_sync(~0u, ml.x, 1)); M = fmaxf(M, __shfl_xor_sync(~0u, M, 2));
            const float e = ex2((ml.x - M) * LOG2E);
            float L = e * ml.y; L += __shfl_xor_sync(~0u, L, 1); L += __shfl_xor_sync(~0u, L, 2);
            if (lane < 8) sts32(sb + SM_ML + 64 + lane * 4, e * rcp(L));
        }
        bar_arrive<B_RDY, NALL>();
        bar_sync<B_STG, 64>();
        {
            const char* const pp = pin(X + blk(X_PART, cta, side) + lane * 16);
            char* const xo = pin(X + (lane >> 4) * 16384 + blk(X_X1, (cta >> 3) & 1, lane >> 3) + (cta & 7) * 512 + (cta >> 4) * 64 + (lane & 7) * 8);
            const float4 gx = lds128(scr + SC_RX + (lane & 7) * 16);
            const unsigned t0 = lds32u(sb + SM_AN) + 256 * TAU + RT0 + (cta & 7) * (TAU / 8);
            while ((int)(now_ns() - t0) < 0) nap(20);
            uint4 v[8]; int n = 0;
            float a[4];
#pragma unroll
            for (int j = 0; j < 8; j++) v[j] = ldg_b128(pp + j * 512);
            while (true) {
#define RSUM(f) (((__uint_as_float(v[0].f) + __uint_as_float(v[1].f)) + (__uint_as_float(v[2].f) + __uint_as_float(v[3].f))) + ((__uint_as_float(v[4].f) + __uint_as_float(v[5].f)) + (__uint_as_float(v[6].f) + __uint_as_float(v[7].f))))
                const bool ok = __all_sync(~0u, max(max(max(v[0].x, v[1].x), max(v[2].x, v[3].x)), max(max(v[4].x, v[5].x), max(v[6].x, v[7].x))) != SENT);
                a[0] = RSUM(x); a[1] = RSUM(y); a[2] = RSUM(z); a[3] = RSUM(w);
                asm volatile("" : "+f"(a[0]), "+f"(a[1]), "+f"(a[2]), "+f"(a[3]));
                if (ok) break;
#pragma unroll
                for (int j = 0; j < 8; j++) if (v[j].x == SENT) v[j] = ldg_b128(pp + j * 512);
                if (++n > SPIN_MAX) __trap();
            }
#pragma unroll
            for (int i = 0; i < 4; i++) a[i] += __shfl_xor_sync(~0u, a[i], 8);
#pragma unroll
            for (int i = 0; i < 4; i++) a[i] += __shfl_xor_sync(~0u, a[i], 16);
            stg_rlx64(xo, add2(__float_as_uint(gx.z), mul2(__float_as_uint(gx.x), pack2(a[0], a[1]))), add2(__float_as_uint(gx.w), mul2(__float_as_uint(gx.y), pack2(a[2], a[3]))));
        }
        if (rid >= DN0) {
            const unsigned c1 = clock();
            const int f = rid - DN0;
            const char* const rp = X + (rid & (XC - 1)) * 16384 + blk(X_X1, f >> 4, side) + (rowoff(g, f * 16 + t * 4) & 4092);
            unsigned r[4]; int n = 0;
            spin(c1, HD0 - 450);
            do {
#pragma unroll
                for (int i = 0; i < 4; i++) r[i] = ldg_rlx32(rp + i * 16);
                if (++n > SPIN_MAX) __trap();
            } while (max(max(r[0], r[1]), max(r[2], r[3])) == SENT);
            const unsigned sel = (f & 1) ? 0x7632 : 0x5410;
            sts64(sb + SM_MN + 256 + lane * 8, __uint_as_float(__byte_perm(r[0], r[1], sel)), __uint_as_float(__byte_perm(r[2], r[3], sel)));
            __syncwarp();
            spin(c1, HD0);
        }
        if (lane == 0) asm volatile("mbarrier.arrive.shared::cta.b64 _, [%0];" :: "r"(sb + SM_BG) : "memory");
    } else if (w == 8) {
        const int row0 = ((cta & 3) * 2 * NH + head) * SK + (SK - WIN);
        auto kv_unit = [&](int u) {
            const uint32_t b = sb + SM_BAR + (u & 7) * 64 + (u >> 3) * 8;
            mbar_expect(b, UNIT);
            tma_kv(sb + (u >> 3) * REG + (u & 7) * UNIT, (u & 8) ? &P.v : &P.k, row0 + ((u >> 2) & 1) * NH * SK + (u & 3) * 16 + tile_key(u >> 4), b, pol);
        };
        if (elect()) {
            mbar_init(sb + SM_BM, 1);
#pragma unroll
            for (int i = 0; i < 8; i++) mbar_init(sb + SM_BAR + i * 64 + 48, 1);
            asm volatile("fence.mbarrier_init.release.cluster;" ::: "memory");
            mbar_expect(sb + SM_BM, 512 * 16);
            tma2d(sb + 4 * REG, &P.wm, cta * 8, 0, sb + SM_BM); tma2d(sb + 4 * REG + 256 * 16, &P.wm, cta * 8, 256, sb + SM_BM);
#pragma unroll
            for (int i = 0; i < 8; i++) { const uint32_t b = sb + SM_BAR + i * 64 + 48; mbar_expect(b, UNIT); tma2d(sb + 5 * REG + i * UNIT, &P.wq, cta * 32, i * 64, b); }
            mbar_init(sb + SM_BN, 1); mbar_init(sb + SM_BT, 1); mbar_init(sb + SM_BG, 1);
#pragma unroll
            for (int i = 0; i < 48; i++) mbar_init(sb + SM_BAR + (i & 7) * 64 + (i >> 3) * 8, 1);
            asm volatile("fence.mbarrier_init.release.cluster;" ::: "memory");
        }
        __syncwarp();
        bar_arrive<B_INIT, NTHR>();
        {
            uint32_t mine = lane >= NTRK ? 0 : lane < 8 ? sb + SM_BAR + lane * 64 + 48 : sb + SM_BM;
            int next = 0, lim = 32, n = 0;
            while (next < 48) {
                const bool idle = lane < (next < PSW ? PWIN0 : PWIN) && (mine == 0 || mbar_test(mine, 0));
                const unsigned m = __ballot_sync(~0u, idle);
                const int u = next + __popc(m & ((1u << lane) - 1));
                if (idle) {
                    mine = 0;
                    if (u < lim) { kv_unit(u); mine = sb + SM_BAR + (u & 7) * 64 + (u >> 3) * 8; }
                }
                next = min(next + __popc(m), lim);
                if (next == lim) {
                    if (lim == 32) { bar_sync<B_MOD, NTHR>(); } else if (lim == 40) { bar_sync<B_WQ, NTHR>(); }
                    lim += 8;
                }
                if (!m) nap(30);
                if (++n > SPIN_MAX) __trap();
            }
        }
        if (lane < 5) pf_map(&P.wn + lane);
        float m[4][4] = {};
        auto late_mod = [&](uint32_t a, int h) {
            const int lrow = (lane & 7) + ((lane >> 4) << 3), lch = (lane >> 3) & 1;
            const uint32_t a0 = a + lrow * 32 + ((lch ^ ((lrow >> 2) & 1)) << 4);
            const uint32_t c0 = sb + SM_SC + h * 4096 + (lane & 7) * 128 + (((lane >> 3) ^ (lane & 7)) << 4);
#pragma unroll
            for (int j = 0; j < 8; j++) {
                uint32_t c[4], r[4], u[4];
                ldsm(c, (c0 + (j >> 1) * 1024) ^ ((j & 1) << 6)); ldsm_t(r, a0 + j * 1024); ldsm_t(u, a0 + j * 1024 + 512);
                mma(m[(j & 1) * 2], r, c[0], c[1]); mma(m[(j & 1) * 2 + 1], u, c[2], c[3]);
            }
        };
        if (rid < 96) {
#pragma unroll 1
            for (int h = 0; h < 2; h++) {
                if (lane == 0) { mbar_expect(sb + SM_BN, 8192); tma2d(sb + SM_MN, &P.wn, 2 * DM + rid * 16, h * 256, sb + SM_BN); }
                mbar_wait(sb + SM_BN, h);
                late_mod(sb + SM_MN, h);
                asm volatile("" :: "f"(m[0][0]), "f"(m[1][0]), "f"(m[2][0]), "f"(m[3][0]) : "memory");
                __syncwarp();
            }
#pragma unroll
            for (int e = 0; e < 4; e++) {
                float v = rbf((m[0][e] + m[1][e]) + (m[2][e] + m[3][e]));
                if (rid >= 64) v += 1.0f;
                stg_rlx16(X + X_MOD + (rid >> 5) * 8192 + rowoff(2 * t + (e & 1), (rid & 31) * 16 + g + (e >> 1) * 8), pack2(v, 0.f));
            }
        }
        {
            const unsigned side = lds32u(sb + SM_SIDE);
#pragma unroll
            for (int i = 0; i < 8; i++) stg_rlx128(X + blk(X_PART, cta, side) + i * 512 + lane * 16, make_uint4(SENT, SENT, SENT, SENT));
            if (lane == 0) stg_rlx32(X + X_SIDE + cta * 4, side);
        }
        bar_sync<B_Q, NTHR>();
        if (lane == 0) {
            const unsigned tag = lds32u(sb + SM_TAG);
            fence_gpu();
            red_add(X + X_READY, 1);
            int n = 0;
            while ((int)(ldg_acq32(X + X_READY) - tag * NCTA) < 0) { nap(1000); if (++n > SPIN_MAX) __trap(); }
            if (cta == 0) stg_rlx32(X + X_EPOCH, tag);
        }
        __syncwarp();
        {
            stg_rlx128(X + blk(X_Q, head >> 1, 0) + (head & 1) * 2048 + g * 256 + (cta & 3) * 64 + t * 16, make_uint4(0, 0, 0, 0));
            stg_rlx128(X + blk(X_Q, head >> 1, 1) + (head & 1) * 2048 + g * 256 + (cta & 3) * 64 + t * 16, make_uint4(0, 0, 0, 0));
            stg_rlx64(X + blk(X_M1, cta >> 5, lane >> 4) + (cta & 31) * 128 + (lane & 15) * 8, 0, 0);
            const int wt = (cta & 3) * 32 + lane;
            const unsigned mask = __ballot_sync(~0u, blk(X_PART, wt, ldg_rlx32(X + X_SIDE + wt * 4)) & 4096);
            if (lane == 0) sts32u(sb + SM_MASK, mask);
            if (lane < 8) {
                const int rb = cta >> 4, c = ((cta & 15) >> 1) * 64 + (cta & 1) * 4 + (lane >> 1) + (lane & 1) * 8;
                const uint2 ga = ldg_rlx64(X + X_MOD + rowoff(rb, c));
                const unsigned short* const xp = (const unsigned short*)px + rb * DM + c;
                sts128(scr + SC_RX + lane * 16, make_uint4(ga.x, ga.y, xp[0] | (xp[16] << 16), xp[32] | (xp[48] << 16)));
            }
            if (rid < NF1) {
#pragma unroll 1
                for (int i = 0; i < 4; i++) {
                    uint4 v[8];
#pragma unroll
                    for (int j = 0; j < 8; j++) v[j] = ldg_rlx128(X + X_MOD + 8192 + (i * 8 + j) * 512 + lane * 16);
#pragma unroll
                    for (int j = 0; j < 8; j++) sts128(sb + SM_MN + (i * 8 + j) * 512 + lane * 16, v[j]);
                }
            }
        }
        bar_arrive<B_RDY, NALL>();
        bar_arrive<B_STG, 64>();
        for (int n = 0; __any_sync(~0u, lds32u(sb + SM_BAR + (lane & 7) * 64 + 56) < 30); n++) { nap(100); if (n > SPIN_MAX) __trap(); }
        const unsigned t_ref = lds32u(sb + SM_AN) + 256 * TAU + (cta & 7) * (TAU / 8);
        auto until = [&](int x) { while ((int)(now_ns() - t_ref) < x) nap(20); };
        if (rid < NF1) {
            if (elect()) {
#pragma unroll
                for (int i = 0; i < 4; i++) mbar_expect(sb + SM_BAR + i * 64 + 48, 2 * UNIT);
#pragma unroll 1
                for (int i = 0; i < 4; i++) {
                    const uint32_t b = sb + SM_BAR + i * 64 + 48;
                    until(W0 + i * WS);
                    tma5d(sb + 2 * REG + i * UNIT, &P.wg, rid * 16, i * 4, b); tma5d(sb + 2 * REG + 16384 + i * UNIT, &P.wu, rid * 16, i * 4, b);
                }
            }
        } else if (rid >= DN0) {
            bar_sync<B_LAST, NTHR>();
            if (elect()) {
                mbar_expect(sb + SM_BN, 16384); mbar_expect(sb + SM_BT, FF * 32);
                until(WD0);
                tma5d(sb + 2 * REG + 16384, &P.wd, (rid - DN0) * 16, 0, sb + SM_BT);
                tma2d(sb + 2 * REG, &P.wn, 2 * DM + rid * 16, 0, sb + SM_BN); tma2d(sb + 2 * REG + 8192, &P.wn, 2 * DM + rid * 16, 256, sb + SM_BN);
            }
        }
        __syncwarp();
        if (rid >= DN0) {
            mbar_wait(sb + SM_BN, 0);
            late_mod(sb + 2 * REG, 0); late_mod(sb + 2 * REG + 8192, 1);
#pragma unroll
            for (int e = 0; e < 2; e++)
                sts32u(sb + SM_MN + g * 32 + e * 16 + t * 4, movm(pack2((m[0][2 * e] + m[1][2 * e]) + (m[2][2 * e] + m[3][2 * e]), (m[0][2 * e + 1] + m[1][2 * e + 1]) + (m[2][2 * e + 1] + m[3][2 * e + 1]))));
            bar_arrive<B_DN, NTHR>();
        }
    }
    if (w >= 8) {
        if (rid < NF1) {
            const int b = (tid - 256) >> 3, c = tid & 7;
            char* const ho = pin(X + X_HM + (rid >> 4) * 8192 + ((rid >> 1) & 7) * 512 + b * 64 + (rid & 1) * 32 + c * 4);
            const uint32_t pi = pin(scr + SC_F1 + c * 144 + b * 16), si = pin(sb + SM_ST + b * 64);
            bar_sync<B_PRE, NALL>();
            float4 C = sum8x4<UNIT>(sb + REG + c * 144 + b * 16), S = sum8x4<UNIT>(sb + REG + 1152 + c * 144 + b * 16);
            S.x *= -LOG2E; S.y *= -LOG2E; C.x *= LOG2E; C.y *= LOG2E;
            sts128f(sb + SM_PR + lane * 16, C.x, C.y, C.z, C.w); sts128f(sb + SM_PR + lane * 16, S.x, S.y, S.z, S.w);
            sts128(sb + SM_PR + lane * 16, make_uint4(pi, si, (uint32_t)(size_t)ho, (uint32_t)((size_t)ho >> 32)));
            bar_sync<B_FIN, NALL>();
            const float4 s0_ = lds128(si), s1_ = lds128(si + 16), s2_ = lds128(si + 32), s3_ = lds128(si + 48);
            const float4 p = sum8x4<SCR>(pi);
            const float mean = (((s0_.x + s0_.z) + (s1_.x + s1_.z)) + ((s2_.x + s2_.z) + (s3_.x + s3_.z))) * (1.0f / DM);
            const float sq = (((s0_.y + s0_.w) + (s1_.y + s1_.w)) + ((s2_.y + s2_.w) + (s3_.y + s3_.w))) * (1.0f / DM);
            float rs; asm("rsqrt.approx.ftz.f32 %0, %1;" : "=f"(rs) : "f"(fmaxf(sq - mean * mean, 0.f) + 1e-5f));
            const float e0 = rs * (mean * C.x - LOG2E * p.x) + S.x, e1 = rs * (mean * C.y - LOG2E * p.y) + S.y;
            const float u0 = rs * (p.z - mean * C.z) + S.z, u1 = rs * (p.w - mean * C.w) + S.w;
            const unsigned hw = pack2(rcp(1.0f + ex2(e0)) * u0, rcp(1.0f + ex2(e1)) * u1);
            stg_rlx32(ho, hw); stg_rlx32(ho + 4096, hw);
        }
        return;
    }
    const unsigned ce = (lane >> 3) * (DM * 2) + w * 128 + (lane & 7) * 16;
    const uint4 ca = ldg_nc((const char*)pc + ce), cb = ldg_nc((const char*)pc + ce + 4 * DM * 2);
    const uint4 xa = ldg_nc((const char*)px + w * (DM * 2) + lane * 16), xb = ldg_nc((const char*)px + w * (DM * 2) + lane * 16 + 512);
    const uint4 xc = ldg_nc((const char*)px + ce), xd = ldg_nc((const char*)px + ce + 4 * DM * 2);
    if (w >= 4) pf_map(&P.wm + (w & 3));
    char* const qout = X + blk(X_Q, head >> 1, tid >> 7) + (head & 1) * 2048 + ((tid >> 4) & 7) * 256 + (cta & 3) * 64 + (tid & 3) * 16 + ((tid >> 2) & 3) * 4;
    char* const mout = X + blk(X_M1, cta >> 5, w) + (cta & 31) * 128 + lane * 4;
    stg_rlx32(qout, 0);
    if (w < 2) stg_rlx32(mout, 0);
    uint32_t sc[8], xf[8];
    {
        const uint32_t a = (lane >> 3) * 128 + (((lane & 7) ^ (lane >> 3)) << 4), b = (lane & 7) * 128 + (((lane >> 3) ^ (lane & 7)) << 4);
        const uint32_t cs = sb + SM_SC + w * 1024;
        sts128(cs + a, make_uint4(silu2(ca.x), silu2(ca.y), silu2(ca.z), silu2(ca.w)));
        sts128(cs + 512 + (a ^ 64), make_uint4(silu2(cb.x), silu2(cb.y), silu2(cb.z), silu2(cb.w)));
        sts128(myscr + a, xc); sts128(myscr + 512 + (a ^ 64), xd);
        __syncwarp();
        ldsm(*(uint32_t(*)[4])&sc[0], cs + b); ldsm(*(uint32_t(*)[4])&sc[4], cs + (b ^ 64));
        ldsm(*(uint32_t(*)[4])&xf[0], myscr + b); ldsm(*(uint32_t(*)[4])&xf[4], myscr + (b ^ 64));
        __syncwarp();
    }
    {
        float v[16] = {blo(xa.x), bhi(xa.x), blo(xa.y), bhi(xa.y), blo(xa.z), bhi(xa.z), blo(xa.w), bhi(xa.w),
                       blo(xb.x), bhi(xb.x), blo(xb.y), bhi(xb.y), blo(xb.z), bhi(xb.z), blo(xb.w), bhi(xb.w)};
        float s = 0;
#pragma unroll
        for (int i = 0; i < 16; i++) s += v[i];
#pragma unroll
        for (int o = 16; o; o >>= 1) s += __shfl_xor_sync(~0u, s, o);
        s *= (1.0f / DM);
        float q2 = 0;
#pragma unroll
        for (int i = 0; i < 16; i++) q2 += (v[i] - s) * (v[i] - s);
#pragma unroll
        for (int o = 16; o; o >>= 1) q2 += __shfl_xor_sync(~0u, q2, o);
        uint32_t mu2; float rs; ln_consts(s, q2 * (1.0f / DM), mu2, rs);
        if (lane == 0) sts64(sb + SM_ST + w * 8, __uint_as_float(mu2), rs);
    }
    const int lrow = (lane & 7) + ((lane >> 4) << 3), lch = (lane >> 3) & 1;
    const uint32_t off64 = lrow * 64 + ((lch ^ ((lrow >> 1) & 3)) << 4);
    const uint32_t off128 = lrow * 128 + ((lch ^ (lane & 7)) << 4);
    bar_sync<B_INIT, NTHR>();
    mbar_wait(sb + SM_BM, 0);
    {
        float a[4] = {0, 0, 0, 0}, b[4] = {0, 0, 0, 0};
        uint32_t r[4], u[4];
        ldsm_t(r, sb + 4 * REG + (w * 64 + lane) * 16); ldsm_t(u, sb + 4 * REG + (w * 64 + 32 + lane) * 16);
        mma(a, sc[0], 0, sc[1], 0, r[0], r[1]); mma(b, sc[4], 0, sc[5], 0, u[0], u[1]);
        mma(a, sc[2], 0, sc[3], 0, r[2], r[3]); mma(b, sc[6], 0, sc[7], 0, u[2], u[3]);
        sts64(myscr + SC_M + lane * 8, a[0] + b[0], a[1] + b[1]);
    }
    bar_arrive<B_MOD, NTHR>();
    bar_sync<B_ALL, 256>();
    if (w < 2) {
        const float2 m = sum8(scr + SC_M + lane * 8);
        stg_rlx32(mout, ~pack2(m.x, m.y));
    }
    if (tid < 8 * XC) stg_rlx128(X + X_X1 + (cta * 8 * XC + tid) * 16, make_uint4(SENT, SENT, SENT, SENT));
    else if (tid >= 232) stg_rlx128(X + X_HM + (cta * 24 + tid - 232) * 16, make_uint4(SENT, SENT, SENT, SENT));
    {
        const float2 st = lds64(sb + SM_ST + g * 8);
#pragma unroll
        for (int i = 0; i < 8; i++) xf[i] = ln_norm(xf[i], __float_as_uint(st.x), st.y);
    }
    {
        unsigned sv[8], cv[8]; int n = 0;
        bar_sync<B_SIDE, NTHR>();
        const char* const mp = X + blk(X_M1, w >> 2, lds32u(sb + SM_SIDE)) + (w & 3) * 1024 + lane * 4;
        if (lane == 0) while (!ldg_rlx32(mp + 16384 + 7 * 128)) { nap(40); if (++n > SPIN_MAX) __trap(); }
        __syncwarp();
#pragma unroll
        for (int j = 0; j < 8; j++) { sv[j] = ldg_rlx32(mp + j * 128); cv[j] = ldg_rlx32(mp + 16384 + j * 128); }
        while (true) {
            unsigned m = ~0u;
#pragma unroll
            for (int j = 0; j < 8; j++) m = min(m, min(sv[j], cv[j]));
            if (__all_sync(~0u, m)) break;
#pragma unroll
            for (int j = 0; j < 8; j++) { if (!sv[j]) sv[j] = ldg_rlx32(mp + j * 128); if (!cv[j]) cv[j] = ldg_rlx32(mp + 16384 + j * 128); }
            if (++n > SPIN_MAX) __trap();
        }
#pragma unroll
        for (int j = 0; j < 8; j++) xf[j] = add2(mul2(xf[j], add2(~cv[j], ONE2)), ~sv[j]);
        mbar_wait(bar0 + 48, 0);
        float acc[4][4] = {};
#pragma unroll
        for (int j = 0; j < 4; j++) {
            uint32_t r[4], u[4];
            ldsm_t(r, s2 + REG + j * 1024 + off64); ldsm_t(u, s2 + REG + j * 1024 + (off64 ^ 32));
            mma(acc[0], xf[2 * j], 0, xf[2 * j + 1], 0, r[0], r[2]); mma(acc[1], xf[2 * j], 0, xf[2 * j + 1], 0, r[1], r[3]);
            mma(acc[2], xf[2 * j], 0, xf[2 * j + 1], 0, u[0], u[2]); mma(acc[3], xf[2 * j], 0, xf[2 * j + 1], 0, u[1], u[3]);
        }
#pragma unroll
        for (int n2 = 0; n2 < 4; n2++) sts64(myscr + SC_Q + g * 160 + n2 * 32 + t * 8, acc[n2][0], acc[n2][1]);
    }
    bar_arrive<B_WQ, NTHR>();
    bar_sync<B_ALL, 256>();
    {
        const float2 s = sum8(scr + SC_Q + ((tid >> 4) & 7) * 160 + (tid & 15) * 8);
        stg_rlx32(qout, ~pack2(s.x, s.y));
    }
    uint32_t q[16];
    {
        int n = 0;
        const char* const qp = X + blk(X_Q, head >> 1, lds32u(sb + SM_SIDE)) + (head & 1) * 2048 + bat * 256 + t * 16;
        uint4 v[4];
#pragma unroll
        for (int j = 0; j < 4; j++) v[j] = ldg_rlx128(qp + j * 64);
        while (true) {
            bool bad[4];
#pragma unroll
            for (int j = 0; j < 4; j++) bad[j] = !min(min(v[j].x, v[j].y), min(v[j].z, v[j].w));
            if (!__any_sync(~0u, bad[0] | bad[1] | bad[2] | bad[3])) break;
#pragma unroll
            for (int j = 0; j < 4; j++) if (bad[j]) v[j] = ldg_rlx128(qp + j * 64);
            if (++n > SPIN_MAX) __trap();
        }
#pragma unroll
        for (int j = 0; j < 4; j++) { q[4 * j] = ~v[j].x; q[4 * j + 1] = ~v[j].y; q[4 * j + 2] = ~v[j].z; q[4 * j + 3] = ~v[j].w; }
    }
    bar_arrive<B_Q, NTHR>();

    float o[2][4] = {};
    float mrun = -3.0e38f, lrun = 0.f;
    uint32_t wa[16][4], pb[2];
#pragma unroll
    for (int i = 0; i < 16; i++) wa[i][0] = wa[i][1] = wa[i][2] = wa[i][3] = 0;
    const uint32_t offk = (lane & 15) * 128 + (((lane >> 4) ^ (lane & 7)) << 4);
    float p0, p1;
    auto scores = [&](uint32_t a0) {
        uint32_t kf[8][4];
#pragma unroll
        for (int j = 0; j < 8; j++) ldsm(kf[j], ((a0 + offk) ^ ((j & 3) << 5)) + (j >> 2) * 2048);
        float sa[4] = {0, 0, 0, 0}, sb2[4] = {0, 0, 0, 0};
#pragma unroll
        for (int j = 0; j < 8; j += 2) { mma(sa, kf[j], q[2 * j], q[2 * j + 1]); mma(sb2, kf[j + 1], q[2 * j + 2], q[2 * j + 3]); }
        uint32_t u = pack2(sa[0] + sb2[0], sa[2] + sb2[2]);
        u = pack2(blo(u) * SCALE, bhi(u) * SCALE);
        const float z0 = blo(u), z1 = bhi(u);
        float mx = fmaxf(z0, z1);
        mx = fmaxf(mx, __shfl_xor_sync(~0u, mx, 4)); mx = fmaxf(mx, __shfl_xor_sync(~0u, mx, 8)); mx = fmaxf(mx, __shfl_xor_sync(~0u, mx, 16));
        mx = fmaxf(mx, mrun);
        const float f = ex2((mrun - mx) * LOG2E);
        p0 = ex2((z0 - mx) * LOG2E); p1 = ex2((z1 - mx) * LOG2E);
        mrun = mx; lrun = lrun * f + (p0 + p1);
#pragma unroll
        for (int j = 0; j < 4; j++) { o[0][j] *= f; o[1][j] *= f; }
    };
    const int kvrow = (bat * NH + head) * SK + (SK - WIN) + (w & 3) * 16;
    const int wofs = (w * 8 + (cta & 7)) * TAU / 8;
    auto request = [&](int u) {
        sts32u(bar0 + 56, u - 1);
        while ((int)(now_ns() - lds32u(sb + SM_AN) - u * 8 * TAU - wofs) < 0) nap(20);
        const int sl = (~u & 2) + (u & 1);
        mbar_expect(bar0 + sl * 8, UNIT); tma_kv(s0 + sl * REG, &P.k + (u & 1), kvrow + tile_key(u >> 1), bar0 + sl * 8, pol);
    };
#pragma unroll 1
    for (int it = 0; it < NT - 1; it++) {
        const int si = it < 3 ? it : (it + 1) & 1;
        const uint32_t bar = bar0 + si * 16, a0 = s0 + si * 2 * REG;
        const uint32_t par = it < 3 ? 0 : ((it - 1) >> 1) & 1;
        const bool refill = lane == 0 && it >= 2;
        mbar_wait(bar, par);
        if (refill) {
            request(2 * it + 2);
            const int e = it - (it > WOA_READ ? WOA_READ + 1 : WOA_ISSUE);
            if (e == 0) mbar_expect(barC, 2 * UNIT);
            if (e == 0 || e == WO_GAP) tma2d(s2 + (e ? REG : 0), &P.wo, w * 64, head * 128 + (it > WOA_READ ? 64 : 0) + (e ? 32 : 0), barC);
        }
        __syncwarp();
        if (it == WOA_READ) {
            mbar_wait(barC, 1);
#pragma unroll
            for (int j = 0; j < 16; j++) ldsm_t(wa[j], s2 + (j >> 3) * REG + ((j >> 2) & 1) * 2048 + (off128 ^ ((j & 3) << 5)));
        }
        scores(a0);
        pb[0] = movm(pack2(p0, p0)); pb[1] = movm(pack2(p1, p1));
        mbar_wait(bar + 8, par);
        if (refill) request(2 * it + 3);
        __syncwarp();
        uint32_t vf[8][4];
#pragma unroll
        for (int j = 0; j < 8; j++) ldsm_t(vf[j], ((a0 + off128) ^ ((j & 3) << 5)) + (j >> 2) * 2048 + REG);
#pragma unroll
        for (int j = 0; j < 8; j++) { const bool on = (g >> 1) == (j >> 1); mma(o[j & 1], vf[j], on ? pb[0] : 0, on ? pb[1] : 0); }
    }
    {
        uint32_t wb[16][4];
        mbar_wait(bar0, 1);
        if (rid >= DN0) bar_arrive<B_LAST, NTHR>();
        scores(s0);
        lrun += __shfl_xor_sync(~0u, lrun, 4); lrun += __shfl_xor_sync(~0u, lrun, 8); lrun += __shfl_xor_sync(~0u, lrun, 16);
        if (lane == 0) sts64(sb + SM_ML + w * 8, mrun, lrun);
        bar_arrive<B_ML, NTHR>();
        pb[0] = movm(pack2(p0, p0)); pb[1] = movm(pack2(p1, p1));
        const uint32_t va = pin(s0 + REG + off128);
        auto load_wb = [&](int j) { ldsm_t(wb[j], (va ^ ((j & 3) << 5)) + (3 + (j >> 3)) * REG + ((j >> 2) & 1) * 2048); };
        mbar_wait(barC, 0);
#pragma unroll
        for (int j = 0; j < NPRE; j++) load_wb(j);
        const uint32_t ho = pin(s0 + w * 16 + ((lane & 7) >> 1) * 64 + ((lane >> 3) & 1) * 32 + (lane & 1) * 16), oa = pin(sb + (lane & 7) * (UNIT + 16) + (lane >> 3) * 16);
        const uint32_t rd = pin((t >> 1) * 16 + w * 2 + (g >> 2));
        char* const pp = pin(X + X_PART + ((cta & 3) * 32 + rd) * 8192 + head * 128 + (g & 3) * 32 + (t & 1) * 16);
        const uint32_t ln = pin(lane);
        mbar_wait(bar0 + 8, 1);
        {
            uint32_t vf[8][4];
            float o2[2][4] = {};
#pragma unroll
            for (int j = 0; j < 8; j++) ldsm_t(vf[j], (va ^ ((j & 3) << 5)) + (j >> 2) * 2048);
#pragma unroll
            for (int j = 0; j < 8; j++) { const bool on = (ln >> 3) == (j >> 1); mma((j & 2) ? o2[j & 1] : o[j & 1], vf[j], on ? pb[0] : 0, on ? pb[1] : 0); }
            asm volatile("stmatrix.sync.aligned.m8n8.x2.trans.shared.b16 [%0], {%1,%2};" :: "r"(ho), "r"(pack2(o[0][0] + o2[0][0], o[0][2] + o2[0][2])), "r"(pack2(o[1][0] + o2[1][0], o[1][2] + o2[1][2])) : "memory");
        }
        bar_sync<B_RDY, NALL>();
        float y[4][4] = {};
        uint32_t ob[4][4];
#pragma unroll
        for (int i2 = 0; i2 < 4; i2++) ldsm(ob[i2], oa + i2 * 64);
        const float2 f = lds64(sb + SM_ML + 64 + (ln & 3) * 8);
        const unsigned half = (lds32u(sb + SM_MASK) >> rd & 1) * 4096;
#pragma unroll
        for (int j = NPRE; j < 16; j++) load_wb(j);
#pragma unroll
        for (int j = 0; j < 8; j++)
#pragma unroll
            for (int i = 0; i < 4; i++) mma(y[i], j < 4 ? wa[j * 4 + i] : wb[(j - 4) * 4 + i], ob[j >> 1][2 * (j & 1)], ob[j >> 1][2 * (j & 1) + 1]);
        uint32_t r[4];
#pragma unroll
        for (int i = 0; i < 4; i++) {
            const float lo = f.x * y[i][0] + f.y * y[i][1], hi = f.x * y[i][2] + f.y * y[i][3];
            r[i] = __float_as_uint(((ln & 1) ? hi : lo) + __shfl_xor_sync(~0u, (ln & 1) ? lo : hi, 1));
        }
        asm("min.u32 %0, %0, 0xFFFFFFFE;" : "+r"(r[0]));
        stg_b128(pp + half, make_uint4(r[0], r[1], r[2], r[3]));
    }
    const unsigned side = lds32u(sb + SM_SIDE);
    const char* const x1p = X + (rid & (XC - 1)) * 16384;
    if (rid < NF1) {
        uint32_t wg[4][4], wu[4][4];
        const char* const xp = pin(x1p + blk(X_X1, w >> 2, side) + (w & 3) * 1024 + lane * 16);
        float4 c1[2], sv[2];
#pragma unroll
        for (int h = 0; h < 2; h++) { sv[h] = lds128(sb + SM_MN + (w * 2 + h) * 512 + lane * 16); c1[h] = lds128(sb + SM_MN + 8192 + (w * 2 + h) * 512 + lane * 16); }
        const uint32_t po = pin(myscr + SC_F1 + g * 144 + t * 32), so = pin(t == (g >> 1) ? sb + SM_ST + g * 64 + w * 8 : myscr + 1792 + lane * 8), odd = pin(g & 1);
        const uint32_t wbar = sb + SM_BAR + (w >> 1) * 64 + 48;
        uint4 x0, x1;
        const bool early = go_first(wbar, 1);
        if (early) { spin(clock(), (7 - w) * XDW); x0 = ldg_rlx2x64(xp); x1 = ldg_rlx2x64(xp + 512); mbar_wait(wbar, 1); }
#pragma unroll
        for (int j = 0; j < 4; j++) {
            const uint32_t a = sb + 2 * REG + w * 2048 + (((lane & 7) >> 1) + (lane & 1) * 4 + j * 8 + (lane >> 4) * 32) * 32 + ((lch ^ (lane & 1)) << 4);
            ldsm_t(wg[j], a); ldsm_t(wu[j], a + 16384);
        }
        {
            float cg[4] = {}, cu[4] = {}, sg[4] = {}, su[4] = {};
#pragma unroll
            for (int j = 0; j < 4; j++) {
                const float4 a = c1[j & 1], b = sv[j & 1];
                const uint32_t a0 = __float_as_uint(j >> 1 ? a.z : a.x), a1 = __float_as_uint(j >> 1 ? a.w : a.y), b0 = __float_as_uint(j >> 1 ? b.z : b.x), b1 = __float_as_uint(j >> 1 ? b.w : b.y);
                mma(cg, wg[j], a0, a1); mma(cu, wu[j], a0, a1); mma(sg, wg[j], b0, b1); mma(su, wu[j], b0, b1);
            }
            const uint32_t d = s0 + REG + g * 144 + t * 32;
            sts128f(d, cg[0], cg[2], cu[0], cu[2]); sts128f(d + 16, cg[1], cg[3], cu[1], cu[3]);
            sts128f(d + 1152, sg[0], sg[2], su[0], su[2]); sts128f(d + 1168, sg[1], sg[3], su[1], su[3]);
            bar_arrive<B_PRE, NALL>();
        }
        if (!early) { mbar_wait(sb + SM_BG, 0); spin(clock(), (7 - w) * XDW); x0 = ldg_rlx2x64(xp); x1 = ldg_rlx2x64(xp + 512); }
        int n = 0;
        while (true) {
            const bool b0 = max(x0.x, x0.z) == SENT, b1 = max(x1.x, x1.z) == SENT;
            if (!__any_sync(~0u, b0 | b1)) break;
            if (b0) x0 = ldg_rlx2x64(xp);
            if (b1) x1 = ldg_rlx2x64(xp + 512);
            if (++n > SPIN_MAX) __trap();
        }
        float q0[4] = {}, q1[4] = {}, ag[2][4] = {}, au[2][4] = {};
        {
            mma(q0, x0.x, ONE2, x0.y, ONE2, x0.x, x0.y); mma(q1, x0.z, ONE2, x0.w, ONE2, x0.z, x0.w);
            mma(q0, x1.x, ONE2, x1.y, ONE2, x1.x, x1.y); mma(q1, x1.z, ONE2, x1.w, ONE2, x1.z, x1.w);
#pragma unroll
            for (int j = 0; j < 4; j++) {
                const uint4 xv = (j & 1) ? x1 : x0; const float4 a = c1[j & 1];
                const uint32_t h0 = mul2(j >> 1 ? xv.z : xv.x, __float_as_uint(j >> 1 ? a.z : a.x)), h1 = mul2(j >> 1 ? xv.w : xv.y, __float_as_uint(j >> 1 ? a.w : a.y));
                mma(ag[j & 1], wg[j], h0, h1); mma(au[j & 1], wu[j], h0, h1);
            }
        }
        sts64(so, odd ? q0[3] + q1[3] : q0[2] + q1[2], odd ? q0[1] + q1[1] : q0[0] + q1[0]);
        sts128f(po, ag[0][0] + ag[1][0], ag[0][2] + ag[1][2], au[0][0] + au[1][0], au[0][2] + au[1][2]);
        sts128f(po + 16, ag[0][1] + ag[1][1], ag[0][3] + ag[1][3], au[0][1] + au[1][1], au[0][3] + au[1][3]);
        bar_arrive<B_FIN, NALL>();
    } else if (rid >= DN0) {
        const int f = rid - DN0;
        uint32_t wd[12][4];
        const char* const hp0 = pin(X + blk(X_HM, 0, side) + w * 512 + lane * 16);
        const char* const hp1 = pin(X + blk(X_HM, 1, side) + w * 512 + lane * 16);
        auto hm = [&](int j) { return ldg_rlx128((j & 1 ? hp1 : hp0) + (j >> 1) * 16384); };
        __nv_bfloat16* const op = pin(P.out + ((tid >> 4) & 7) * DM + f * 16 + (tid & 15));
        const uint32_t po = pin(myscr + SC_DN + t * 160 + g * 16), pi = pin(scr + SC_DN + (w & 3) * 160 + (tid & 7) * 16 + (tid & 8) + ((tid >> 4) & 1) * 4), gi = pin(sb + SM_MN + tid * 2), first = pin(w < 4);
        uint4 hv[6]; int n = 0;
        auto first_poll = [&]() {
            spin(clock(), w * HDW);
#pragma unroll
            for (int j = 0; j < 6; j++) hv[j] = (j < 5 || w < 3) ? hm(j) : make_uint4(0, 0, 0, 0);
        };
        const bool early = go_first(sb + SM_BT, 0);
        if (early) { first_poll(); mbar_wait(sb + SM_BT, 0); }
#pragma unroll
        for (int j = 0; j < 12; j++)
            if (j < 10 || w < 3) ldsm_t(wd[j], sb + 2 * REG + 16384 + (w + (j >> 1) * 8) * 1024 + (j & 1) * 512 + (((lane >> 1) & 1) + (lane & 1) * 2 + (lane & 4) + (lane >> 4) * 8) * 32 + ((lch ^ ((lane >> 2) & 1)) << 4));
            else wd[j][0] = wd[j][1] = wd[j][2] = wd[j][3] = 0;
        if (!early) { mbar_wait(sb + SM_BG, 0); first_poll(); }
        while (true) {
            unsigned m[6];
#pragma unroll
            for (int j = 0; j < 6; j++) m[j] = max(max(hv[j].x, hv[j].y), max(hv[j].z, hv[j].w));
            if (__all_sync(~0u, max(max(max(m[0], m[1]), m[2]), max(max(m[3], m[4]), m[5])) != SENT)) break;
#pragma unroll
            for (int j = 0; j < 6; j++) if (m[j] == SENT) hv[j] = hm(j);
            if (++n > SPIN_MAX) __trap();
        }
        float d[4][4] = {};
#pragma unroll
        for (int j = 0; j < 6; j++) { mma(d[(2 * j) & 3], wd[2 * j], hv[j].x, hv[j].y); mma(d[(2 * j + 1) & 3], wd[2 * j + 1], hv[j].z, hv[j].w); }
        sts128f(po, (d[0][0] + d[1][0]) + (d[2][0] + d[3][0]), (d[0][1] + d[1][1]) + (d[2][1] + d[3][1]), (d[0][2] + d[1][2]) + (d[2][2] + d[3][2]), (d[0][3] + d[1][3]) + (d[2][3] + d[3][3]));
        bar_sync<B_DN, NTHR>();
        if (first) {
            float v[8];
#pragma unroll
            for (int i = 0; i < 8; i++) v[i] = lds32(pi + i * SCR);
            unsigned gw, res;
            asm volatile("ld.shared.u16 %0, [%1];" : "=r"(gw) : "r"(gi) : "memory"); asm volatile("ld.shared.u16 %0, [%1];" : "=r"(res) : "r"(gi + 256) : "memory");
            asm volatile("st.global.u16 [%0], %1;" :: "l"(op), "h"((unsigned short)add2(res, mul2(gw, pack2(((v[0] + v[1]) + (v[2] + v[3])) + ((v[4] + v[5]) + (v[6] + v[7])), 0.f)))) : "memory");
        }
    }
}

typedef CUresult (*EncodeFn)(CUtensorMap*, CUtensorMapDataType, cuuint32_t, void*, const cuuint64_t*, const cuuint64_t*, const cuuint32_t*,
                             const cuuint32_t*, CUtensorMapInterleave, CUtensorMapSwizzle, CUtensorMapL2promotion, CUtensorMapFloatOOBfill);

void make2d(EncodeFn enc, CUtensorMap* m, const void* p, int rows, int cols, int brows, int bcols, CUtensorMapSwizzle sw) {
    cuuint64_t dims[2] = {(cuuint64_t)cols, (cuuint64_t)rows}, strides[1] = {(cuuint64_t)cols * 2};
    cuuint32_t box[2] = {(cuuint32_t)bcols, (cuuint32_t)brows}, es[2] = {1, 1};
    enc(m, CU_TENSOR_MAP_DATA_TYPE_BFLOAT16, 2, (void*)p, dims, strides, box, es, CU_TENSOR_MAP_INTERLEAVE_NONE, sw,
        CU_TENSOR_MAP_L2_PROMOTION_L2_128B, CU_TENSOR_MAP_FLOAT_OOB_FILL_NONE);
}
void make5d(EncodeFn enc, CUtensorMap* m, const void* p, int cols, const unsigned (&n)[4], const unsigned (&s)[4], unsigned nb) {
    const cuuint64_t rs = (cuuint64_t)cols * 2;
    cuuint64_t dims[5] = {(cuuint64_t)cols, n[0], n[1], n[2], n[3]}, strides[4] = {rs * s[0], rs * s[1], rs * s[2], rs * s[3]};
    cuuint32_t box[5] = {16, n[0], n[1], n[2], nb}, es[5] = {1, 1, 1, 1, 1};
    enc(m, CU_TENSOR_MAP_DATA_TYPE_BFLOAT16, 5, (void*)p, dims, strides, box, es, CU_TENSOR_MAP_INTERLEAVE_NONE, CU_TENSOR_MAP_SWIZZLE_32B,
        CU_TENSOR_MAP_L2_PROMOTION_L2_128B, CU_TENSOR_MAP_FLOAT_OOB_FILL_NONE);
}
void makekv(EncodeFn enc, CUtensorMap* m, const void* p) {
    cuuint64_t dims[3] = {64, (cuuint64_t)NB * NH * SK, 2}, strides[2] = {256, 128};
    cuuint32_t box[3] = {64, 16, 2}, es[3] = {1, 1, 1};
    enc(m, CU_TENSOR_MAP_DATA_TYPE_BFLOAT16, 3, (void*)p, dims, strides, box, es, CU_TENSOR_MAP_INTERLEAVE_NONE, CU_TENSOR_MAP_SWIZZLE_128B,
        CU_TENSOR_MAP_L2_PROMOTION_NONE, CU_TENSOR_MAP_FLOAT_OOB_FILL_NONE);
}

}

extern "C" void kernel_launch(void* const* d_in, const int* in_sizes, int n_in, void* d_out, int out_size) {
    (void)in_sizes; (void)n_in; (void)out_size;
    static EncodeFn enc = nullptr;
    static void* raw = nullptr;
    if (!enc) {
        void* fn = nullptr; cudaDriverEntryPointQueryResult qr;
        cudaGetDriverEntryPoint("cuTensorMapEncodeTiled", &fn, cudaEnableDefault, &qr);
        enc = (EncodeFn)fn;
        cudaFuncSetAttribute(fused_kernel, cudaFuncAttributeMaxDynamicSharedMemorySize, SM_TOTAL);
        cudaGetSymbolAddress(&raw, g_raw);
    }
    Params P;
    makekv(enc, &P.k, d_in[1]);
    makekv(enc, &P.v, d_in[2]);
    make2d(enc, &P.wq, d_in[3], DM, NH * DH, 64, 32, CU_TENSOR_MAP_SWIZZLE_64B);
    make2d(enc, &P.wo, d_in[4], NH * DH, DM, 32, 64, CU_TENSOR_MAP_SWIZZLE_128B);
    make2d(enc, &P.wm, d_in[10], DM, 6 * DM, 256, 8, CU_TENSOR_MAP_SWIZZLE_NONE);
    make2d(enc, &P.wn, d_in[10], DM, 6 * DM, 256, 16, CU_TENSOR_MAP_SWIZZLE_32B);
    make5d(enc, &P.wg, d_in[6], FF, {4, 2, 4, 16}, {1, 16, 4, 32}, 4);
    make5d(enc, &P.wu, d_in[7], FF, {4, 2, 4, 16}, {1, 16, 4, 32}, 4);
    make5d(enc, &P.wd, d_in[8], DM, {8, 4, 1, 43}, {4, 1, 1, 32}, 43);
    P.out = (__nv_bfloat16*)d_out;
    typedef const __nv_bfloat16* W;
    fused_kernel<<<NCTA, NALL, SM_TOTAL>>>((W)d_in[0], (W)d_in[9], (W)d_in[1], (W)d_in[10], (W)d_in[3], (char*)(((size_t)raw + X_ALIGN - 1) & ~(size_t)(X_ALIGN - 1)), P);
}
```

```cpp
#include <cuda_runtime.h>
#include <cuda_bf16.h>
#include <cuda.h>
#include <stdint.h>

namespace {

constexpr int NB = 8, DM = 512, NH = 32, DH = 128, SK = 4096, WIN = 1024, FF = 1376;
constexpr int NCTA = 128, NTHR = 288, NALL = 320;
constexpr int NT = 16;
constexpr int NF1 = 86, DN0 = 96;
constexpr unsigned SENT = 0xFFFFFFFFu;
constexpr int SPIN_MAX = 1 << 20;

constexpr int PWIN0 = 12;
constexpr int PWIN = 16;
constexpr int PSW = 22;
constexpr int NTRK = 8;
constexpr int PFK = 2;
constexpr int QN = 7;
constexpr int TAU = 166;
constexpr int ANCH0 = 176;
constexpr int LEAD = 1600;
constexpr int PACE0 = 7000;
constexpr int PNAP = 200;
constexpr int WOA_ISSUE = 3;
constexpr int WO_GAP = 2;
constexpr int WOA_READ = 8;
constexpr int WJ = 4;
constexpr int WO0 = 520;
constexpr int WOS = 35;
constexpr int W0 = 880;
constexpr int WS = 200;
constexpr int WD0 = 1800;
constexpr int RT0 = 1850;
constexpr int HD0 = 1000;
constexpr int XDW = 30;
constexpr int HDW = 45;
constexpr int XC = 2;

constexpr unsigned WO_ITS = 1u << WOA_ISSUE | 1u << (WOA_ISSUE + WO_GAP) | 1u << (WOA_READ + 1);

constexpr int UNIT = 4096, REG = 8 * UNIT;
constexpr int SM_SCR = 6 * REG;
constexpr int SCR = 2048;
constexpr int SM_MN = SM_SCR + 8 * SCR;
constexpr int SM_SC = SM_MN + 8192;
constexpr int SM_BAR = SM_SC + 8192;
constexpr int SM_BM = SM_BAR + 512, SM_BT = SM_BM + 8, SM_BN = SM_BM + 16, SM_BG = SM_BM + 24;
constexpr int SM_AN = SM_BM + 32, SM_SIDE = SM_BM + 36, SM_TAG = SM_BM + 40, SM_MASK = SM_BM + 44;
constexpr int SM_ST = SM_BAR + 576;
constexpr int SM_ML = SM_ST + 512;
constexpr int SM_PR = SM_ML + 96;
constexpr int SM_TOTAL = SM_PR + 512;
constexpr int SC_M = 0, SC_Q = 256;
constexpr int SC_F1 = 0, SC_DN = 0, SC_RX = 1536;
constexpr int B_INIT = 0, B_ALL = 2, B_MOD = 3, B_WQ = 4, B_LAST = 5, B_RDY = 6, B_DN = 7, B_PRE = 8, B_FIN = 9, B_STG = 10, B_SIDE = 11, B_Q = 12, B_ML = 13;

constexpr unsigned HOME = 0xB3000;
constexpr int X_PART = 0;
constexpr int X_Q = 0x100000;
constexpr int X_M1 = 0x140000;
constexpr int X_X1 = 0x150000;
constexpr int X_HM = 0x160000;
constexpr int X_MOD = 0x170000;
constexpr int X_SIDE = 0x176000;
constexpr int X_EPOCH = 0x176400;
constexpr int X_READY = 0x176480;
constexpr int X_LAG = 0x178000;
constexpr int X_ANC = 0x158000;
constexpr int X_PRB = 0x180000;
constexpr int X_ALIGN = 0x200000;
static_assert(XC == 2, "one store writes all copies of x1");
__device__ uint4 g_raw[2 * X_ALIGN / 16];
__device__ __forceinline__ unsigned blk(unsigned base, unsigned k, unsigned s) { const unsigned o = base + k * 8192; return o + ((__popc(o & HOME) ^ s) & 1) * 4096; }

struct Params {
    CUtensorMap wm, wq, k, v, wn, wo, wg, wu, wd;
    __nv_bfloat16* out;
};

__device__ __forceinline__ int tile_key(int i) { return (i & 1) * 128 + (i & 2) * 32 + (i & 12) * 64; }

__device__ __forceinline__ uint32_t smem_u32(const void* p) { return (uint32_t)__cvta_generic_to_shared(p); }
__device__ __forceinline__ void mbar_init(uint32_t a, uint32_t c) { asm volatile("mbarrier.init.shared::cta.b64 [%0], %1;" :: "r"(a), "r"(c) : "memory"); }
__device__ __forceinline__ void mbar_expect(uint32_t a, uint32_t b) { asm volatile("mbarrier.arrive.expect_tx.shared::cta.b64 _, [%0], %1;" :: "r"(a), "r"(b) : "memory"); }
__device__ __forceinline__ void mbar_wait(uint32_t a, uint32_t par) {
    uint32_t ok; int n = 0;
    do {
        asm volatile("{\n.reg .pred p;\nmbarrier.try_wait.parity.shared::cta.b64 p, [%1], %2, 2000;\nselp.u32 %0, 1, 0, p;\n}" : "=r"(ok) : "r"(a), "r"(par) : "memory");
        if (++n > SPIN_MAX) __trap();
    } while (!ok);
}
__device__ __forceinline__ bool mbar_test(uint32_t a, uint32_t par) {
    uint32_t ok; asm volatile("{\n.reg .pred p;\nmbarrier.test_wait.parity.shared::cta.b64 p, [%1], %2;\nselp.u32 %0, 1, 0, p;\n}" : "=r"(ok) : "r"(a), "r"(par) : "memory"); return ok;
}
__device__ __forceinline__ void tma2d(uint32_t dst, const CUtensorMap* m, int x, int y, uint32_t bar) {
    asm volatile("cp.async.bulk.tensor.2d.shared::cluster.global.mbarrier::complete_tx::bytes [%0], [%1, {%3, %4}], [%2];"
                 :: "r"(dst), "l"(m), "r"(bar), "r"(x), "r"(y) : "memory");
}
__device__ __forceinline__ void tma5d(uint32_t dst, const CUtensorMap* m, int x, int y, uint32_t bar) {
    asm volatile("cp.async.bulk.tensor.5d.shared::cluster.global.mbarrier::complete_tx::bytes [%0], [%1, {%3, 0, 0, 0, %4}], [%2];"
                 :: "r"(dst), "l"(m), "r"(bar), "r"(x), "r"(y) : "memory");
}
__device__ __forceinline__ void tma_kv(uint32_t dst, const CUtensorMap* m, int row, uint32_t bar, uint64_t pol) {
    asm volatile("cp.async.bulk.tensor.3d.shared::cluster.global.mbarrier::complete_tx::bytes.L2::cache_hint [%0], [%1, {0, %3, 0}], [%2], %4;"
                 :: "r"(dst), "l"(m), "r"(bar), "r"(row), "l"(pol) : "memory");
}
__device__ __forceinline__ void pf_bulk(const void* p, uint32_t n) { asm volatile("cp.async.bulk.prefetch.L2.global [%0], %1;" :: "l"(p), "r"(n) : "memory"); }
__device__ __forceinline__ void pf_if(const void* p, unsigned i, unsigned n) { asm volatile("{\n.reg .pred p;\nsetp.lt.u32 p, %1, %2;\n@p prefetch.global.L2 [%0];\n}" :: "l"(p), "r"(i), "r"(n) : "memory"); }
__device__ __forceinline__ uint4 ldg_nc(const void* p) { uint4 v; asm volatile("ld.global.nc.v4.u32 {%0,%1,%2,%3}, [%4];" : "=r"(v.x), "=r"(v.y), "=r"(v.z), "=r"(v.w) : "l"(p)); return v; }
__device__ __forceinline__ bool elect() { uint32_t p; asm volatile("{\n.reg .pred p;\nelect.sync _|p, -1;\nselp.u32 %0, 1, 0, p;\n}" : "=r"(p)); return p; }
__device__ __forceinline__ void pf_map(const CUtensorMap* m) { asm volatile("prefetch.tensormap [%0];" :: "l"(m) : "memory"); }
__device__ __forceinline__ void ldsm(uint32_t (&r)[4], uint32_t a) {
    asm volatile("ldmatrix.sync.aligned.m8n8.x4.shared.b16 {%0,%1,%2,%3}, [%4];" : "=r"(r[0]), "=r"(r[1]), "=r"(r[2]), "=r"(r[3]) : "r"(a) : "memory");
}
__device__ __forceinline__ void ldsm_t(uint32_t (&r)[4], uint32_t a) {
    asm volatile("ldmatrix.sync.aligned.m8n8.x4.trans.shared.b16 {%0,%1,%2,%3}, [%4];" : "=r"(r[0]), "=r"(r[1]), "=r"(r[2]), "=r"(r[3]) : "r"(a) : "memory");
}
__device__ __forceinline__ void mma(float (&c)[4], uint32_t a0, uint32_t a1, uint32_t a2, uint32_t a3, uint32_t b0, uint32_t b1) {
    asm("mma.sync.aligned.m16n8k16.row.col.f32.bf16.bf16.f32 {%0,%1,%2,%3}, {%4,%5,%6,%7}, {%8,%9}, {%0,%1,%2,%3};"
        : "+f"(c[0]), "+f"(c[1]), "+f"(c[2]), "+f"(c[3]) : "r"(a0), "r"(a1), "r"(a2), "r"(a3), "r"(b0), "r"(b1));
}
__device__ __forceinline__ void mma(float (&c)[4], const uint32_t (&a)[4], uint32_t b0, uint32_t b1) { mma(c, a[0], a[1], a[2], a[3], b0, b1); }
__device__ __forceinline__ uint32_t pin(uint32_t v) { asm volatile("shfl.sync.bfly.b32 %0, %0, 0, 31, -1;" : "+r"(v)); return v; }
template <class T> __device__ __forceinline__ T* pin(T* p) { const size_t a = (size_t)p; return (T*)(pin((uint32_t)a) | (size_t)pin((uint32_t)(a >> 32)) << 32); }
__device__ __forceinline__ void mmav(float (&c)[4], const uint32_t (&a)[4], uint32_t b0, uint32_t b1) {
    asm volatile("mma.sync.aligned.m16n8k16.row.col.f32.bf16.bf16.f32 {%0,%1,%2,%3}, {%4,%5,%6,%7}, {%8,%9}, {%0,%1,%2,%3};"
        : "+f"(c[0]), "+f"(c[1]), "+f"(c[2]), "+f"(c[3]) : "r"(a[0]), "r"(a[1]), "r"(a[2]), "r"(a[3]), "r"(b0), "r"(b1));
}
__device__ __forceinline__ uint32_t movm(uint32_t a) { uint32_t r; asm volatile("movmatrix.sync.aligned.m8n8.trans.b16 %0, %1;" : "=r"(r) : "r"(a)); return r; }
__device__ __forceinline__ uint32_t pack2(float lo, float hi) { uint32_t r; asm("cvt.rn.bf16x2.f32 %0, %1, %2;" : "=r"(r) : "f"(hi), "f"(lo)); return r; }
__device__ __forceinline__ float blo(uint32_t w) { return __uint_as_float(w << 16); }
__device__ __forceinline__ float bhi(uint32_t w) { return __uint_as_float(w & 0xFFFF0000u); }
__device__ __forceinline__ float rbf(float x) { return blo(pack2(x, 0.f)); }
__device__ __forceinline__ uint32_t add2(uint32_t a, uint32_t b) { uint32_t r; asm("add.rn.bf16x2 %0, %1, %2;" : "=r"(r) : "r"(a), "r"(b)); return r; }
__device__ __forceinline__ uint32_t sub2(uint32_t a, uint32_t b) { uint32_t r; asm("sub.rn.bf16x2 %0, %1, %2;" : "=r"(r) : "r"(a), "r"(b)); return r; }
__device__ __forceinline__ uint32_t mul2(uint32_t a, uint32_t b) { uint32_t r; asm("mul.rn.bf16x2 %0, %1, %2;" : "=r"(r) : "r"(a), "r"(b)); return r; }
constexpr uint32_t ONE2 = 0x3F803F80u;
constexpr float LOG2E = 1.4426950408889634f, SCALE = 0.08838834764831845f;
__device__ __forceinline__ float ex2(float x) { float y; asm("ex2.approx.ftz.f32 %0, %1;" : "=f"(y) : "f"(x)); return y; }
__device__ __forceinline__ uint4 ldg_rlx128(const void* p) {
    uint4 v; asm volatile("ld.relaxed.gpu.global.v4.u32 {%0,%1,%2,%3}, [%4];" : "=r"(v.x), "=r"(v.y), "=r"(v.z), "=r"(v.w) : "l"(p) : "memory"); return v;
}
__device__ __forceinline__ uint4 ldg_rlx2x64(const void* p) {
    unsigned long long a, b; asm volatile("ld.relaxed.gpu.global.v2.u64 {%0,%1}, [%2];" : "=l"(a), "=l"(b) : "l"(p) : "memory");
    return make_uint4((unsigned)a, (unsigned)(a >> 32), (unsigned)b, (unsigned)(b >> 32));
}
__device__ __forceinline__ uint2 ldg_rlx64(const void* p) {
    unsigned long long a; asm volatile("ld.relaxed.gpu.global.u64 %0, [%1];" : "=l"(a) : "l"(p) : "memory"); return make_uint2((unsigned)a, (unsigned)(a >> 32));
}
__device__ __forceinline__ unsigned ldg_acq32(const void* p) { unsigned v; asm volatile("ld.acquire.gpu.global.u32 %0, [%1];" : "=r"(v) : "l"(p) : "memory"); return v; }
__device__ __forceinline__ void red_add(void* p, unsigned v) { asm volatile("red.relaxed.gpu.global.add.u32 [%0], %1;" :: "l"(p), "r"(v) : "memory"); }
__device__ __forceinline__ unsigned now_ns() { unsigned t; asm volatile("mov.u32 %0, %%globaltimer_lo;" : "=r"(t)); return t; }
__device__ __forceinline__ void nap(unsigned ns) { asm volatile("nanosleep.u32 %0;" :: "r"(ns)); }
__device__ __forceinline__ unsigned ldg_rlx32(const void* p) { unsigned v; asm volatile("ld.relaxed.gpu.global.u32 %0, [%1];" : "=r"(v) : "l"(p) : "memory"); return v; }
__device__ __forceinline__ void stg_rlx32(void* p, unsigned v) { asm volatile("st.relaxed.gpu.global.u32 [%0], %1;" :: "l"(p), "r"(v) : "memory"); }
__device__ __forceinline__ void stg_rlx16(void* p, unsigned v) { asm volatile("st.relaxed.gpu.global.u16 [%0], %1;" :: "l"(p), "h"((unsigned short)v) : "memory"); }
__device__ __forceinline__ uint4 ldg_b128(const void* p) {
    unsigned long long a, b; asm volatile("{\n.reg .b128 x;\nld.relaxed.gpu.global.b128 x, [%2];\nmov.b128 {%0,%1}, x;\n}" : "=l"(a), "=l"(b) : "l"(p) : "memory");
    return make_uint4((unsigned)a, (unsigned)(a >> 32), (unsigned)b, (unsigned)(b >> 32));
}
__device__ __forceinline__ void stg_b128(void* p, uint4 v) {
    asm volatile("{\n.reg .b128 x;\nmov.b128 x, {%1,%2};\nst.relaxed.gpu.global.b128 [%0], x;\n}" :: "l"(p), "l"(v.x | ((unsigned long long)v.y << 32)), "l"(v.z | ((unsigned long long)v.w << 32)) : "memory");
}
__device__ __forceinline__ int rowoff(int b, int c) { return ((c >> 6) * 2 + ((c >> 2) & 1)) * 512 + b * 64 + (c & 3) * 16 + ((c >> 3) & 1) * 8 + ((c >> 5) & 1) * 4 + ((c >> 4) & 1) * 2; }
__device__ __forceinline__ void stg_rlx64(void* p, unsigned lo, unsigned hi) {
    unsigned long long a = lo | ((unsigned long long)hi << 32); asm volatile("st.relaxed.gpu.global.u64 [%0], %1;" :: "l"(p), "l"(a) : "memory");
}
__device__ __forceinline__ void stg_rlx128(void* p, uint4 v) { asm volatile("st.relaxed.gpu.global.v4.u32 [%0], {%1,%2,%3,%4};" :: "l"(p), "r"(v.x), "r"(v.y), "r"(v.z), "r"(v.w) : "memory"); }
__device__ __forceinline__ void sts32u(uint32_t a, unsigned x) { asm volatile("st.volatile.shared.u32 [%0], %1;" :: "r"(a), "r"(x) : "memory"); }
__device__ __forceinline__ unsigned lds32u(uint32_t a) { unsigned v; asm volatile("ld.volatile.shared.u32 %0, [%1];" : "=r"(v) : "r"(a) : "memory"); return v; }
__device__ __forceinline__ void spin(unsigned c0, unsigned d) { if (d) while ((unsigned)clock() - c0 < d) {} }
__device__ __forceinline__ void fence_gpu() { asm volatile("fence.acq_rel.gpu;" ::: "memory"); }
template <int ID, int N> __device__ __forceinline__ void bar_sync() { asm volatile("bar.sync %0, %1;" :: "n"(ID), "n"(N) : "memory"); }
template <int ID, int N> __device__ __forceinline__ void bar_arrive() { asm volatile("bar.arrive %0, %1;" :: "n"(ID), "n"(N) : "memory"); }
__device__ __forceinline__ void sts64(uint32_t a, float x, float y) { asm volatile("st.shared.v2.f32 [%0], {%1,%2};" :: "r"(a), "f"(x), "f"(y) : "memory"); }
__device__ __forceinline__ void sts128(uint32_t a, uint4 v) { asm volatile("st.volatile.shared.v4.u32 [%0], {%1,%2,%3,%4};" :: "r"(a), "r"(v.x), "r"(v.y), "r"(v.z), "r"(v.w) : "memory"); }
__device__ __forceinline__ void sts128f(uint32_t a, float x, float y, float z, float w) { asm volatile("st.volatile.shared.v4.f32 [%0], {%1,%2,%3,%4};" :: "r"(a), "f"(x), "f"(y), "f"(z), "f"(w) : "memory"); }
__device__ __forceinline__ void sts32(uint32_t a, float x) { asm volatile("st.shared.f32 [%0], %1;" :: "r"(a), "f"(x) : "memory"); }
__device__ __forceinline__ float2 lds64(uint32_t a) { float2 v; asm volatile("ld.shared.v2.f32 {%0,%1}, [%2];" : "=f"(v.x), "=f"(v.y) : "r"(a) : "memory"); return v; }
__device__ __forceinline__ float lds32(uint32_t a) { float v; asm volatile("ld.shared.f32 %0, [%1];" : "=f"(v) : "r"(a) : "memory"); return v; }
__device__ __forceinline__ float4 lds128(uint32_t a) { float4 v; asm volatile("ld.shared.v4.f32 {%0,%1,%2,%3}, [%4];" : "=f"(v.x), "=f"(v.y), "=f"(v.z), "=f"(v.w) : "r"(a) : "memory"); return v; }
__device__ __forceinline__ float2 sum8(uint32_t a) {
    float2 v[8];
#pragma unroll
    for (int i = 0; i < 8; i++) v[i] = lds64(a + i * SCR);
    return make_float2(((v[0].x + v[1].x) + (v[2].x + v[3].x)) + ((v[4].x + v[5].x) + (v[6].x + v[7].x)),
                       ((v[0].y + v[1].y) + (v[2].y + v[3].y)) + ((v[4].y + v[5].y) + (v[6].y + v[7].y)));
}
template <int STRIDE> __device__ __forceinline__ float4 sum8x4(uint32_t a) {
    float4 v[8];
#pragma unroll
    for (int i = 0; i < 8; i++) v[i] = lds128(a + i * STRIDE);
    return make_float4(((v[0].x + v[1].x) + (v[2].x + v[3].x)) + ((v[4].x + v[5].x) + (v[6].x + v[7].x)), ((v[0].y + v[1].y) + (v[2].y + v[3].y)) + ((v[4].y + v[5].y) + (v[6].y + v[7].y)),
                       ((v[0].z + v[1].z) + (v[2].z + v[3].z)) + ((v[4].z + v[5].z) + (v[6].z + v[7].z)), ((v[0].w + v[1].w) + (v[2].w + v[3].w)) + ((v[4].w + v[5].w) + (v[6].w + v[7].w)));
}
__device__ __forceinline__ float rcp(float x) { float y; asm("rcp.approx.ftz.f32 %0, %1;" : "=f"(y) : "f"(x)); return y; }
__device__ __forceinline__ float sigmoid_f(float x) { return rcp(1.0f + ex2(x * -LOG2E)); }
__device__ __forceinline__ uint32_t silu2(uint32_t c) { const float a = blo(c), b = bhi(c); return pack2(a * sigmoid_f(a), b * sigmoid_f(b)); }
__device__ __forceinline__ void ln_consts(float mean, float var, uint32_t& mu2, float& rs) {
    mu2 = pack2(mean, mean);
    float sd; asm("sqrt.approx.ftz.f32 %0, %1;" : "=f"(sd) : "f"(rbf(rbf(var) + 1e-5f)));
    rs = rcp(rbf(sd));
}
__device__ __forceinline__ uint32_t ln_norm(uint32_t x2, uint32_t mu2, float rs) { const uint32_t d = sub2(x2, mu2); return pack2(blo(d) * rs, bhi(d) * rs); }

__global__ void __launch_bounds__(NALL, 1) fused_kernel(const __nv_bfloat16* const px, const __nv_bfloat16* const pc, const __nv_bfloat16* const pk, const __nv_bfloat16* const pwm,
                                                        const __nv_bfloat16* const pwq, char* const X, const __grid_constant__ Params P) {
    extern __shared__ __align__(1024) unsigned char smem[];
    const uint32_t sb = smem_u32(smem);
    const int tid = threadIdx.x, w = tid >> 5, lane = tid & 31, g = lane >> 2, t = lane & 3;
    const int cta = blockIdx.x, head = cta >> 2, bat = (cta & 3) * 2 + (w >> 2);
    const uint32_t s0 = sb + w * UNIT, s2 = s0 + 4 * REG;
    const uint32_t bar0 = sb + SM_BAR + w * 64;
    const uint32_t barC = bar0 + 32;
    const uint32_t scr = sb + SM_SCR, myscr = scr + w * SCR;
    pf_if((const char*)pwm + ((cta * 4 + (lane >> 3)) * (6 * DM * 2) + w * 1024 + (lane & 7) * 128), w, 5);
    pf_if((const char*)pk + (unsigned)(((((cta & 3) * 2 + (w & 1)) * NH + head) * SK + (SK - WIN - 48) + tile_key(2) + (w >> 1) * 16) * (DH * 2) + lane * 128), w - 6, PFK);
    const int rid = !(cta & 1) ? cta >> 1 : (cta >> 2) + (cta & 2 ? 64 : 96);
    const unsigned t_start = now_ns();
    uint64_t pol;
    asm volatile("createpolicy.fractional.L2::evict_first.b64 %0, 1.0;" : "=l"(pol));
    auto go_first = [&](uint32_t wbar, uint32_t par) {
        for (int n = 0;; n++) {
            if (__all_sync(~0u, mbar_test(wbar, par))) return false;
            if (__all_sync(~0u, mbar_test(sb + SM_BG, 0))) return true;
            if (n > SPIN_MAX * 4) __trap();
            nap(20);
        }
    };
    if (w == 9) {
        const uint32_t sl = sb + SM_PR + lane * 16;
        char* const pl = X + blk(X_PRB, cta >> 1, lane & 1) + (lane >> 1) * 256 + (cta & 1) * 128;
        {
            char* const ps = X + X_PRB + (cta >> 1) * 8192 + g * 256 + (cta & 1) * 128 + t * 16;
            sts32u(sl, 0);
#pragma unroll
            for (int i = 0; i < 4; i++) stg_rlx128(ps + i * 2048, make_uint4(1, 1, 1, 1));
            __syncwarp();
        }
        unsigned v; asm volatile("atom.relaxed.gpu.global.add.u32 %0, [%1], 1;" : "=r"(v) : "l"(pl) : "memory");
        unsigned tag = ldg_rlx32(X + X_EPOCH);
        if (lane == 0) pf_bulk(pwq + (size_t)cta * QN * 1024, QN * 2048);
        if (lane == 0) sts32u(sb + SM_AN, t_start + ANCH0);
        if (lane < 8) sts32u(sb + SM_BAR + lane * 64 + 56, 0);
        unsigned side;
        {
            int d, n = 0;
#pragma unroll 1
            for (int r = 0; r < 4; r++) {
                if (v == SENT) __trap();
                asm volatile("cp.async.cg.shared.global [%0], [%1], 16;" :: "r"(sl), "l"(pl) : "memory");
                unsigned m;
                do {
                    m = __ballot_sync(~0u, lds32u(sl));
                    d = __popc(m & 0xAAAAAAAAu) - __popc(m & 0x55555555u);
                    if (++n > SPIN_MAX) __trap();
                } while (abs(d) < 6 && m != ~0u);
                if (abs(d) >= 6) break;
                asm volatile("cp.async.wait_all;" ::: "memory");
                sts32u(sl, 0);
                asm volatile("atom.relaxed.gpu.global.add.u32 %0, [%1], 1;" : "=r"(v) : "l"(pl) : "memory");
            }
            side = d > 0;
            tag++;
            if (lane == 0) { sts32u(sb + SM_SIDE, side); sts32u(sb + SM_TAG, tag); }
            bar_arrive<B_SIDE, NTHR>();
        }
        asm volatile("cp.async.wait_all;" ::: "memory");
        while (now_ns() - t_start < PACE0) nap(200);
        for (int n = 0; n < SPIN_MAX; n++) {
            const uint32_t wb = sb + SM_BAR + (lane & 7) * 64;
            const unsigned seen = lds32u(wb + 56), u = seen + ((lane >> 3) & 1), t1 = now_ns();
            const unsigned more = seen && mbar_test(wb + (u < 6 ? u : (~u & 2) + (u & 1)) * 8, u < 6 ? 0 : ((u - 2) >> 2) & 1);
            const unsigned lo = __reduce_min_sync(~0u, seen), sum = __reduce_add_sync(~0u, lane < 8 ? seen + more : lane < 16 ? more : 0);
            if (lo == 30) break;
            if (lo && lane < 2) stg_rlx64(X + X_LAG + (cta >> 5) * 8192 + lane * 4096 + (cta & 31) * 128, t1 - sum * TAU, tag);
            uint2 a = make_uint2(0, 0);
            if (cta == 0) {
                uint2 u[4];
#pragma unroll
                for (int i = 0; i < 4; i++) u[i] = ldg_rlx64(X + blk(X_LAG, i, side) + lane * 128);
                const int s = __reduce_add_sync(~0u, (int)(u[0].x + u[1].x + u[2].x + u[3].x - 4 * t_start));
                if (__all_sync(~0u, (u[0].y == tag) & (u[1].y == tag) & (u[2].y == tag) & (u[3].y == tag)) && lane < 2) {
                    a = make_uint2(t_start + s / NCTA, tag);
                    stg_rlx64(X + X_ANC + lane * 4096, a.x, tag);
                }
            } else if (lane == 0) a = ldg_rlx64(X + blk(X_ANC, 0, side));
            if (lane == 0 && a.y == tag) sts32u(sb + SM_AN, a.x - LEAD);
            __syncwarp();
            nap(PNAP);
        }
        {
            bar_sync<B_ML, NTHR>();
            const float2 ml = lds64(sb + SM_ML + (lane & 7) * 8);
            float M = fmaxf(ml.x, __shfl_xor_sync(~0u, ml.x, 1)); M = fmaxf(M, __shfl_xor_sync(~0u, M, 2));
            const float e = ex2((ml.x - M) * LOG2E);
            float L = e * ml.y; L += __shfl_xor_sync(~0u, L, 1); L += __shfl_xor_sync(~0u, L, 2);
            if (lane < 8) sts32(sb + SM_ML + 64 + lane * 4, e * rcp(L));
        }
        bar_arrive<B_RDY, NALL>();
        bar_sync<B_STG, 64>();
        {
            const char* const pp = pin(X + blk(X_PART, cta, side) + lane * 16);
            char* const xo = pin(X + (lane >> 4) * 16384 + blk(X_X1, (cta >> 3) & 1, lane >> 3) + (cta & 7) * 512 + (cta >> 4) * 64 + (lane & 7) * 8);
            const float4 gx = lds128(scr + SC_RX + (lane & 7) * 16);
            const unsigned t0 = lds32u(sb + SM_AN) + 256 * TAU + RT0 + (cta & 7) * (TAU / 8);
            while ((int)(now_ns() - t0) < 0) nap(20);
            uint4 v[8]; int n = 0;
            float a[4];
#pragma unroll
            for (int j = 0; j < 8; j++) v[j] = ldg_b128(pp + j * 512);
            while (true) {
#define RSUM(f) (((__uint_as_float(v[0].f) + __uint_as_float(v[1].f)) + (__uint_as_float(v[2].f) + __uint_as_float(v[3].f))) + ((__uint_as_float(v[4].f) + __uint_as_float(v[5].f)) + (__uint_as_float(v[6].f) + __uint_as_float(v[7].f))))
                const bool ok = __all_sync(~0u, max(max(max(v[0].x, v[1].x), max(v[2].x, v[3].x)), max(max(v[4].x, v[5].x), max(v[6].x, v[7].x))) != SENT);
                a[0] = RSUM(x); a[1] = RSUM(y); a[2] = RSUM(z); a[3] = RSUM(w);
                asm volatile("" : "+f"(a[0]), "+f"(a[1]), "+f"(a[2]), "+f"(a[3]));
                if (ok) break;
#pragma unroll
                for (int j = 0; j < 8; j++) if (v[j].x == SENT) v[j] = ldg_b128(pp + j * 512);
                if (++n > SPIN_MAX) __trap();
            }
#pragma unroll
            for (int i = 0; i < 4; i++) a[i] += __shfl_xor_sync(~0u, a[i], 8);
#pragma unroll
            for (int i = 0; i < 4; i++) a[i] += __shfl_xor_sync(~0u, a[i], 16);
            stg_rlx64(xo, add2(__float_as_uint(gx.z), mul2(__float_as_uint(gx.x), pack2(a[0], a[1]))), add2(__float_as_uint(gx.w), mul2(__float_as_uint(gx.y), pack2(a[2], a[3]))));
        }
        if (rid >= DN0) {
            const unsigned c1 = clock();
            const int f = rid - DN0;
            const char* const rp = X + (rid & (XC - 1)) * 16384 + blk(X_X1, f >> 4, side) + (rowoff(g, f * 16 + t * 4) & 4092);
            unsigned r[4]; int n = 0;
            spin(c1, HD0 - 450);
            do {
#pragma unroll
                for (int i = 0; i < 4; i++) r[i] = ldg_rlx32(rp + i * 16);
                if (++n > SPIN_MAX) __trap();
            } while (max(max(r[0], r[1]), max(r[2], r[3])) == SENT);
            const unsigned sel = (f & 1) ? 0x7632 : 0x5410;
            sts64(sb + SM_MN + 256 + lane * 8, __uint_as_float(__byte_perm(r[0], r[1], sel)), __uint_as_float(__byte_perm(r[2], r[3], sel)));
            __syncwarp();
            spin(c1, HD0);
        }
        if (lane == 0) asm volatile("mbarrier.arrive.shared::cta.b64 _, [%0];" :: "r"(sb + SM_BG) : "memory");
    } else if (w == 8) {
        const int row0 = ((cta & 3) * 2 * NH + head) * SK + (SK - WIN);
        auto kv_unit = [&](int u) {
            const uint32_t b = sb + SM_BAR + (u & 7) * 64 + (u >> 3) * 8;
            mbar_expect(b, UNIT);
            tma_kv(sb + (u >> 3) * REG + (u & 7) * UNIT, (u & 8) ? &P.v : &P.k, row0 + ((u >> 2) & 1) * NH * SK + (u & 3) * 16 + tile_key(u >> 4), b, pol);
        };
        if (elect()) {
            mbar_init(sb + SM_BM, 1);
#pragma unroll
            for (int i = 0; i < 8; i++) mbar_init(sb + SM_BAR + i * 64 + 48, 1);
            asm volatile("fence.mbarrier_init.release.cluster;" ::: "memory");
            mbar_expect(sb + SM_BM, 512 * 16);
            tma2d(sb + 4 * REG, &P.wm, cta * 8, 0, sb + SM_BM); tma2d(sb + 4 * REG + 256 * 16, &P.wm, cta * 8, 256, sb + SM_BM);
#pragma unroll
            for (int i = 0; i < 8; i++) { const uint32_t b = sb + SM_BAR + i * 64 + 48; mbar_expect(b, UNIT); tma2d(sb + 5 * REG + i * UNIT, &P.wq, cta * 32, i * 64, b); }
            mbar_init(sb + SM_BN, 1); mbar_init(sb + SM_BT, 1); mbar_init(sb + SM_BG, 1);
#pragma unroll
            for (int i = 0; i < 48; i++) mbar_init(sb + SM_BAR + (i & 7) * 64 + (i >> 3) * 8, 1);
            asm volatile("fence.mbarrier_init.release.cluster;" ::: "memory");
        }
        __syncwarp();
        bar_arrive<B_INIT, NTHR>();
        {
            uint32_t mine = lane >= NTRK ? 0 : lane < 8 ? sb + SM_BAR + lane * 64 + 48 : sb + SM_BM;
            int next = 0, lim = 32, n = 0;
            while (next < 48) {
                const bool idle = lane < (next < PSW ? PWIN0 : PWIN) && (mine == 0 || mbar_test(mine, 0));
                const unsigned m = __ballot_sync(~0u, idle);
                const int u = next + __popc(m & ((1u << lane) - 1));
                if (idle) {
                    mine = 0;
                    if (u < lim) { kv_unit(u); mine = sb + SM_BAR + (u & 7) * 64 + (u >> 3) * 8; }
                }
                next = min(next + __popc(m), lim);
                if (next == lim) {
                    if (lim == 32) { bar_sync<B_MOD, NTHR>(); } else if (lim == 40) { bar_sync<B_WQ, NTHR>(); }
                    lim += 8;
                }
                if (!m) nap(30);
                if (++n > SPIN_MAX) __trap();
            }
        }
        if (lane < 5) pf_map(&P.wn + lane);
        float m[4][4] = {};
        auto late_mod = [&](uint32_t a, int h) {
            const int lrow = (lane & 7) + ((lane >> 4) << 3), lch = (lane >> 3) & 1;
            const uint32_t a0 = a + lrow * 32 + ((lch ^ ((lrow >> 2) & 1)) << 4);
            const uint32_t c0 = sb + SM_SC + h * 4096 + (lane & 7) * 128 + (((lane >> 3) ^ (lane & 7)) << 4);
#pragma unroll
            for (int j = 0; j < 8; j++) {
                uint32_t c[4], r[4], u[4];
                ldsm(c, (c0 + (j >> 1) * 1024) ^ ((j & 1) << 6)); ldsm_t(r, a0 + j * 1024); ldsm_t(u, a0 + j * 1024 + 512);
                mma(m[(j & 1) * 2], r, c[0], c[1]); mma(m[(j & 1) * 2 + 1], u, c[2], c[3]);
            }
        };
        if (rid < 96) {
#pragma unroll 1
            for (int h = 0; h < 2; h++) {
                if (lane == 0) { mbar_expect(sb + SM_BN, 8192); tma2d(sb + SM_MN, &P.wn, 2 * DM + rid * 16, h * 256, sb + SM_BN); }
                mbar_wait(sb + SM_BN, h);
                late_mod(sb + SM_MN, h);
                asm volatile("" :: "f"(m[0][0]), "f"(m[1][0]), "f"(m[2][0]), "f"(m[3][0]) : "memory");
                __syncwarp();
            }
#pragma unroll
            for (int e = 0; e < 4; e++) {
                float v = rbf((m[0][e] + m[1][e]) + (m[2][e] + m[3][e]));
                if (rid >= 64) v += 1.0f;
                stg_rlx16(X + X_MOD + (rid >> 5) * 8192 + rowoff(2 * t + (e & 1), (rid & 31) * 16 + g + (e >> 1) * 8), pack2(v, 0.f));
            }
        }
        {
            const unsigned side = lds32u(sb + SM_SIDE);
#pragma unroll
            for (int i = 0; i < 8; i++) stg_rlx128(X + blk(X_PART, cta, side) + i * 512 + lane * 16, make_uint4(SENT, SENT, SENT, SENT));
            if (lane == 0) stg_rlx32(X + X_SIDE + cta * 4, side);
        }
        bar_sync<B_Q, NTHR>();
        if (lane == 0) {
            const unsigned tag = lds32u(sb + SM_TAG);
            fence_gpu();
            red_add(X + X_READY, 1);
            int n = 0;
            while ((int)(ldg_acq32(X + X_READY) - tag * NCTA) < 0) { nap(1000); if (++n > SPIN_MAX) __trap(); }
            if (cta == 0) stg_rlx32(X + X_EPOCH, tag);
        }
        __syncwarp();
        {
            stg_rlx128(X + blk(X_Q, head >> 1, 0) + (head & 1) * 2048 + g * 256 + (cta & 3) * 64 + t * 16, make_uint4(0, 0, 0, 0));
            stg_rlx128(X + blk(X_Q, head >> 1, 1) + (head & 1) * 2048 + g * 256 + (cta & 3) * 64 + t * 16, make_uint4(0, 0, 0, 0));
            stg_rlx64(X + blk(X_M1, cta >> 5, lane >> 4) + (cta & 31) * 128 + (lane & 15) * 8, 0, 0);
            const int wt = (cta & 3) * 32 + lane;
            const unsigned mask = __ballot_sync(~0u, blk(X_PART, wt, ldg_rlx32(X + X_SIDE + wt * 4)) & 4096);
            if (lane == 0) sts32u(sb + SM_MASK, mask);
            if (lane < 8) {
                const int rb = cta >> 4, c = ((cta & 15) >> 1) * 64 + (cta & 1) * 4 + (lane >> 1) + (lane & 1) * 8;
                const uint2 ga = ldg_rlx64(X + X_MOD + rowoff(rb, c));
                const unsigned short* const xp = (const unsigned short*)px + rb * DM + c;
                sts128(scr + SC_RX + lane * 16, make_uint4(ga.x, ga.y, xp[0] | (xp[16] << 16), xp[32] | (xp[48] << 16)));
            }
            if (rid < NF1) {
#pragma unroll 1
                for (int i = 0; i < 4; i++) {
                    uint4 v[8];
#pragma unroll
                    for (int j = 0; j < 8; j++) v[j] = ldg_rlx128(X + X_MOD + 8192 + (i * 8 + j) * 512 + lane * 16);
#pragma unroll
                    for (int j = 0; j < 8; j++) sts128(sb + SM_MN + (i * 8 + j) * 512 + lane * 16, v[j]);
                }
            }
        }
        bar_arrive<B_RDY, NALL>();
        bar_arrive<B_STG, 64>();
        for (int n = 0; __any_sync(~0u, lds32u(sb + SM_BAR + (lane & 7) * 64 + 56) < 30); n++) { nap(100); if (n > SPIN_MAX) __trap(); }
        const unsigned t_ref = lds32u(sb + SM_AN) + 256 * TAU + (cta & 7) * (TAU / 8);
        auto until = [&](int x) { while ((int)(now_ns() - t_ref) < x) nap(20); };
        if (lane < 8) mbar_expect(sb + SM_BAR + lane * 64 + 40, UNIT);
        __syncwarp();
        if (elect()) {
#pragma unroll 1
            for (int i = 0; i < 8; i += 2) {
                until(WO0 + i * WOS);
#pragma unroll
                for (int j = i; j < i + 2; j++) tma2d(sb + 5 * REG + j * UNIT, &P.wo, j * 64, head * 128 + 96, sb + SM_BAR + j * 64 + 40);
            }
        }
        if (rid < NF1) {
            if (elect()) {
#pragma unroll
                for (int i = 0; i < 4; i++) mbar_expect(sb + SM_BAR + i * 64 + 48, 2 * UNIT);
#pragma unroll 1
                for (int i = 0; i < 4; i++) {
                    const uint32_t b = sb + SM_BAR + i * 64 + 48;
                    until(W0 + i * WS);
                    tma5d(sb + 2 * REG + i * UNIT, &P.wg, rid * 16, i * 4, b); tma5d(sb + 2 * REG + 16384 + i * UNIT, &P.wu, rid * 16, i * 4, b);
                }
            }
        } else if (rid >= DN0) {
            bar_sync<B_LAST, NTHR>();
            if (elect()) {
                mbar_expect(sb + SM_BN, 16384); mbar_expect(sb + SM_BT, FF * 32);
                until(WD0);
                tma5d(sb + 2 * REG + 16384, &P.wd, (rid - DN0) * 16, 0, sb + SM_BT);
                tma2d(sb + 2 * REG, &P.wn, 2 * DM + rid * 16, 0, sb + SM_BN); tma2d(sb + 2 * REG + 8192, &P.wn, 2 * DM + rid * 16, 256, sb + SM_BN);
            }
        }
        __syncwarp();
        if (rid >= DN0) {
            mbar_wait(sb + SM_BN, 0);
            late_mod(sb + 2 * REG, 0); late_mod(sb + 2 * REG + 8192, 1);
#pragma unroll
            for (int e = 0; e < 2; e++)
                sts32u(sb + SM_MN + g * 32 + e * 16 + t * 4, movm(pack2((m[0][2 * e] + m[1][2 * e]) + (m[2][2 * e] + m[3][2 * e]), (m[0][2 * e + 1] + m[1][2 * e + 1]) + (m[2][2 * e + 1] + m[3][2 * e + 1]))));
            bar_arrive<B_DN, NTHR>();
        }
    }
    if (w >= 8) {
        if (rid < NF1) {
            const int b = (tid - 256) >> 3, c = tid & 7;
            char* const ho = pin(X + X_HM + (rid >> 4) * 8192 + ((rid >> 1) & 7) * 512 + b * 64 + (rid & 1) * 32 + c * 4);
            const uint32_t pi = pin(scr + SC_F1 + c * 144 + b * 16), si = pin(sb + SM_ST + b * 64);
            bar_sync<B_PRE, NALL>();
            float4 C = sum8x4<UNIT>(sb + REG + c * 144 + b * 16), S = sum8x4<UNIT>(sb + REG + 1152 + c * 144 + b * 16);
            S.x *= -LOG2E; S.y *= -LOG2E; C.x *= LOG2E; C.y *= LOG2E;
            sts128f(sb + SM_PR + lane * 16, C.x, C.y, C.z, C.w); sts128f(sb + SM_PR + lane * 16, S.x, S.y, S.z, S.w);
            sts128(sb + SM_PR + lane * 16, make_uint4(pi, si, (uint32_t)(size_t)ho, (uint32_t)((size_t)ho >> 32)));
            bar_sync<B_FIN, NALL>();
            const float4 s0_ = lds128(si), s1_ = lds128(si + 16), s2_ = lds128(si + 32), s3_ = lds128(si + 48);
            const float4 p = sum8x4<SCR>(pi);
            const float mean = (((s0_.x + s0_.z) + (s1_.x + s1_.z)) + ((s2_.x + s2_.z) + (s3_.x + s3_.z))) * (1.0f / DM);
            const float sq = (((s0_.y + s0_.w) + (s1_.y + s1_.w)) + ((s2_.y + s2_.w) + (s3_.y + s3_.w))) * (1.0f / DM);
            float rs; asm("rsqrt.approx.ftz.f32 %0, %1;" : "=f"(rs) : "f"(fmaxf(sq - mean * mean, 0.f) + 1e-5f));
            const float e0 = rs * (mean * C.x - LOG2E * p.x) + S.x, e1 = rs * (mean * C.y - LOG2E * p.y) + S.y;
            const float u0 = rs * (p.z - mean * C.z) + S.z, u1 = rs * (p.w - mean * C.w) + S.w;
            const unsigned hw = pack2(rcp(1.0f + ex2(e0)) * u0, rcp(1.0f + ex2(e1)) * u1);
            stg_rlx32(ho, hw); stg_rlx32(ho + 4096, hw);
        }
        return;
    }
    const unsigned ce = (lane >> 3) * (DM * 2) + w * 128 + (lane & 7) * 16;
    const uint4 ca = ldg_nc((const char*)pc + ce), cb = ldg_nc((const char*)pc + ce + 4 * DM * 2);
    const uint4 xa = ldg_nc((const char*)px + w * (DM * 2) + lane * 16), xb = ldg_nc((const char*)px + w * (DM * 2) + lane * 16 + 512);
    const uint4 xc = ldg_nc((const char*)px + ce), xd = ldg_nc((const char*)px + ce + 4 * DM * 2);
    if (w >= 4) pf_map(&P.wm + (w & 3));
    char* const qout = X + blk(X_Q, head >> 1, tid >> 7) + (head & 1) * 2048 + ((tid >> 4) & 7) * 256 + (cta & 3) * 64 + (tid & 3) * 16 + ((tid >> 2) & 3) * 4;
    char* const mout = X + blk(X_M1, cta >> 5, w) + (cta & 31) * 128 + lane * 4;
    stg_rlx32(qout, 0);
    if (w < 2) stg_rlx32(mout, 0);
    uint32_t sc[8], xf[8];
    {
        const uint32_t a = (lane >> 3) * 128 + (((lane & 7) ^ (lane >> 3)) << 4), b = (lane & 7) * 128 + (((lane >> 3) ^ (lane & 7)) << 4);
        const uint32_t cs = sb + SM_SC + w * 1024;
        sts128(cs + a, make_uint4(silu2(ca.x), silu2(ca.y), silu2(ca.z), silu2(ca.w)));
        sts128(cs + 512 + (a ^ 64), make_uint4(silu2(cb.x), silu2(cb.y), silu2(cb.z), silu2(cb.w)));
        sts128(myscr + a, xc); sts128(myscr + 512 + (a ^ 64), xd);
        __syncwarp();
        ldsm(*(uint32_t(*)[4])&sc[0], cs + b); ldsm(*(uint32_t(*)[4])&sc[4], cs + (b ^ 64));
        ldsm(*(uint32_t(*)[4])&xf[0], myscr + b); ldsm(*(uint32_t(*)[4])&xf[4], myscr + (b ^ 64));
        __syncwarp();
    }
    {
        float v[16] = {blo(xa.x), bhi(xa.x), blo(xa.y), bhi(xa.y), blo(xa.z), bhi(xa.z), blo(xa.w), bhi(xa.w),
                       blo(xb.x), bhi(xb.x), blo(xb.y), bhi(xb.y), blo(xb.z), bhi(xb.z), blo(xb.w), bhi(xb.w)};
        float s = 0;
#pragma unroll
        for (int i = 0; i < 16; i++) s += v[i];
#pragma unroll
        for (int o = 16; o; o >>= 1) s += __shfl_xor_sync(~0u, s, o);
        s *= (1.0f / DM);
        float q2 = 0;
#pragma unroll
        for (int i = 0; i < 16; i++) q2 += (v[i] - s) * (v[i] - s);
#pragma unroll
        for (int o = 16; o; o >>= 1) q2 += __shfl_xor_sync(~0u, q2, o);
        uint32_t mu2; float rs; ln_consts(s, q2 * (1.0f / DM), mu2, rs);
        if (lane == 0) sts64(sb + SM_ST + w * 8, __uint_as_float(mu2), rs);
    }
    const int lrow = (lane & 7) + ((lane >> 4) << 3), lch = (lane >> 3) & 1;
    const uint32_t off64 = lrow * 64 + ((lch ^ ((lrow >> 1) & 3)) << 4);
    const uint32_t off128 = lrow * 128 + ((lch ^ (lane & 7)) << 4);
    bar_sync<B_INIT, NTHR>();
    mbar_wait(sb + SM_BM, 0);
    {
        float a[4] = {0, 0, 0, 0}, b[4] = {0, 0, 0, 0};
        uint32_t r[4], u[4];
        ldsm_t(r, sb + 4 * REG + (w * 64 + lane) * 16); ldsm_t(u, sb + 4 * REG + (w * 64 + 32 + lane) * 16);
        mma(a, sc[0], 0, sc[1], 0, r[0], r[1]); mma(b, sc[4], 0, sc[5], 0, u[0], u[1]);
        mma(a, sc[2], 0, sc[3], 0, r[2], r[3]); mma(b, sc[6], 0, sc[7], 0, u[2], u[3]);
        sts64(myscr + SC_M + lane * 8, a[0] + b[0], a[1] + b[1]);
    }
    bar_arrive<B_MOD, NTHR>();
    bar_sync<B_ALL, 256>();
    if (w < 2) {
        const float2 m = sum8(scr + SC_M + lane * 8);
        stg_rlx32(mout, ~pack2(m.x, m.y));
    }
    if (tid < 8 * XC) stg_rlx128(X + X_X1 + (cta * 8 * XC + tid) * 16, make_uint4(SENT, SENT, SENT, SENT));
    else if (tid >= 232) stg_rlx128(X + X_HM + (cta * 24 + tid - 232) * 16, make_uint4(SENT, SENT, SENT, SENT));
    {
        const float2 st = lds64(sb + SM_ST + g * 8);
#pragma unroll
        for (int i = 0; i < 8; i++) xf[i] = ln_norm(xf[i], __float_as_uint(st.x), st.y);
    }
    {
        unsigned sv[8], cv[8]; int n = 0;
        bar_sync<B_SIDE, NTHR>();
        const char* const mp = X + blk(X_M1, w >> 2, lds32u(sb + SM_SIDE)) + (w & 3) * 1024 + lane * 4;
        if (lane == 0) while (!ldg_rlx32(mp + 16384 + 7 * 128)) { nap(40); if (++n > SPIN_MAX) __trap(); }
        __syncwarp();
#pragma unroll
        for (int j = 0; j < 8; j++) { sv[j] = ldg_rlx32(mp + j * 128); cv[j] = ldg_rlx32(mp + 16384 + j * 128); }
        while (true) {
            unsigned m = ~0u;
#pragma unroll
            for (int j = 0; j < 8; j++) m = min(m, min(sv[j], cv[j]));
            if (__all_sync(~0u, m)) break;
#pragma unroll
            for (int j = 0; j < 8; j++) { if (!sv[j]) sv[j] = ldg_rlx32(mp + j * 128); if (!cv[j]) cv[j] = ldg_rlx32(mp + 16384 + j * 128); }
            if (++n > SPIN_MAX) __trap();
        }
#pragma unroll
        for (int j = 0; j < 8; j++) xf[j] = add2(mul2(xf[j], add2(~cv[j], ONE2)), ~sv[j]);
        mbar_wait(bar0 + 48, 0);
        float acc[4][4] = {};
#pragma unroll
        for (int j = 0; j < 4; j++) {
            uint32_t r[4], u[4];
            ldsm_t(r, s2 + REG + j * 1024 + off64); ldsm_t(u, s2 + REG + j * 1024 + (off64 ^ 32));
            mma(acc[0], xf[2 * j], 0, xf[2 * j + 1], 0, r[0], r[2]); mma(acc[1], xf[2 * j], 0, xf[2 * j + 1], 0, r[1], r[3]);
            mma(acc[2], xf[2 * j], 0, xf[2 * j + 1], 0, u[0], u[2]); mma(acc[3], xf[2 * j], 0, xf[2 * j + 1], 0, u[1], u[3]);
        }
#pragma unroll
        for (int n2 = 0; n2 < 4; n2++) sts64(myscr + SC_Q + g * 160 + n2 * 32 + t * 8, acc[n2][0], acc[n2][1]);
    }
    bar_arrive<B_WQ, NTHR>();
    bar_sync<B_ALL, 256>();
    {
        const float2 s = sum8(scr + SC_Q + ((tid >> 4) & 7) * 160 + (tid & 15) * 8);
        stg_rlx32(qout, ~pack2(s.x, s.y));
    }
    uint32_t q[16];
    {
        int n = 0;
        const char* const qp = X + blk(X_Q, head >> 1, lds32u(sb + SM_SIDE)) + (head & 1) * 2048 + bat * 256 + t * 16;
        uint4 v[4];
#pragma unroll
        for (int j = 0; j < 4; j++) v[j] = ldg_rlx128(qp + j * 64);
        while (true) {
            bool bad[4];
#pragma unroll
            for (int j = 0; j < 4; j++) bad[j] = !min(min(v[j].x, v[j].y), min(v[j].z, v[j].w));
            if (!__any_sync(~0u, bad[0] | bad[1] | bad[2] | bad[3])) break;
#pragma unroll
            for (int j = 0; j < 4; j++) if (bad[j]) v[j] = ldg_rlx128(qp + j * 64);
            if (++n > SPIN_MAX) __trap();
        }
#pragma unroll
        for (int j = 0; j < 4; j++) { q[4 * j] = ~v[j].x; q[4 * j + 1] = ~v[j].y; q[4 * j + 2] = ~v[j].z; q[4 * j + 3] = ~v[j].w; }
    }
    bar_arrive<B_Q, NTHR>();

    float o[2][4] = {};
    float mrun = -3.0e38f, lrun = 0.f;
    uint32_t wa[16][4], pb[2];
#pragma unroll
    for (int i = 0; i < 16; i++) wa[i][0] = wa[i][1] = wa[i][2] = wa[i][3] = 0;
    const uint32_t offk = (lane & 15) * 128 + (((lane >> 4) ^ (lane & 7)) << 4);
    float p0, p1;
    auto scores = [&](uint32_t a0) {
        uint32_t kf[8][4];
#pragma unroll
        for (int j = 0; j < 8; j++) ldsm(kf[j], ((a0 + offk) ^ ((j & 3) << 5)) + (j >> 2) * 2048);
        float sa[4] = {0, 0, 0, 0}, sb2[4] = {0, 0, 0, 0};
#pragma unroll
        for (int j = 0; j < 8; j += 2) { mma(sa, kf[j], q[2 * j], q[2 * j + 1]); mma(sb2, kf[j + 1], q[2 * j + 2], q[2 * j + 3]); }
        uint32_t u = pack2(sa[0] + sb2[0], sa[2] + sb2[2]);
        u = pack2(blo(u) * SCALE, bhi(u) * SCALE);
        const float z0 = blo(u), z1 = bhi(u);
        float mx = fmaxf(z0, z1);
        mx = fmaxf(mx, __shfl_xor_sync(~0u, mx, 4)); mx = fmaxf(mx, __shfl_xor_sync(~0u, mx, 8)); mx = fmaxf(mx, __shfl_xor_sync(~0u, mx, 16));
        mx = fmaxf(mx, mrun);
        const float f = ex2((mrun - mx) * LOG2E);
        p0 = ex2((z0 - mx) * LOG2E); p1 = ex2((z1 - mx) * LOG2E);
        mrun = mx; lrun = lrun * f + (p0 + p1);
#pragma unroll
        for (int j = 0; j < 4; j++) { o[0][j] *= f; o[1][j] *= f; }
    };
    const int kvrow = (bat * NH + head) * SK + (SK - WIN) + (w & 3) * 16;
    const int wofs = (w * 8 + (cta & 7)) * TAU / 8;
    auto request = [&](int u) {
        sts32u(bar0 + 56, u - 1);
        while ((int)(now_ns() - lds32u(sb + SM_AN) - u * 8 * TAU - wofs) < 0) nap(20);
        const int sl = (~u & 2) + (u & 1);
        mbar_expect(bar0 + sl * 8, UNIT); tma_kv(s0 + sl * REG, &P.k + (u & 1), kvrow + tile_key(u >> 1), bar0 + sl * 8, pol);
    };
#pragma unroll 1
    for (int it = 0; it < NT - 1; it++) {
        const int si = it < 3 ? it : (it + 1) & 1;
        const uint32_t bar = bar0 + si * 16, a0 = s0 + si * 2 * REG;
        const uint32_t par = it < 3 ? 0 : ((it - 1) >> 1) & 1;
        const bool refill = lane == 0 && it >= 2;
        mbar_wait(bar, par);
        if (refill) {
            request(2 * it + 2);
            const unsigned bit = 1u << it, pc = __popc((bit - 1) & WO_ITS);
            if (bit & WO_ITS) {
                if (pc != 1) mbar_expect(barC, pc ? UNIT : 2 * UNIT);
                tma2d(s2 + (pc & 1) * REG, &P.wo, w * 64, head * 128 + pc * 32, barC);
            }
        }
        __syncwarp();
        if (it == WOA_READ) {
            mbar_wait(barC, 1);
#pragma unroll
            for (int j = 0; j < 16; j++) ldsm_t(wa[j], s2 + (j >> 3) * REG + ((j >> 2) & 1) * 2048 + (off128 ^ ((j & 3) << 5)));
        }
        scores(a0);
        pb[0] = movm(pack2(p0, p0)); pb[1] = movm(pack2(p1, p1));
        mbar_wait(bar + 8, par);
        if (refill) request(2 * it + 3);
        __syncwarp();
        uint32_t vf[8][4];
#pragma unroll
        for (int j = 0; j < 8; j++) ldsm_t(vf[j], ((a0 + off128) ^ ((j & 3) << 5)) + (j >> 2) * 2048 + REG);
#pragma unroll
        for (int j = 0; j < 8; j++) { const bool on = (g >> 1) == (j >> 1); mma(o[j & 1], vf[j], on ? pb[0] : 0, on ? pb[1] : 0); }
    }
    {
        uint32_t wb[16][4];
        mbar_wait(bar0, 1);
        if (rid >= DN0) bar_arrive<B_LAST, NTHR>();
        scores(s0);
        lrun += __shfl_xor_sync(~0u, lrun, 4); lrun += __shfl_xor_sync(~0u, lrun, 8); lrun += __shfl_xor_sync(~0u, lrun, 16);
        if (lane == 0) sts64(sb + SM_ML + w * 8, mrun, lrun);
        bar_arrive<B_ML, NTHR>();
        pb[0] = movm(pack2(p0, p0)); pb[1] = movm(pack2(p1, p1));
        const uint32_t va = pin(s0 + REG + off128);
        auto load_wb = [&](int j) { ldsm_t(wb[j], (va ^ ((j & 3) << 5)) + (3 + (j >> 3)) * REG + ((j >> 2) & 1) * 2048); };
        mbar_wait(barC, 0);
#pragma unroll
        for (int j = 0; j < 8; j++) load_wb(j);
        const uint32_t ho = pin(s0 + w * 16 + ((lane & 7) >> 1) * 64 + ((lane >> 3) & 1) * 32 + (lane & 1) * 16), oa = pin(sb + (lane & 7) * (UNIT + 16) + (lane >> 3) * 16);
        const uint32_t rd = pin((t >> 1) * 16 + w * 2 + (g >> 2));
        char* const pp = pin(X + X_PART + ((cta & 3) * 32 + rd) * 8192 + head * 128 + (g & 3) * 32 + (t & 1) * 16);
        const uint32_t ln = pin(lane), wbar = pin(barC + 8);
        mbar_wait(bar0 + 8, 1);
        {
            uint32_t vf[8][4];
            float o2[2][4] = {};
#pragma unroll
            for (int j = 0; j < 8; j++) ldsm_t(vf[j], (va ^ ((j & 3) << 5)) + (j >> 2) * 2048);
#pragma unroll
            for (int j = 0; j < 8; j++) { const bool on = (ln >> 3) == (j >> 1); mma((j & 2) ? o2[j & 1] : o[j & 1], vf[j], on ? pb[0] : 0, on ? pb[1] : 0); }
            asm volatile("stmatrix.sync.aligned.m8n8.x2.trans.shared.b16 [%0], {%1,%2};" :: "r"(ho), "r"(pack2(o[0][0] + o2[0][0], o[0][2] + o2[0][2])), "r"(pack2(o[1][0] + o2[1][0], o[1][2] + o2[1][2])) : "memory");
        }
        bar_sync<B_RDY, NALL>();
        float y[4][4] = {};
        uint32_t ob[4][4];
#pragma unroll
        for (int i2 = 0; i2 < 4; i2++) ldsm(ob[i2], oa + i2 * 64);
        const float2 f = lds64(sb + SM_ML + 64 + (ln & 3) * 8);
        const unsigned half = (lds32u(sb + SM_MASK) >> rd & 1) * 4096;
#pragma unroll
        for (int j = 0; j < 8; j++) {
            if (j == WJ) {
                if (!mbar_test(wbar, 1)) mbar_wait(wbar, 1);
#pragma unroll
                for (int k = 8; k < 16; k++) load_wb(k);
            }
#pragma unroll
            for (int i = 0; i < 4; i++) mmav(y[i], j < 4 ? wa[j * 4 + i] : wb[(j - 4) * 4 + i], ob[j >> 1][2 * (j & 1)], ob[j >> 1][2 * (j & 1) + 1]);
        }
        uint32_t r[4];
#pragma unroll
        for (int i = 0; i < 4; i++) {
            const float lo = f.x * y[i][0] + f.y * y[i][1], hi = f.x * y[i][2] + f.y * y[i][3];
            r[i] = __float_as_uint(((ln & 1) ? hi : lo) + __shfl_xor_sync(~0u, (ln & 1) ? lo : hi, 1));
        }
        asm("min.u32 %0, %0, 0xFFFFFFFE;" : "+r"(r[0]));
        stg_b128(pp + half, make_uint4(r[0], r[1], r[2], r[3]));
    }
    const unsigned side = lds32u(sb + SM_SIDE);
    const char* const x1p = X + (rid & (XC - 1)) * 16384;
    if (rid < NF1) {
        uint32_t wg[4][4], wu[4][4];
        const char* const xp = pin(x1p + blk(X_X1, w >> 2, side) + (w & 3) * 1024 + lane * 16);
        float4 c1[2], sv[2];
#pragma unroll
        for (int h = 0; h < 2; h++) { sv[h] = lds128(sb + SM_MN + (w * 2 + h) * 512 + lane * 16); c1[h] = lds128(sb + SM_MN + 8192 + (w * 2 + h) * 512 + lane * 16); }
        const uint32_t po = pin(myscr + SC_F1 + g * 144 + t * 32), so = pin(t == (g >> 1) ? sb + SM_ST + g * 64 + w * 8 : myscr + 1792 + lane * 8), odd = pin(g & 1);
        const uint32_t wbar = sb + SM_BAR + (w >> 1) * 64 + 48;
        uint4 x0, x1;
        const bool early = go_first(wbar, 1);
        if (early) { spin(clock(), (7 - w) * XDW); x0 = ldg_rlx2x64(xp); x1 = ldg_rlx2x64(xp + 512); mbar_wait(wbar, 1); }
#pragma unroll
        for (int j = 0; j < 4; j++) {
            const uint32_t a = sb + 2 * REG + w * 2048 + (((lane & 7) >> 1) + (lane & 1) * 4 + j * 8 + (lane >> 4) * 32) * 32 + ((lch ^ (lane & 1)) << 4);
            ldsm_t(wg[j], a); ldsm_t(wu[j], a + 16384);
        }
        {
            float cg[4] = {}, cu[4] = {}, sg[4] = {}, su[4] = {};
#pragma unroll
            for (int j = 0; j < 4; j++) {
                const float4 a = c1[j & 1], b = sv[j & 1];
                const uint32_t a0 = __float_as_uint(j >> 1 ? a.z : a.x), a1 = __float_as_uint(j >> 1 ? a.w : a.y), b0 = __float_as_uint(j >> 1 ? b.z : b.x), b1 = __float_as_uint(j >> 1 ? b.w : b.y);
                mma(cg, wg[j], a0, a1); mma(cu, wu[j], a0, a1); mma(sg, wg[j], b0, b1); mma(su, wu[j], b0, b1);
            }
            const uint32_t d = s0 + REG + g * 144 + t * 32;
            sts128f(d, cg[0], cg[2], cu[0], cu[2]); sts128f(d + 16, cg[1], cg[3], cu[1], cu[3]);
            sts128f(d + 1152, sg[0], sg[2], su[0], su[2]); sts128f(d + 1168, sg[1], sg[3], su[1], su[3]);
            bar_arrive<B_PRE, NALL>();
        }
        if (!early) { mbar_wait(sb + SM_BG, 0); spin(clock(), (7 - w) * XDW); x0 = ldg_rlx2x64(xp); x1 = ldg_rlx2x64(xp + 512); }
        int n = 0;
        while (true) {
            const bool b0 = max(x0.x, x0.z) == SENT, b1 = max(x1.x, x1.z) == SENT;
            if (!__any_sync(~0u, b0 | b1)) break;
            if (b0) x0 = ldg_rlx2x64(xp);
            if (b1) x1 = ldg_rlx2x64(xp + 512);
            if (++n > SPIN_MAX) __trap();
        }
        float q0[4] = {}, q1[4] = {}, ag[2][4] = {}, au[2][4] = {};
        {
            mma(q0, x0.x, ONE2, x0.y, ONE2, x0.x, x0.y); mma(q1, x0.z, ONE2, x0.w, ONE2, x0.z, x0.w);
            mma(q0, x1.x, ONE2, x1.y, ONE2, x1.x, x1.y); mma(q1, x1.z, ONE2, x1.w, ONE2, x1.z, x1.w);
#pragma unroll
            for (int j = 0; j < 4; j++) {
                const uint4 xv = (j & 1) ? x1 : x0; const float4 a = c1[j & 1];
                const uint32_t h0 = mul2(j >> 1 ? xv.z : xv.x, __float_as_uint(j >> 1 ? a.z : a.x)), h1 = mul2(j >> 1 ? xv.w : xv.y, __float_as_uint(j >> 1 ? a.w : a.y));
                mma(ag[j & 1], wg[j], h0, h1); mma(au[j & 1], wu[j], h0, h1);
            }
        }
        sts64(so, odd ? q0[3] + q1[3] : q0[2] + q1[2], odd ? q0[1] + q1[1] : q0[0] + q1[0]);
        sts128f(po, ag[0][0] + ag[1][0], ag[0][2] + ag[1][2], au[0][0] + au[1][0], au[0][2] + au[1][2]);
        sts128f(po + 16, ag[0][1] + ag[1][1], ag[0][3] + ag[1][3], au[0][1] + au[1][1], au[0][3] + au[1][3]);
        bar_arrive<B_FIN, NALL>();
    } else if (rid >= DN0) {
        const int f = rid - DN0;
        uint32_t wd[12][4];
        const char* const hp0 = pin(X + blk(X_HM, 0, side) + w * 512 + lane * 16);
        const char* const hp1 = pin(X + blk(X_HM, 1, side) + w * 512 + lane * 16);
        auto hm = [&](int j) { return ldg_rlx128((j & 1 ? hp1 : hp0) + (j >> 1) * 16384); };
        __nv_bfloat16* const op = pin(P.out + ((tid >> 4) & 7) * DM + f * 16 + (tid & 15));
        const uint32_t po = pin(myscr + SC_DN + t * 160 + g * 16), pi = pin(scr + SC_DN + (w & 3) * 160 + (tid & 7) * 16 + (tid & 8) + ((tid >> 4) & 1) * 4), gi = pin(sb + SM_MN + tid * 2), first = pin(w < 4);
        uint4 hv[6]; int n = 0;
        auto first_poll = [&]() {
            spin(clock(), w * HDW);
#pragma unroll
            for (int j = 0; j < 6; j++) hv[j] = (j < 5 || w < 3) ? hm(j) : make_uint4(0, 0, 0, 0);
        };
        const bool early = go_first(sb + SM_BT, 0);
        if (early) { first_poll(); mbar_wait(sb + SM_BT, 0); }
#pragma unroll
        for (int j = 0; j < 12; j++)
            if (j < 10 || w < 3) ldsm_t(wd[j], sb + 2 * REG + 16384 + (w + (j >> 1) * 8) * 1024 + (j & 1) * 512 + (((lane >> 1) & 1) + (lane & 1) * 2 + (lane & 4) + (lane >> 4) * 8) * 32 + ((lch ^ ((lane >> 2) & 1)) << 4));
            else wd[j][0] = wd[j][1] = wd[j][2] = wd[j][3] = 0;
        if (!early) { mbar_wait(sb + SM_BG, 0); first_poll(); }
        while (true) {
            unsigned m[6];
#pragma unroll
            for (int j = 0; j < 6; j++) m[j] = max(max(hv[j].x, hv[j].y), max(hv[j].z, hv[j].w));
            if (__all_sync(~0u, max(max(max(m[0], m[1]), m[2]), max(max(m[3], m[4]), m[5])) != SENT)) break;
#pragma unroll
            for (int j = 0; j < 6; j++) if (m[j] == SENT) hv[j] = hm(j);
            if (++n > SPIN_MAX) __trap();
        }
        float d[4][4] = {};
#pragma unroll
        for (int j = 0; j < 6; j++) { mma(d[(2 * j) & 3], wd[2 * j], hv[j].x, hv[j].y); mma(d[(2 * j + 1) & 3], wd[2 * j + 1], hv[j].z, hv[j].w); }
        sts128f(po, (d[0][0] + d[1][0]) + (d[2][0] + d[3][0]), (d[0][1] + d[1][1]) + (d[2][1] + d[3][1]), (d[0][2] + d[1][2]) + (d[2][2] + d[3][2]), (d[0][3] + d[1][3]) + (d[2][3] + d[3][3]));
        bar_sync<B_DN, NTHR>();
        if (first) {
            float v[8];
#pragma unroll
            for (int i = 0; i < 8; i++) v[i] = lds32(pi + i * SCR);
            unsigned gw, res;
            asm volatile("ld.shared.u16 %0, [%1];" : "=r"(gw) : "r"(gi) : "memory"); asm volatile("ld.shared.u16 %0, [%1];" : "=r"(res) : "r"(gi + 256) : "memory");
            asm volatile("st.global.u16 [%0], %1;" :: "l"(op), "h"((unsigned short)add2(res, mul2(gw, pack2(((v[0] + v[1]) + (v[2] + v[3])) + ((v[4] + v[5]) + (v[6] + v[7])), 0.f)))) : "memory");
        }
    }
}

typedef CUresult (*EncodeFn)(CUtensorMap*, CUtensorMapDataType, cuuint32_t, void*, const cuuint64_t*, const cuuint64_t*, const cuuint32_t*,
                             const cuuint32_t*, CUtensorMapInterleave, CUtensorMapSwizzle, CUtensorMapL2promotion, CUtensorMapFloatOOBfill);

void make2d(EncodeFn enc, CUtensorMap* m, const void* p, int rows, int cols, int brows, int bcols, CUtensorMapSwizzle sw) {
    cuuint64_t dims[2] = {(cuuint64_t)cols, (cuuint64_t)rows}, strides[1] = {(cuuint64_t)cols * 2};
    cuuint32_t box[2] = {(cuuint32_t)bcols, (cuuint32_t)brows}, es[2] = {1, 1};
    enc(m, CU_TENSOR_MAP_DATA_TYPE_BFLOAT16, 2, (void*)p, dims, strides, box, es, CU_TENSOR_MAP_INTERLEAVE_NONE, sw,
        CU_TENSOR_MAP_L2_PROMOTION_L2_128B, CU_TENSOR_MAP_FLOAT_OOB_FILL_NONE);
}
void make5d(EncodeFn enc, CUtensorMap* m, const void* p, int cols, const unsigned (&n)[4], const unsigned (&s)[4], unsigned nb) {
    const cuuint64_t rs = (cuuint64_t)cols * 2;
    cuuint64_t dims[5] = {(cuuint64_t)cols, n[0], n[1], n[2], n[3]}, strides[4] = {rs * s[0], rs * s[1], rs * s[2], rs * s[3]};
    cuuint32_t box[5] = {16, n[0], n[1], n[2], nb}, es[5] = {1, 1, 1, 1, 1};
    enc(m, CU_TENSOR_MAP_DATA_TYPE_BFLOAT16, 5, (void*)p, dims, strides, box, es, CU_TENSOR_MAP_INTERLEAVE_NONE, CU_TENSOR_MAP_SWIZZLE_32B,
        CU_TENSOR_MAP_L2_PROMOTION_L2_128B, CU_TENSOR_MAP_FLOAT_OOB_FILL_NONE);
}
void makekv(EncodeFn enc, CUtensorMap* m, const void* p) {
    cuuint64_t dims[3] = {64, (cuuint64_t)NB * NH * SK, 2}, strides[2] = {256, 128};
    cuuint32_t box[3] = {64, 16, 2}, es[3] = {1, 1, 1};
    enc(m, CU_TENSOR_MAP_DATA_TYPE_BFLOAT16, 3, (void*)p, dims, strides, box, es, CU_TENSOR_MAP_INTERLEAVE_NONE, CU_TENSOR_MAP_SWIZZLE_128B,
        CU_TENSOR_MAP_L2_PROMOTION_NONE, CU_TENSOR_MAP_FLOAT_OOB_FILL_NONE);
}

}

extern "C" void kernel_launch(void* const* d_in, const int* in_sizes, int n_in, void* d_out, int out_size) {
    (void)in_sizes; (void)n_in; (void)out_size;
    static EncodeFn enc = nullptr;
    static void* raw = nullptr;
    if (!enc) {
        void* fn = nullptr; cudaDriverEntryPointQueryResult qr;
        cudaGetDriverEntryPoint("cuTensorMapEncodeTiled", &fn, cudaEnableDefault, &qr);
        enc = (EncodeFn)fn;
        cudaFuncSetAttribute(fused_kernel, cudaFuncAttributeMaxDynamicSharedMemorySize, SM_TOTAL);
        cudaGetSymbolAddress(&raw, g_raw);
    }
    Params P;
    makekv(enc, &P.k, d_in[1]);
    makekv(enc, &P.v, d_in[2]);
    make2d(enc, &P.wq, d_in[3], DM, NH * DH, 64, 32, CU_TENSOR_MAP_SWIZZLE_64B);
    make2d(enc, &P.wo, d_in[4], NH * DH, DM, 32, 64, CU_TENSOR_MAP_SWIZZLE_128B);
    make2d(enc, &P.wm, d_in[10], DM, 6 * DM, 256, 8, CU_TENSOR_MAP_SWIZZLE_NONE);
    make2d(enc, &P.wn, d_in[10], DM, 6 * DM, 256, 16, CU_TENSOR_MAP_SWIZZLE_32B);
    make5d(enc, &P.wg, d_in[6], FF, {4, 2, 4, 16}, {1, 16, 4, 32}, 4);
    make5d(enc, &P.wu, d_in[7], FF, {4, 2, 4, 16}, {1, 16, 4, 32}, 4);
    make5d(enc, &P.wd, d_in[8], DM, {8, 4, 1, 43}, {4, 1, 1, 32}, 43);
    P.out = (__nv_bfloat16*)d_out;
    typedef const __nv_bfloat16* W;
    fused_kernel<<<NCTA, NALL, SM_TOTAL>>>((W)d_in[0], (W)d_in[9], (W)d_in[1], (W)d_in[10], (W)d_in[3], (char*)(((size_t)raw + X_ALIGN - 1) & ~(size_t)(X_ALIGN - 1)), P);
}
```

```cpp
#include <cuda_runtime.h>
#include <cuda_bf16.h>
#include <cuda.h>
#include <stdint.h>

namespace {

constexpr int NB = 8, DM = 512, NH = 32, DH = 128, SK = 4096, WIN = 1024, FF = 1376;
constexpr int NCTA = 128, NTHR = 288, NALL = 320;
constexpr int NT = 16;
constexpr int NF1 = 86, DN0 = 96;
constexpr unsigned SENT = 0xFFFFFFFFu;
constexpr int SPIN_MAX = 1 << 20;

constexpr int PWIN0 = 12;
constexpr int PWIN = 16;
constexpr int PSW = 22;
constexpr int NTRK = 8;
constexpr int PFK = 2;
constexpr int QN = 7;
constexpr int TAU = 166;
constexpr int ANCH0 = 176;
constexpr int LEAD = 1600;
constexpr int PACE0 = 7000;
constexpr int PNAP = 200;
constexpr int WOA_ISSUE = 3;
constexpr int WO_GAP = 2;
constexpr int WOA_READ = 8;
constexpr int WK = 1;
constexpr int WJ = 4;
constexpr int WO0 = 450;
constexpr int WOS = 35;
constexpr int WOG = 350;
constexpr int W0 = 1150;
constexpr int WS = 200;
constexpr int WD0 = 2100;
constexpr int RT0 = 2100;
constexpr int HD0 = 1000;
constexpr int XDW = 30;
constexpr int HDW = 45;
constexpr int XC = 2;

constexpr int UNIT = 4096, REG = 8 * UNIT;
constexpr int SM_SCR = 6 * REG;
constexpr int SCR = 2048;
constexpr int SM_MN = SM_SCR + 8 * SCR;
constexpr int SM_SC = SM_MN + 8192;
constexpr int SM_BAR = SM_SC + 8192;
constexpr int SM_BM = SM_BAR + 512, SM_BT = SM_BM + 8, SM_BN = SM_BM + 16, SM_BG = SM_BM + 24;
constexpr int SM_AN = SM_BM + 32, SM_SIDE = SM_BM + 36, SM_TAG = SM_BM + 40, SM_MASK = SM_BM + 44;
constexpr int SM_ST = SM_BAR + 576;
constexpr int SM_ML = SM_ST + 512;
constexpr int SM_PR = SM_ML + 96;
constexpr int SM_TOTAL = SM_PR + 512;
constexpr int SC_M = 0, SC_Q = 256;
constexpr int SC_F1 = 0, SC_DN = 0, SC_RX = 1536;
constexpr int B_INIT = 0, B_ALL = 2, B_MOD = 3, B_WQ = 4, B_LAST = 5, B_RDY = 6, B_DN = 7, B_PRE = 8, B_FIN = 9, B_STG = 10, B_SIDE = 11, B_Q = 12, B_ML = 13;

constexpr unsigned HOME = 0xB3000;
constexpr int X_PART = 0;
constexpr int X_Q = 0x100000;
constexpr int X_M1 = 0x140000;
constexpr int X_X1 = 0x150000;
constexpr int X_HM = 0x160000;
constexpr int X_MOD = 0x170000;
constexpr int X_SIDE = 0x176000;
constexpr int X_EPOCH = 0x176400;
constexpr int X_READY = 0x176480;
constexpr int X_LAG = 0x178000;
constexpr int X_ANC = 0x158000;
constexpr int X_PRB = 0x180000;
constexpr int X_ALIGN = 0x200000;
static_assert(XC == 2, "one store writes all copies of x1");
__device__ uint4 g_raw[2 * X_ALIGN / 16];
__device__ __forceinline__ unsigned blk(unsigned base, unsigned k, unsigned s) { const unsigned o = base + k * 8192; return o + ((__popc(o & HOME) ^ s) & 1) * 4096; }

struct Params {
    CUtensorMap wm, wq, k, v, wn, wo, wg, wu, wd;
    __nv_bfloat16* out;
};

__device__ __forceinline__ int tile_key(int i) { return (i & 1) * 128 + (i & 2) * 32 + (i & 12) * 64; }

__device__ __forceinline__ uint32_t smem_u32(const void* p) { return (uint32_t)__cvta_generic_to_shared(p); }
__device__ __forceinline__ void mbar_init(uint32_t a, uint32_t c) { asm volatile("mbarrier.init.shared::cta.b64 [%0], %1;" :: "r"(a), "r"(c) : "memory"); }
__device__ __forceinline__ void mbar_expect(uint32_t a, uint32_t b) { asm volatile("mbarrier.arrive.expect_tx.shared::cta.b64 _, [%0], %1;" :: "r"(a), "r"(b) : "memory"); }
__device__ __forceinline__ void mbar_wait(uint32_t a, uint32_t par) {
    uint32_t ok; int n = 0;
    do {
        asm volatile("{\n.reg .pred p;\nmbarrier.try_wait.parity.shared::cta.b64 p, [%1], %2, 2000;\nselp.u32 %0, 1, 0, p;\n}" : "=r"(ok) : "r"(a), "r"(par) : "memory");
        if (++n > SPIN_MAX) __trap();
    } while (!ok);
}
__device__ __forceinline__ bool mbar_test(uint32_t a, uint32_t par) {
    uint32_t ok; asm volatile("{\n.reg .pred p;\nmbarrier.test_wait.parity.shared::cta.b64 p, [%1], %2;\nselp.u32 %0, 1, 0, p;\n}" : "=r"(ok) : "r"(a), "r"(par) : "memory"); return ok;
}
__device__ __forceinline__ void tma2d(uint32_t dst, const CUtensorMap* m, int x, int y, uint32_t bar) {
    asm volatile("cp.async.bulk.tensor.2d.shared::cluster.global.mbarrier::complete_tx::bytes [%0], [%1, {%3, %4}], [%2];"
                 :: "r"(dst), "l"(m), "r"(bar), "r"(x), "r"(y) : "memory");
}
__device__ __forceinline__ void tma5d(uint32_t dst, const CUtensorMap* m, int x, int y, uint32_t bar) {
    asm volatile("cp.async.bulk.tensor.5d.shared::cluster.global.mbarrier::complete_tx::bytes [%0], [%1, {%3, 0, 0, 0, %4}], [%2];"
                 :: "r"(dst), "l"(m), "r"(bar), "r"(x), "r"(y) : "memory");
}
__device__ __forceinline__ void tma_kv(uint32_t dst, const CUtensorMap* m, int row, uint32_t bar, uint64_t pol) {
    asm volatile("cp.async.bulk.tensor.3d.shared::cluster.global.mbarrier::complete_tx::bytes.L2::cache_hint [%0], [%1, {0, %3, 0}], [%2], %4;"
                 :: "r"(dst), "l"(m), "r"(bar), "r"(row), "l"(pol) : "memory");
}
__device__ __forceinline__ void pf_bulk(const void* p, uint32_t n) { asm volatile("cp.async.bulk.prefetch.L2.global [%0], %1;" :: "l"(p), "r"(n) : "memory"); }
__device__ __forceinline__ void pf_if(const void* p, unsigned i, unsigned n) { asm volatile("{\n.reg .pred p;\nsetp.lt.u32 p, %1, %2;\n@p prefetch.global.L2 [%0];\n}" :: "l"(p), "r"(i), "r"(n) : "memory"); }
__device__ __forceinline__ uint4 ldg_nc(const void* p) { uint4 v; asm volatile("ld.global.nc.v4.u32 {%0,%1,%2,%3}, [%4];" : "=r"(v.x), "=r"(v.y), "=r"(v.z), "=r"(v.w) : "l"(p)); return v; }
__device__ __forceinline__ bool elect() { uint32_t p; asm volatile("{\n.reg .pred p;\nelect.sync _|p, -1;\nselp.u32 %0, 1, 0, p;\n}" : "=r"(p)); return p; }
__device__ __forceinline__ void pf_map(const CUtensorMap* m) { asm volatile("prefetch.tensormap [%0];" :: "l"(m) : "memory"); }
__device__ __forceinline__ void ldsm(uint32_t (&r)[4], uint32_t a) {
    asm volatile("ldmatrix.sync.aligned.m8n8.x4.shared.b16 {%0,%1,%2,%3}, [%4];" : "=r"(r[0]), "=r"(r[1]), "=r"(r[2]), "=r"(r[3]) : "r"(a) : "memory");
}
__device__ __forceinline__ void ldsm_t(uint32_t (&r)[4], uint32_t a) {
    asm volatile("ldmatrix.sync.aligned.m8n8.x4.trans.shared.b16 {%0,%1,%2,%3}, [%4];" : "=r"(r[0]), "=r"(r[1]), "=r"(r[2]), "=r"(r[3]) : "r"(a) : "memory");
}
__device__ __forceinline__ void mma(float (&c)[4], uint32_t a0, uint32_t a1, uint32_t a2, uint32_t a3, uint32_t b0, uint32_t b1) {
    asm("mma.sync.aligned.m16n8k16.row.col.f32.bf16.bf16.f32 {%0,%1,%2,%3}, {%4,%5,%6,%7}, {%8,%9}, {%0,%1,%2,%3};"
        : "+f"(c[0]), "+f"(c[1]), "+f"(c[2]), "+f"(c[3]) : "r"(a0), "r"(a1), "r"(a2), "r"(a3), "r"(b0), "r"(b1));
}
__device__ __forceinline__ void mma(float (&c)[4], const uint32_t (&a)[4], uint32_t b0, uint32_t b1) { mma(c, a[0], a[1], a[2], a[3], b0, b1); }
__device__ __forceinline__ uint32_t pin(uint32_t v) { asm volatile("shfl.sync.bfly.b32 %0, %0, 0, 31, -1;" : "+r"(v)); return v; }
template <class T> __device__ __forceinline__ T* pin(T* p) { const size_t a = (size_t)p; return (T*)(pin((uint32_t)a) | (size_t)pin((uint32_t)(a >> 32)) << 32); }
__device__ __forceinline__ void mmav(float (&c)[4], const uint32_t (&a)[4], uint32_t b0, uint32_t b1) {
    asm volatile("mma.sync.aligned.m16n8k16.row.col.f32.bf16.bf16.f32 {%0,%1,%2,%3}, {%4,%5,%6,%7}, {%8,%9}, {%0,%1,%2,%3};"
        : "+f"(c[0]), "+f"(c[1]), "+f"(c[2]), "+f"(c[3]) : "r"(a[0]), "r"(a[1]), "r"(a[2]), "r"(a[3]), "r"(b0), "r"(b1));
}
__device__ __forceinline__ uint32_t movm(uint32_t a) { uint32_t r; asm volatile("movmatrix.sync.aligned.m8n8.trans.b16 %0, %1;" : "=r"(r) : "r"(a)); return r; }
__device__ __forceinline__ uint32_t pack2(float lo, float hi) { uint32_t r; asm("cvt.rn.bf16x2.f32 %0, %1, %2;" : "=r"(r) : "f"(hi), "f"(lo)); return r; }
__device__ __forceinline__ float blo(uint32_t w) { return __uint_as_float(w << 16); }
__device__ __forceinline__ float bhi(uint32_t w) { return __uint_as_float(w & 0xFFFF0000u); }
__device__ __forceinline__ float rbf(float x) { return blo(pack2(x, 0.f)); }
__device__ __forceinline__ uint32_t add2(uint32_t a, uint32_t b) { uint32_t r; asm("add.rn.bf16x2 %0, %1, %2;" : "=r"(r) : "r"(a), "r"(b)); return r; }
__device__ __forceinline__ uint32_t sub2(uint32_t a, uint32_t b) { uint32_t r; asm("sub.rn.bf16x2 %0, %1, %2;" : "=r"(r) : "r"(a), "r"(b)); return r; }
__device__ __forceinline__ uint32_t mul2(uint32_t a, uint32_t b) { uint32_t r; asm("mul.rn.bf16x2 %0, %1, %2;" : "=r"(r) : "r"(a), "r"(b)); return r; }
constexpr uint32_t ONE2 = 0x3F803F80u;
constexpr float LOG2E = 1.4426950408889634f, SCALE = 0.08838834764831845f;
__device__ __forceinline__ float ex2(float x) { float y; asm("ex2.approx.ftz.f32 %0, %1;" : "=f"(y) : "f"(x)); return y; }
__device__ __forceinline__ uint4 ldg_rlx128(const void* p) {
    uint4 v; asm volatile("ld.relaxed.gpu.global.v4.u32 {%0,%1,%2,%3}, [%4];" : "=r"(v.x), "=r"(v.y), "=r"(v.z), "=r"(v.w) : "l"(p) : "memory"); return v;
}
__device__ __forceinline__ uint4 ldg_rlx2x64(const void* p) {
    unsigned long long a, b; asm volatile("ld.relaxed.gpu.global.v2.u64 {%0,%1}, [%2];" : "=l"(a), "=l"(b) : "l"(p) : "memory");
    return make_uint4((unsigned)a, (unsigned)(a >> 32), (unsigned)b, (unsigned)(b >> 32));
}
__device__ __forceinline__ uint2 ldg_rlx64(const void* p) {
    unsigned long long a; asm volatile("ld.relaxed.gpu.global.u64 %0, [%1];" : "=l"(a) : "l"(p) : "memory"); return make_uint2((unsigned)a, (unsigned)(a >> 32));
}
__device__ __forceinline__ unsigned ldg_acq32(const void* p) { unsigned v; asm volatile("ld.acquire.gpu.global.u32 %0, [%1];" : "=r"(v) : "l"(p) : "memory"); return v; }
__device__ __forceinline__ void red_add(void* p, unsigned v) { asm volatile("red.relaxed.gpu.global.add.u32 [%0], %1;" :: "l"(p), "r"(v) : "memory"); }
__device__ __forceinline__ unsigned now_ns() { unsigned t; asm volatile("mov.u32 %0, %%globaltimer_lo;" : "=r"(t)); return t; }
__device__ __forceinline__ void nap(unsigned ns) { asm volatile("nanosleep.u32 %0;" :: "r"(ns)); }
__device__ __forceinline__ unsigned ldg_rlx32(const void* p) { unsigned v; asm volatile("ld.relaxed.gpu.global.u32 %0, [%1];" : "=r"(v) : "l"(p) : "memory"); return v; }
__device__ __forceinline__ void stg_rlx32(void* p, unsigned v) { asm volatile("st.relaxed.gpu.global.u32 [%0], %1;" :: "l"(p), "r"(v) : "memory"); }
__device__ __forceinline__ void stg_rlx16(void* p, unsigned v) { asm volatile("st.relaxed.gpu.global.u16 [%0], %1;" :: "l"(p), "h"((unsigned short)v) : "memory"); }
__device__ __forceinline__ uint4 ldg_b128(const void* p) {
    unsigned long long a, b; asm volatile("{\n.reg .b128 x;\nld.relaxed.gpu.global.b128 x, [%2];\nmov.b128 {%0,%1}, x;\n}" : "=l"(a), "=l"(b) : "l"(p) : "memory");
    return make_uint4((unsigned)a, (unsigned)(a >> 32), (unsigned)b, (unsigned)(b >> 32));
}
__device__ __forceinline__ void stg_b128(void* p, uint4 v) {
    asm volatile("{\n.reg .b128 x;\nmov.b128 x, {%1,%2};\nst.relaxed.gpu.global.b128 [%0], x;\n}" :: "l"(p), "l"(v.x | ((unsigned long long)v.y << 32)), "l"(v.z | ((unsigned long long)v.w << 32)) : "memory");
}
__device__ __forceinline__ int rowoff(int b, int c) { return ((c >> 6) * 2 + ((c >> 2) & 1)) * 512 + b * 64 + (c & 3) * 16 + ((c >> 3) & 1) * 8 + ((c >> 5) & 1) * 4 + ((c >> 4) & 1) * 2; }
__device__ __forceinline__ void stg_rlx64(void* p, unsigned lo, unsigned hi) {
    unsigned long long a = lo | ((unsigned long long)hi << 32); asm volatile("st.relaxed.gpu.global.u64 [%0], %1;" :: "l"(p), "l"(a) : "memory");
}
__device__ __forceinline__ void stg_rlx128(void* p, uint4 v) { asm volatile("st.relaxed.gpu.global.v4.u32 [%0], {%1,%2,%3,%4};" :: "l"(p), "r"(v.x), "r"(v.y), "r"(v.z), "r"(v.w) : "memory"); }
__device__ __forceinline__ void sts32u(uint32_t a, unsigned x) { asm volatile("st.volatile.shared.u32 [%0], %1;" :: "r"(a), "r"(x) : "memory"); }
__device__ __forceinline__ unsigned lds32u(uint32_t a) { unsigned v; asm volatile("ld.volatile.shared.u32 %0, [%1];" : "=r"(v) : "r"(a) : "memory"); return v; }
__device__ __forceinline__ void spin(unsigned c0, unsigned d) { if (d) while ((unsigned)clock() - c0 < d) {} }
__device__ __forceinline__ void fence_gpu() { asm volatile("fence.acq_rel.gpu;" ::: "memory"); }
template <int ID, int N> __device__ __forceinline__ void bar_sync() { asm volatile("bar.sync %0, %1;" :: "n"(ID), "n"(N) : "memory"); }
template <int ID, int N> __device__ __forceinline__ void bar_arrive() { asm volatile("bar.arrive %0, %1;" :: "n"(ID), "n"(N) : "memory"); }
__device__ __forceinline__ void sts64(uint32_t a, float x, float y) { asm volatile("st.shared.v2.f32 [%0], {%1,%2};" :: "r"(a), "f"(x), "f"(y) : "memory"); }
__device__ __forceinline__ void sts128(uint32_t a, uint4 v) { asm volatile("st.volatile.shared.v4.u32 [%0], {%1,%2,%3,%4};" :: "r"(a), "r"(v.x), "r"(v.y), "r"(v.z), "r"(v.w) : "memory"); }
__device__ __forceinline__ void sts128f(uint32_t a, float x, float y, float z, float w) { asm volatile("st.volatile.shared.v4.f32 [%0], {%1,%2,%3,%4};" :: "r"(a), "f"(x), "f"(y), "f"(z), "f"(w) : "memory"); }
__device__ __forceinline__ void sts32(uint32_t a, float x) { asm volatile("st.shared.f32 [%0], %1;" :: "r"(a), "f"(x) : "memory"); }
__device__ __forceinline__ float2 lds64(uint32_t a) { float2 v; asm volatile("ld.shared.v2.f32 {%0,%1}, [%2];" : "=f"(v.x), "=f"(v.y) : "r"(a) : "memory"); return v; }
__device__ __forceinline__ float lds32(uint32_t a) { float v; asm volatile("ld.shared.f32 %0, [%1];" : "=f"(v) : "r"(a) : "memory"); return v; }
__device__ __forceinline__ float4 lds128(uint32_t a) { float4 v; asm volatile("ld.shared.v4.f32 {%0,%1,%2,%3}, [%4];" : "=f"(v.x), "=f"(v.y), "=f"(v.z), "=f"(v.w) : "r"(a) : "memory"); return v; }
__device__ __forceinline__ float2 sum8(uint32_t a) {
    float2 v[8];
#pragma unroll
    for (int i = 0; i < 8; i++) v[i] = lds64(a + i * SCR);
    return make_float2(((v[0].x + v[1].x) + (v[2].x + v[3].x)) + ((v[4].x + v[5].x) + (v[6].x + v[7].x)),
                       ((v[0].y + v[1].y) + (v[2].y + v[3].y)) + ((v[4].y + v[5].y) + (v[6].y + v[7].y)));
}
template <int STRIDE> __device__ __forceinline__ float4 sum8x4(uint32_t a) {
    float4 v[8];
#pragma unroll
    for (int i = 0; i < 8; i++) v[i] = lds128(a + i * STRIDE);
    return make_float4(((v[0].x + v[1].x) + (v[2].x + v[3].x)) + ((v[4].x + v[5].x) + (v[6].x + v[7].x)), ((v[0].y + v[1].y) + (v[2].y + v[3].y)) + ((v[4].y + v[5].y) + (v[6].y + v[7].y)),
                       ((v[0].z + v[1].z) + (v[2].z + v[3].z)) + ((v[4].z + v[5].z) + (v[6].z + v[7].z)), ((v[0].w + v[1].w) + (v[2].w + v[3].w)) + ((v[4].w + v[5].w) + (v[6].w + v[7].w)));
}
__device__ __forceinline__ float rcp(float x) { float y; asm("rcp.approx.ftz.f32 %0, %1;" : "=f"(y) : "f"(x)); return y; }
__device__ __forceinline__ float sigmoid_f(float x) { return rcp(1.0f + ex2(x * -LOG2E)); }
__device__ __forceinline__ uint32_t silu2(uint32_t c) { const float a = blo(c), b = bhi(c); return pack2(a * sigmoid_f(a), b * sigmoid_f(b)); }
__device__ __forceinline__ void ln_consts(float mean, float var, uint32_t& mu2, float& rs) {
    mu2 = pack2(mean, mean);
    float sd; asm("sqrt.approx.ftz.f32 %0, %1;" : "=f"(sd) : "f"(rbf(rbf(var) + 1e-5f)));
    rs = rcp(rbf(sd));
}
__device__ __forceinline__ uint32_t ln_norm(uint32_t x2, uint32_t mu2, float rs) { const uint32_t d = sub2(x2, mu2); return pack2(blo(d) * rs, bhi(d) * rs); }

__global__ void __launch_bounds__(NALL, 1) fused_kernel(const __nv_bfloat16* const px, const __nv_bfloat16* const pc, const __nv_bfloat16* const pk, const __nv_bfloat16* const pwm,
                                                        const __nv_bfloat16* const pwq, char* const X, const __grid_constant__ Params P) {
    extern __shared__ __align__(1024) unsigned char smem[];
    const uint32_t sb = smem_u32(smem);
    const int tid = threadIdx.x, w = tid >> 5, lane = tid & 31, g = lane >> 2, t = lane & 3;
    const int cta = blockIdx.x, head = cta >> 2, bat = (cta & 3) * 2 + (w >> 2);
    const uint32_t s0 = sb + w * UNIT, s2 = s0 + 4 * REG;
    const uint32_t bar0 = sb + SM_BAR + w * 64;
    const uint32_t barC = bar0 + 32;
    const uint32_t scr = sb + SM_SCR, myscr = scr + w * SCR;
    pf_if((const char*)pwm + ((cta * 4 + (lane >> 3)) * (6 * DM * 2) + w * 1024 + (lane & 7) * 128), w, 5);
    pf_if((const char*)pk + (unsigned)(((((cta & 3) * 2 + (w & 1)) * NH + head) * SK + (SK - WIN - 48) + tile_key(2) + (w >> 1) * 16) * (DH * 2) + lane * 128), w - 6, PFK);
    const int rid = !(cta & 1) ? cta >> 1 : (cta >> 2) + (cta & 2 ? 64 : 96);
    const unsigned t_start = now_ns();
    uint64_t pol;
    asm volatile("createpolicy.fractional.L2::evict_first.b64 %0, 1.0;" : "=l"(pol));
    auto go_first = [&](uint32_t wbar, uint32_t par) {
        for (int n = 0;; n++) {
            if (__all_sync(~0u, mbar_test(wbar, par))) return false;
            if (__all_sync(~0u, mbar_test(sb + SM_BG, 0))) return true;
            if (n > SPIN_MAX * 4) __trap();
            nap(20);
        }
    };
    if (w == 9) {
        const uint32_t sl = sb + SM_PR + lane * 16;
        char* const pl = X + blk(X_PRB, cta >> 1, lane & 1) + (lane >> 1) * 256 + (cta & 1) * 128;
        {
            char* const ps = X + X_PRB + (cta >> 1) * 8192 + g * 256 + (cta & 1) * 128 + t * 16;
            sts32u(sl, 0);
#pragma unroll
            for (int i = 0; i < 4; i++) stg_rlx128(ps + i * 2048, make_uint4(1, 1, 1, 1));
            __syncwarp();
        }
        unsigned v; asm volatile("atom.relaxed.gpu.global.add.u32 %0, [%1], 1;" : "=r"(v) : "l"(pl) : "memory");
        unsigned tag = ldg_rlx32(X + X_EPOCH);
        if (lane == 0) pf_bulk(pwq + (size_t)cta * QN * 1024, QN * 2048);
        if (lane == 0) sts32u(sb + SM_AN, t_start + ANCH0);
        if (lane < 8) sts32u(sb + SM_BAR + lane * 64 + 56, 0);
        unsigned side;
        {
            int d, n = 0;
#pragma unroll 1
            for (int r = 0; r < 4; r++) {
                if (v == SENT) __trap();
                asm volatile("cp.async.cg.shared.global [%0], [%1], 16;" :: "r"(sl), "l"(pl) : "memory");
                unsigned m;
                do {
                    m = __ballot_sync(~0u, lds32u(sl));
                    d = __popc(m & 0xAAAAAAAAu) - __popc(m & 0x55555555u);
                    if (++n > SPIN_MAX) __trap();
                } while (abs(d) < 6 && m != ~0u);
                if (abs(d) >= 6) break;
                asm volatile("cp.async.wait_all;" ::: "memory");
                sts32u(sl, 0);
                asm volatile("atom.relaxed.gpu.global.add.u32 %0, [%1], 1;" : "=r"(v) : "l"(pl) : "memory");
            }
            side = d > 0;
            tag++;
            if (lane == 0) { sts32u(sb + SM_SIDE, side); sts32u(sb + SM_TAG, tag); }
            bar_arrive<B_SIDE, NTHR>();
        }
        asm volatile("cp.async.wait_all;" ::: "memory");
        while (now_ns() - t_start < PACE0) nap(200);
        for (int n = 0; n < SPIN_MAX; n++) {
            const uint32_t wb = sb + SM_BAR + (lane & 7) * 64;
            const unsigned seen = lds32u(wb + 56), u = seen + ((lane >> 3) & 1), t1 = now_ns();
            const unsigned more = seen && mbar_test(wb + (u < 6 ? u : (~u & 2) + (u & 1)) * 8, u < 6 ? 0 : ((u - 2) >> 2) & 1);
            const unsigned lo = __reduce_min_sync(~0u, seen), sum = __reduce_add_sync(~0u, lane < 8 ? seen + more : lane < 16 ? more : 0);
            if (lo == 30) break;
            if (lo && lane < 2) stg_rlx64(X + X_LAG + (cta >> 5) * 8192 + lane * 4096 + (cta & 31) * 128, t1 - sum * TAU, tag);
            uint2 a = make_uint2(0, 0);
            if (cta == 0) {
                uint2 u[4];
#pragma unroll
                for (int i = 0; i < 4; i++) u[i] = ldg_rlx64(X + blk(X_LAG, i, side) + lane * 128);
                const int s = __reduce_add_sync(~0u, (int)(u[0].x + u[1].x + u[2].x + u[3].x - 4 * t_start));
                if (__all_sync(~0u, (u[0].y == tag) & (u[1].y == tag) & (u[2].y == tag) & (u[3].y == tag)) && lane < 2) {
                    a = make_uint2(t_start + s / NCTA, tag);
                    stg_rlx64(X + X_ANC + lane * 4096, a.x, tag);
                }
            } else if (lane == 0) a = ldg_rlx64(X + blk(X_ANC, 0, side));
            if (lane == 0 && a.y == tag) sts32u(sb + SM_AN, a.x - LEAD);
            __syncwarp();
            nap(PNAP);
        }
        {
            bar_sync<B_ML, NTHR>();
            const float2 ml = lds64(sb + SM_ML + (lane & 7) * 8);
            float M = fmaxf(ml.x, __shfl_xor_sync(~0u, ml.x, 1)); M = fmaxf(M, __shfl_xor_sync(~0u, M, 2));
            const float e = ex2((ml.x - M) * LOG2E);
            float L = e * ml.y; L += __shfl_xor_sync(~0u, L, 1); L += __shfl_xor_sync(~0u, L, 2);
            if (lane < 8) sts32(sb + SM_ML + 64 + lane * 4, e * rcp(L));
        }
        bar_arrive<B_RDY, NALL>();
        bar_sync<B_STG, 64>();
        {
            const char* const pp = pin(X + blk(X_PART, cta, side) + lane * 16);
            char* const xo = pin(X + (lane >> 4) * 16384 + blk(X_X1, (cta >> 3) & 1, lane >> 3) + (cta & 7) * 512 + (cta >> 4) * 64 + (lane & 7) * 8);
            const float4 gx = lds128(scr + SC_RX + (lane & 7) * 16);
            const unsigned t0 = lds32u(sb + SM_AN) + 256 * TAU + RT0 + (cta & 7) * (TAU / 8);
            while ((int)(now_ns() - t0) < 0) nap(20);
            uint4 v[8]; int n = 0;
            float a[4];
#pragma unroll
            for (int j = 0; j < 8; j++) v[j] = ldg_b128(pp + j * 512);
            while (true) {
#define RSUM(f) (((__uint_as_float(v[0].f) + __uint_as_float(v[1].f)) + (__uint_as_float(v[2].f) + __uint_as_float(v[3].f))) + ((__uint_as_float(v[4].f) + __uint_as_float(v[5].f)) + (__uint_as_float(v[6].f) + __uint_as_float(v[7].f))))
                const bool ok = __all_sync(~0u, max(max(max(v[0].x, v[1].x), max(v[2].x, v[3].x)), max(max(v[4].x, v[5].x), max(v[6].x, v[7].x))) != SENT);
                a[0] = RSUM(x); a[1] = RSUM(y); a[2] = RSUM(z); a[3] = RSUM(w);
                asm volatile("" : "+f"(a[0]), "+f"(a[1]), "+f"(a[2]), "+f"(a[3]));
                if (ok) break;
#pragma unroll
                for (int j = 0; j < 8; j++) if (v[j].x == SENT) v[j] = ldg_b128(pp + j * 512);
                if (++n > SPIN_MAX) __trap();
            }
#pragma unroll
            for (int i = 0; i < 4; i++) a[i] += __shfl_xor_sync(~0u, a[i], 8);
#pragma unroll
            for (int i = 0; i < 4; i++) a[i] += __shfl_xor_sync(~0u, a[i], 16);
            stg_rlx64(xo, add2(__float_as_uint(gx.z), mul2(__float_as_uint(gx.x), pack2(a[0], a[1]))), add2(__float_as_uint(gx.w), mul2(__float_as_uint(gx.y), pack2(a[2], a[3]))));
        }
        if (rid >= DN0) {
            const unsigned c1 = clock();
            const int f = rid - DN0;
            const char* const rp = X + (rid & (XC - 1)) * 16384 + blk(X_X1, f >> 4, side) + (rowoff(g, f * 16 + t * 4) & 4092);
            unsigned r[4]; int n = 0;
            spin(c1, HD0 - 450);
            do {
#pragma unroll
                for (int i = 0; i < 4; i++) r[i] = ldg_rlx32(rp + i * 16);
                if (++n > SPIN_MAX) __trap();
            } while (max(max(r[0], r[1]), max(r[2], r[3])) == SENT);
            const unsigned sel = (f & 1) ? 0x7632 : 0x5410;
            sts64(sb + SM_MN + 256 + lane * 8, __uint_as_float(__byte_perm(r[0], r[1], sel)), __uint_as_float(__byte_perm(r[2], r[3], sel)));
            __syncwarp();
            spin(c1, HD0);
        }
        if (lane == 0) asm volatile("mbarrier.arrive.shared::cta.b64 _, [%0];" :: "r"(sb + SM_BG) : "memory");
    } else if (w == 8) {
        const int row0 = ((cta & 3) * 2 * NH + head) * SK + (SK - WIN);
        auto kv_unit = [&](int u) {
            const uint32_t b = sb + SM_BAR + (u & 7) * 64 + (u >> 3) * 8;
            mbar_expect(b, UNIT);
            tma_kv(sb + (u >> 3) * REG + (u & 7) * UNIT, (u & 8) ? &P.v : &P.k, row0 + ((u >> 2) & 1) * NH * SK + (u & 3) * 16 + tile_key(u >> 4), b, pol);
        };
        if (elect()) {
            mbar_init(sb + SM_BM, 1);
#pragma unroll
            for (int i = 0; i < 8; i++) mbar_init(sb + SM_BAR + i * 64 + 48, 1);
            asm volatile("fence.mbarrier_init.release.cluster;" ::: "memory");
            mbar_expect(sb + SM_BM, 512 * 16);
            tma2d(sb + 4 * REG, &P.wm, cta * 8, 0, sb + SM_BM); tma2d(sb + 4 * REG + 256 * 16, &P.wm, cta * 8, 256, sb + SM_BM);
#pragma unroll
            for (int i = 0; i < 8; i++) { const uint32_t b = sb + SM_BAR + i * 64 + 48; mbar_expect(b, UNIT); tma2d(sb + 5 * REG + i * UNIT, &P.wq, cta * 32, i * 64, b); }
            mbar_init(sb + SM_BN, 1); mbar_init(sb + SM_BT, 1); mbar_init(sb + SM_BG, 1);
#pragma unroll
            for (int i = 0; i < 48; i++) mbar_init(sb + SM_BAR + (i & 7) * 64 + (i >> 3) * 8, 1);
            asm volatile("fence.mbarrier_init.release.cluster;" ::: "memory");
        }
        __syncwarp();
        bar_arrive<B_INIT, NTHR>();
        {
            uint32_t mine = lane >= NTRK ? 0 : lane < 8 ? sb + SM_BAR + lane * 64 + 48 : sb + SM_BM;
            int next = 0, lim = 32, n = 0;
            while (next < 48) {
                const bool idle = lane < (next < PSW ? PWIN0 : PWIN) && (mine == 0 || mbar_test(mine, 0));
                const unsigned m = __ballot_sync(~0u, idle);
                const int u = next + __popc(m & ((1u << lane) - 1));
                if (idle) {
                    mine = 0;
                    if (u < lim) { kv_unit(u); mine = sb + SM_BAR + (u & 7) * 64 + (u >> 3) * 8; }
                }
                next = min(next + __popc(m), lim);
                if (next == lim) {
                    if (lim == 32) { bar_sync<B_MOD, NTHR>(); } else if (lim == 40) { bar_sync<B_WQ, NTHR>(); }
                    lim += 8;
                }
                if (!m) nap(30);
                if (++n > SPIN_MAX) __trap();
            }
        }
        if (lane < 5) pf_map(&P.wn + lane);
        float m[4][4] = {};
        auto late_mod = [&](uint32_t a, int h) {
            const int lrow = (lane & 7) + ((lane >> 4) << 3), lch = (lane >> 3) & 1;
            const uint32_t a0 = a + lrow * 32 + ((lch ^ ((lrow >> 2) & 1)) << 4);
            const uint32_t c0 = sb + SM_SC + h * 4096 + (lane & 7) * 128 + (((lane >> 3) ^ (lane & 7)) << 4);
#pragma unroll
            for (int j = 0; j < 8; j++) {
                uint32_t c[4], r[4], u[4];
                ldsm(c, (c0 + (j >> 1) * 1024) ^ ((j & 1) << 6)); ldsm_t(r, a0 + j * 1024); ldsm_t(u, a0 + j * 1024 + 512);
                mma(m[(j & 1) * 2], r, c[0], c[1]); mma(m[(j & 1) * 2 + 1], u, c[2], c[3]);
            }
        };
        if (rid < 96) {
#pragma unroll 1
            for (int h = 0; h < 2; h++) {
                if (lane == 0) { mbar_expect(sb + SM_BN, 8192); tma2d(sb + SM_MN, &P.wn, 2 * DM + rid * 16, h * 256, sb + SM_BN); }
                mbar_wait(sb + SM_BN, h);
                late_mod(sb + SM_MN, h);
                asm volatile("" :: "f"(m[0][0]), "f"(m[1][0]), "f"(m[2][0]), "f"(m[3][0]) : "memory");
                __syncwarp();
            }
#pragma unroll
            for (int e = 0; e < 4; e++) {
                float v = rbf((m[0][e] + m[1][e]) + (m[2][e] + m[3][e]));
                if (rid >= 64) v += 1.0f;
                stg_rlx16(X + X_MOD + (rid >> 5) * 8192 + rowoff(2 * t + (e & 1), (rid & 31) * 16 + g + (e >> 1) * 8), pack2(v, 0.f));
            }
        }
        {
            const unsigned side = lds32u(sb + SM_SIDE);
#pragma unroll
            for (int i = 0; i < 8; i++) stg_rlx128(X + blk(X_PART, cta, side) + i * 512 + lane * 16, make_uint4(SENT, SENT, SENT, SENT));
            if (lane == 0) stg_rlx32(X + X_SIDE + cta * 4, side);
        }
        bar_sync<B_Q, NTHR>();
        if (lane == 0) {
            const unsigned tag = lds32u(sb + SM_TAG);
            fence_gpu();
            red_add(X + X_READY, 1);
            int n = 0;
            while ((int)(ldg_acq32(X + X_READY) - tag * NCTA) < 0) { nap(1000); if (++n > SPIN_MAX) __trap(); }
            if (cta == 0) stg_rlx32(X + X_EPOCH, tag);
        }
        __syncwarp();
        {
            stg_rlx128(X + blk(X_Q, head >> 1, 0) + (head & 1) * 2048 + g * 256 + (cta & 3) * 64 + t * 16, make_uint4(0, 0, 0, 0));
            stg_rlx128(X + blk(X_Q, head >> 1, 1) + (head & 1) * 2048 + g * 256 + (cta & 3) * 64 + t * 16, make_uint4(0, 0, 0, 0));
            stg_rlx64(X + blk(X_M1, cta >> 5, lane >> 4) + (cta & 31) * 128 + (lane & 15) * 8, 0, 0);
            const int wt = (cta & 3) * 32 + lane;
            const unsigned mask = __ballot_sync(~0u, blk(X_PART, wt, ldg_rlx32(X + X_SIDE + wt * 4)) & 4096);
            if (lane == 0) sts32u(sb + SM_MASK, mask);
            if (lane < 8) {
                const int rb = cta >> 4, c = ((cta & 15) >> 1) * 64 + (cta & 1) * 4 + (lane >> 1) + (lane & 1) * 8;
                const uint2 ga = ldg_rlx64(X + X_MOD + rowoff(rb, c));
                const unsigned short* const xp = (const unsigned short*)px + rb * DM + c;
                sts128(scr + SC_RX + lane * 16, make_uint4(ga.x, ga.y, xp[0] | (xp[16] << 16), xp[32] | (xp[48] << 16)));
            }
            if (rid < NF1) {
#pragma unroll 1
                for (int i = 0; i < 4; i++) {
                    uint4 v[8];
#pragma unroll
                    for (int j = 0; j < 8; j++) v[j] = ldg_rlx128(X + X_MOD + 8192 + (i * 8 + j) * 512 + lane * 16);
#pragma unroll
                    for (int j = 0; j < 8; j++) sts128(sb + SM_MN + (i * 8 + j) * 512 + lane * 16, v[j]);
                }
            }
        }
        bar_arrive<B_RDY, NALL>();
        bar_arrive<B_STG, 64>();
        for (int n = 0; __any_sync(~0u, lds32u(sb + SM_BAR + (lane & 7) * 64 + 56) < 30); n++) { nap(100); if (n > SPIN_MAX) __trap(); }
        const unsigned t_ref = lds32u(sb + SM_AN) + 256 * TAU + (cta & 7) * (TAU / 8);
        auto until = [&](int x) { while ((int)(now_ns() - t_ref) < x) nap(20); };
        if (lane < 16) mbar_expect(sb + SM_BAR + (lane & 7) * 64 + 32 + (lane & 8), UNIT);
        __syncwarp();
        if (elect()) {
#pragma unroll 1
            for (int i = 0; i < 16; i += 2) {
                until(WO0 + (i & 7) * WOS + (i >> 3) * WOG);
#pragma unroll
                for (int j = i; j < i + 2; j++) tma2d(sb + 4 * REG + j * UNIT, &P.wo, (j & 7) * 64, head * 128 + 64 + (j & 8) * 4, sb + SM_BAR + (j & 7) * 64 + 32 + (j & 8));
            }
        }
        if (rid < NF1) {
            if (elect()) {
#pragma unroll
                for (int i = 0; i < 4; i++) mbar_expect(sb + SM_BAR + i * 64 + 48, 2 * UNIT);
#pragma unroll 1
                for (int i = 0; i < 4; i++) {
                    const uint32_t b = sb + SM_BAR + i * 64 + 48;
                    until(W0 + i * WS);
                    tma5d(sb + 2 * REG + i * UNIT, &P.wg, rid * 16, i * 4, b); tma5d(sb + 2 * REG + 16384 + i * UNIT, &P.wu, rid * 16, i * 4, b);
                }
            }
        } else if (rid >= DN0) {
            bar_sync<B_LAST, NTHR>();
            if (elect()) {
                mbar_expect(sb + SM_BN, 16384); mbar_expect(sb + SM_BT, FF * 32);
                until(WD0);
                tma5d(sb + 2 * REG + 16384, &P.wd, (rid - DN0) * 16, 0, sb + SM_BT);
                tma2d(sb + 2 * REG, &P.wn, 2 * DM + rid * 16, 0, sb + SM_BN); tma2d(sb + 2 * REG + 8192, &P.wn, 2 * DM + rid * 16, 256, sb + SM_BN);
            }
        }
        __syncwarp();
        if (rid >= DN0) {
            mbar_wait(sb + SM_BN, 0);
            late_mod(sb + 2 * REG, 0); late_mod(sb + 2 * REG + 8192, 1);
#pragma unroll
            for (int e = 0; e < 2; e++)
                sts32u(sb + SM_MN + g * 32 + e * 16 + t * 4, movm(pack2((m[0][2 * e] + m[1][2 * e]) + (m[2][2 * e] + m[3][2 * e]), (m[0][2 * e + 1] + m[1][2 * e + 1]) + (m[2][2 * e + 1] + m[3][2 * e + 1]))));
            bar_arrive<B_DN, NTHR>();
        }
    }
    if (w >= 8) {
        if (rid < NF1) {
            const int b = (tid - 256) >> 3, c = tid & 7;
            char* const ho = pin(X + X_HM + (rid >> 4) * 8192 + ((rid >> 1) & 7) * 512 + b * 64 + (rid & 1) * 32 + c * 4);
            const uint32_t pi = pin(scr + SC_F1 + c * 144 + b * 16), si = pin(sb + SM_ST + b * 64);
            bar_sync<B_PRE, NALL>();
            float4 C = sum8x4<UNIT>(sb + REG + c * 144 + b * 16), S = sum8x4<UNIT>(sb + REG + 1152 + c * 144 + b * 16);
            S.x *= -LOG2E; S.y *= -LOG2E; C.x *= LOG2E; C.y *= LOG2E;
            sts128f(sb + SM_PR + lane * 16, C.x, C.y, C.z, C.w); sts128f(sb + SM_PR + lane * 16, S.x, S.y, S.z, S.w);
            sts128(sb + SM_PR + lane * 16, make_uint4(pi, si, (uint32_t)(size_t)ho, (uint32_t)((size_t)ho >> 32)));
            bar_sync<B_FIN, NALL>();
            const float4 s0_ = lds128(si), s1_ = lds128(si + 16), s2_ = lds128(si + 32), s3_ = lds128(si + 48);
            const float4 p = sum8x4<SCR>(pi);
            const float mean = (((s0_.x + s0_.z) + (s1_.x + s1_.z)) + ((s2_.x + s2_.z) + (s3_.x + s3_.z))) * (1.0f / DM);
            const float sq = (((s0_.y + s0_.w) + (s1_.y + s1_.w)) + ((s2_.y + s2_.w) + (s3_.y + s3_.w))) * (1.0f / DM);
            float rs; asm("rsqrt.approx.ftz.f32 %0, %1;" : "=f"(rs) : "f"(fmaxf(sq - mean * mean, 0.f) + 1e-5f));
            const float e0 = rs * (mean * C.x - LOG2E * p.x) + S.x, e1 = rs * (mean * C.y - LOG2E * p.y) + S.y;
            const float u0 = rs * (p.z - mean * C.z) + S.z, u1 = rs * (p.w - mean * C.w) + S.w;
            const unsigned hw = pack2(rcp(1.0f + ex2(e0)) * u0, rcp(1.0f + ex2(e1)) * u1);
            stg_rlx32(ho, hw); stg_rlx32(ho + 4096, hw);
        }
        return;
    }
    const unsigned ce = (lane >> 3) * (DM * 2) + w * 128 + (lane & 7) * 16;
    const uint4 ca = ldg_nc((const char*)pc + ce), cb = ldg_nc((const char*)pc + ce + 4 * DM * 2);
    const uint4 xa = ldg_nc((const char*)px + w * (DM * 2) + lane * 16), xb = ldg_nc((const char*)px + w * (DM * 2) + lane * 16 + 512);
    const uint4 xc = ldg_nc((const char*)px + ce), xd = ldg_nc((const char*)px + ce + 4 * DM * 2);
    if (w >= 4) pf_map(&P.wm + (w & 3));
    char* const qout = X + blk(X_Q, head >> 1, tid >> 7) + (head & 1) * 2048 + ((tid >> 4) & 7) * 256 + (cta & 3) * 64 + (tid & 3) * 16 + ((tid >> 2) & 3) * 4;
    char* const mout = X + blk(X_M1, cta >> 5, w) + (cta & 31) * 128 + lane * 4;
    stg_rlx32(qout, 0);
    if (w < 2) stg_rlx32(mout, 0);
    uint32_t sc[8], xf[8];
    {
        const uint32_t a = (lane >> 3) * 128 + (((lane & 7) ^ (lane >> 3)) << 4), b = (lane & 7) * 128 + (((lane >> 3) ^ (lane & 7)) << 4);
        const uint32_t cs = sb + SM_SC + w * 1024;
        sts128(cs + a, make_uint4(silu2(ca.x), silu2(ca.y), silu2(ca.z), silu2(ca.w)));
        sts128(cs + 512 + (a ^ 64), make_uint4(silu2(cb.x), silu2(cb.y), silu2(cb.z), silu2(cb.w)));
        sts128(myscr + a, xc); sts128(myscr + 512 + (a ^ 64), xd);
        __syncwarp();
        ldsm(*(uint32_t(*)[4])&sc[0], cs + b); ldsm(*(uint32_t(*)[4])&sc[4], cs + (b ^ 64));
        ldsm(*(uint32_t(*)[4])&xf[0], myscr + b); ldsm(*(uint32_t(*)[4])&xf[4], myscr + (b ^ 64));
        __syncwarp();
    }
    {
        float v[16] = {blo(xa.x), bhi(xa.x), blo(xa.y), bhi(xa.y), blo(xa.z), bhi(xa.z), blo(xa.w), bhi(xa.w),
                       blo(xb.x), bhi(xb.x), blo(xb.y), bhi(xb.y), blo(xb.z), bhi(xb.z), blo(xb.w), bhi(xb.w)};
        float s = 0;
#pragma unroll
        for (int i = 0; i < 16; i++) s += v[i];
#pragma unroll
        for (int o = 16; o; o >>= 1) s += __shfl_xor_sync(~0u, s, o);
        s *= (1.0f / DM);
        float q2 = 0;
#pragma unroll
        for (int i = 0; i < 16; i++) q2 += (v[i] - s) * (v[i] - s);
#pragma unroll
        for (int o = 16; o; o >>= 1) q2 += __shfl_xor_sync(~0u, q2, o);
        uint32_t mu2; float rs; ln_consts(s, q2 * (1.0f / DM), mu2, rs);
        if (lane == 0) sts64(sb + SM_ST + w * 8, __uint_as_float(mu2), rs);
    }
    const int lrow = (lane & 7) + ((lane >> 4) << 3), lch = (lane >> 3) & 1;
    const uint32_t off64 = lrow * 64 + ((lch ^ ((lrow >> 1) & 3)) << 4);
    const uint32_t off128 = lrow * 128 + ((lch ^ (lane & 7)) << 4);
    bar_sync<B_INIT, NTHR>();
    mbar_wait(sb + SM_BM, 0);
    {
        float a[4] = {0, 0, 0, 0}, b[4] = {0, 0, 0, 0};
        uint32_t r[4], u[4];
        ldsm_t(r, sb + 4 * REG + (w * 64 + lane) * 16); ldsm_t(u, sb + 4 * REG + (w * 64 + 32 + lane) * 16);
        mma(a, sc[0], 0, sc[1], 0, r[0], r[1]); mma(b, sc[4], 0, sc[5], 0, u[0], u[1]);
        mma(a, sc[2], 0, sc[3], 0, r[2], r[3]); mma(b, sc[6], 0, sc[7], 0, u[2], u[3]);
        sts64(myscr + SC_M + lane * 8, a[0] + b[0], a[1] + b[1]);
    }
    bar_arrive<B_MOD, NTHR>();
    bar_sync<B_ALL, 256>();
    if (w < 2) {
        const float2 m = sum8(scr + SC_M + lane * 8);
        stg_rlx32(mout, ~pack2(m.x, m.y));
    }
    if (tid < 8 * XC) stg_rlx128(X + X_X1 + (cta * 8 * XC + tid) * 16, make_uint4(SENT, SENT, SENT, SENT));
    else if (tid >= 232) stg_rlx128(X + X_HM + (cta * 24 + tid - 232) * 16, make_uint4(SENT, SENT, SENT, SENT));
    {
        const float2 st = lds64(sb + SM_ST + g * 8);
#pragma unroll
        for (int i = 0; i < 8; i++) xf[i] = ln_norm(xf[i], __float_as_uint(st.x), st.y);
    }
    {
        unsigned sv[8], cv[8]; int n = 0;
        bar_sync<B_SIDE, NTHR>();
        const char* const mp = X + blk(X_M1, w >> 2, lds32u(sb + SM_SIDE)) + (w & 3) * 1024 + lane * 4;
        if (lane == 0) while (!ldg_rlx32(mp + 16384 + 7 * 128)) { nap(40); if (++n > SPIN_MAX) __trap(); }
        __syncwarp();
#pragma unroll
        for (int j = 0; j < 8; j++) { sv[j] = ldg_rlx32(mp + j * 128); cv[j] = ldg_rlx32(mp + 16384 + j * 128); }
        while (true) {
            unsigned m = ~0u;
#pragma unroll
            for (int j = 0; j < 8; j++) m = min(m, min(sv[j], cv[j]));
            if (__all_sync(~0u, m)) break;
#pragma unroll
            for (int j = 0; j < 8; j++) { if (!sv[j]) sv[j] = ldg_rlx32(mp + j * 128); if (!cv[j]) cv[j] = ldg_rlx32(mp + 16384 + j * 128); }
            if (++n > SPIN_MAX) __trap();
        }
#pragma unroll
        for (int j = 0; j < 8; j++) xf[j] = add2(mul2(xf[j], add2(~cv[j], ONE2)), ~sv[j]);
        mbar_wait(bar0 + 48, 0);
        float acc[4][4] = {};
#pragma unroll
        for (int j = 0; j < 4; j++) {
            uint32_t r[4], u[4];
            ldsm_t(r, s2 + REG + j * 1024 + off64); ldsm_t(u, s2 + REG + j * 1024 + (off64 ^ 32));
            mma(acc[0], xf[2 * j], 0, xf[2 * j + 1], 0, r[0], r[2]); mma(acc[1], xf[2 * j], 0, xf[2 * j + 1], 0, r[1], r[3]);
            mma(acc[2], xf[2 * j], 0, xf[2 * j + 1], 0, u[0], u[2]); mma(acc[3], xf[2 * j], 0, xf[2 * j + 1], 0, u[1], u[3]);
        }
#pragma unroll
        for (int n2 = 0; n2 < 4; n2++) sts64(myscr + SC_Q + g * 160 + n2 * 32 + t * 8, acc[n2][0], acc[n2][1]);
    }
    bar_arrive<B_WQ, NTHR>();
    bar_sync<B_ALL, 256>();
    {
        const float2 s = sum8(scr + SC_Q + ((tid >> 4) & 7) * 160 + (tid & 15) * 8);
        stg_rlx32(qout, ~pack2(s.x, s.y));
    }
    uint32_t q[16];
    {
        int n = 0;
        const char* const qp = X + blk(X_Q, head >> 1, lds32u(sb + SM_SIDE)) + (head & 1) * 2048 + bat * 256 + t * 16;
        uint4 v[4];
#pragma unroll
        for (int j = 0; j < 4; j++) v[j] = ldg_rlx128(qp + j * 64);
        while (true) {
            bool bad[4];
#pragma unroll
            for (int j = 0; j < 4; j++) bad[j] = !min(min(v[j].x, v[j].y), min(v[j].z, v[j].w));
            if (!__any_sync(~0u, bad[0] | bad[1] | bad[2] | bad[3])) break;
#pragma unroll
            for (int j = 0; j < 4; j++) if (bad[j]) v[j] = ldg_rlx128(qp + j * 64);
            if (++n > SPIN_MAX) __trap();
        }
#pragma unroll
        for (int j = 0; j < 4; j++) { q[4 * j] = ~v[j].x; q[4 * j + 1] = ~v[j].y; q[4 * j + 2] = ~v[j].z; q[4 * j + 3] = ~v[j].w; }
    }
    bar_arrive<B_Q, NTHR>();

    float o[2][4] = {};
    float mrun = -3.0e38f, lrun = 0.f;
    uint32_t wa[16][4], pb[2];
#pragma unroll
    for (int i = 0; i < 16; i++) wa[i][0] = wa[i][1] = wa[i][2] = wa[i][3] = 0;
    const uint32_t offk = (lane & 15) * 128 + (((lane >> 4) ^ (lane & 7)) << 4);
    float p0, p1;
    auto scores = [&](uint32_t a0) {
        uint32_t kf[8][4];
#pragma unroll
        for (int j = 0; j < 8; j++) ldsm(kf[j], ((a0 + offk) ^ ((j & 3) << 5)) + (j >> 2) * 2048);
        float sa[4] = {0, 0, 0, 0}, sb2[4] = {0, 0, 0, 0};
#pragma unroll
        for (int j = 0; j < 8; j += 2) { mma(sa, kf[j], q[2 * j], q[2 * j + 1]); mma(sb2, kf[j + 1], q[2 * j + 2], q[2 * j + 3]); }
        uint32_t u = pack2(sa[0] + sb2[0], sa[2] + sb2[2]);
        u = pack2(blo(u) * SCALE, bhi(u) * SCALE);
        const float z0 = blo(u), z1 = bhi(u);
        float mx = fmaxf(z0, z1);
        mx = fmaxf(mx, __shfl_xor_sync(~0u, mx, 4)); mx = fmaxf(mx, __shfl_xor_sync(~0u, mx, 8)); mx = fmaxf(mx, __shfl_xor_sync(~0u, mx, 16));
        mx = fmaxf(mx, mrun);
        const float f = ex2((mrun - mx) * LOG2E);
        p0 = ex2((z0 - mx) * LOG2E); p1 = ex2((z1 - mx) * LOG2E);
        mrun = mx; lrun = lrun * f + (p0 + p1);
#pragma unroll
        for (int j = 0; j < 4; j++) { o[0][j] *= f; o[1][j] *= f; }
    };
    const int kvrow = (bat * NH + head) * SK + (SK - WIN) + (w & 3) * 16;
    const int wofs = (w * 8 + (cta & 7)) * TAU / 8;
    auto request = [&](int u) {
        sts32u(bar0 + 56, u - 1);
        while ((int)(now_ns() - lds32u(sb + SM_AN) - u * 8 * TAU - wofs) < 0) nap(20);
        const int sl = (~u & 2) + (u & 1);
        mbar_expect(bar0 + sl * 8, UNIT); tma_kv(s0 + sl * REG, &P.k + (u & 1), kvrow + tile_key(u >> 1), bar0 + sl * 8, pol);
    };
#pragma unroll 1
    for (int it = 0; it < NT - 1; it++) {
        const int si = it < 3 ? it : (it + 1) & 1;
        const uint32_t bar = bar0 + si * 16, a0 = s0 + si * 2 * REG;
        const uint32_t par = it < 3 ? 0 : ((it - 1) >> 1) & 1;
        const bool refill = lane == 0 && it >= 2;
        mbar_wait(bar, par);
        if (refill) {
            request(2 * it + 2);
            const int e = it - WOA_ISSUE;
            if (e == 0) mbar_expect(barC, 2 * UNIT);
            if (e == 0 || e == WO_GAP) tma2d(s2 + (e ? REG : 0), &P.wo, w * 64, head * 128 + (e ? 32 : 0), barC);
        }
        __syncwarp();
        if (it == WOA_READ) {
            mbar_wait(barC, 1);
#pragma unroll
            for (int j = 0; j < 16; j++) ldsm_t(wa[j], s2 + (j >> 3) * REG + ((j >> 2) & 1) * 2048 + (off128 ^ ((j & 3) << 5)));
        }
        scores(a0);
        pb[0] = movm(pack2(p0, p0)); pb[1] = movm(pack2(p1, p1));
        mbar_wait(bar + 8, par);
        if (refill) request(2 * it + 3);
        __syncwarp();
        uint32_t vf[8][4];
#pragma unroll
        for (int j = 0; j < 8; j++) ldsm_t(vf[j], ((a0 + off128) ^ ((j & 3) << 5)) + (j >> 2) * 2048 + REG);
#pragma unroll
        for (int j = 0; j < 8; j++) { const bool on = (g >> 1) == (j >> 1); mma(o[j & 1], vf[j], on ? pb[0] : 0, on ? pb[1] : 0); }
    }
    {
        uint32_t wb[16][4];
        mbar_wait(bar0, 1);
        if (rid >= DN0) bar_arrive<B_LAST, NTHR>();
        scores(s0);
        lrun += __shfl_xor_sync(~0u, lrun, 4); lrun += __shfl_xor_sync(~0u, lrun, 8); lrun += __shfl_xor_sync(~0u, lrun, 16);
        if (lane == 0) sts64(sb + SM_ML + w * 8, mrun, lrun);
        bar_arrive<B_ML, NTHR>();
        pb[0] = movm(pack2(p0, p0)); pb[1] = movm(pack2(p1, p1));
        const uint32_t va = pin(s0 + REG + off128);
        auto load_wb = [&](int j) { ldsm_t(wb[j], (va ^ ((j & 3) << 5)) + (3 + (j >> 3)) * REG + ((j >> 2) & 1) * 2048); };
        const uint32_t ho = pin(s0 + w * 16 + ((lane & 7) >> 1) * 64 + ((lane >> 3) & 1) * 32 + (lane & 1) * 16), oa = pin(sb + (lane & 7) * (UNIT + 16) + (lane >> 3) * 16);
        const uint32_t rd = pin((t >> 1) * 16 + w * 2 + (g >> 2));
        char* const pp = pin(X + X_PART + ((cta & 3) * 32 + rd) * 8192 + head * 128 + (g & 3) * 32 + (t & 1) * 16);
        const uint32_t ln = pin(lane), wbar = pin(barC + 8);
        mbar_wait(bar0 + 8, 1);
        {
            uint32_t vf[8][4];
            float o2[2][4] = {};
#pragma unroll
            for (int j = 0; j < 8; j++) ldsm_t(vf[j], (va ^ ((j & 3) << 5)) + (j >> 2) * 2048);
#pragma unroll
            for (int j = 0; j < 8; j++) { const bool on = (ln >> 3) == (j >> 1); mma((j & 2) ? o2[j & 1] : o[j & 1], vf[j], on ? pb[0] : 0, on ? pb[1] : 0); }
            asm volatile("stmatrix.sync.aligned.m8n8.x2.trans.shared.b16 [%0], {%1,%2};" :: "r"(ho), "r"(pack2(o[0][0] + o2[0][0], o[0][2] + o2[0][2])), "r"(pack2(o[1][0] + o2[1][0], o[1][2] + o2[1][2])) : "memory");
        }
        bar_sync<B_RDY, NALL>();
        float y[4][4] = {};
        uint32_t ob[4][4];
#pragma unroll
        for (int i2 = 0; i2 < 4; i2++) ldsm(ob[i2], oa + i2 * 64);
        const float2 f = lds64(sb + SM_ML + 64 + (ln & 3) * 8);
        const unsigned half = (lds32u(sb + SM_MASK) >> rd & 1) * 4096;
#pragma unroll
        for (int j = 0; j < 8; j++) {
            if (j == WK) {
                if (!mbar_test(wbar - 8, 0)) mbar_wait(wbar - 8, 0);
#pragma unroll
                for (int k = 0; k < 8; k++) load_wb(k);
            }
            if (j == WJ) {
                if (!mbar_test(wbar, 1)) mbar_wait(wbar, 1);
#pragma unroll
                for (int k = 8; k < 16; k++) load_wb(k);
            }
#pragma unroll
            for (int i = 0; i < 4; i++) mmav(y[i], j < 4 ? wa[j * 4 + i] : wb[(j - 4) * 4 + i], ob[j >> 1][2 * (j & 1)], ob[j >> 1][2 * (j & 1) + 1]);
        }
        uint32_t r[4];
#pragma unroll
        for (int i = 0; i < 4; i++) {
            const float lo = f.x * y[i][0] + f.y * y[i][1], hi = f.x * y[i][2] + f.y * y[i][3];
            r[i] = __float_as_uint(((ln & 1) ? hi : lo) + __shfl_xor_sync(~0u, (ln & 1) ? lo : hi, 1));
        }
        asm("min.u32 %0, %0, 0xFFFFFFFE;" : "+r"(r[0]));
        stg_b128(pp + half, make_uint4(r[0], r[1], r[2], r[3]));
    }
    const unsigned side = lds32u(sb + SM_SIDE);
    const char* const x1p = X + (rid & (XC - 1)) * 16384;
    if (rid < NF1) {
        uint32_t wg[4][4], wu[4][4];
        const char* const xp = pin(x1p + blk(X_X1, w >> 2, side) + (w & 3) * 1024 + lane * 16);
        float4 c1[2], sv[2];
#pragma unroll
        for (int h = 0; h < 2; h++) { sv[h] = lds128(sb + SM_MN + (w * 2 + h) * 512 + lane * 16); c1[h] = lds128(sb + SM_MN + 8192 + (w * 2 + h) * 512 + lane * 16); }
        const uint32_t po = pin(myscr + SC_F1 + g * 144 + t * 32), so = pin(t == (g >> 1) ? sb + SM_ST + g * 64 + w * 8 : myscr + 1792 + lane * 8), odd = pin(g & 1);
        const uint32_t wbar = sb + SM_BAR + (w >> 1) * 64 + 48;
        uint4 x0, x1;
        const bool early = go_first(wbar, 1);
        if (early) { spin(clock(), (7 - w) * XDW); x0 = ldg_rlx2x64(xp); x1 = ldg_rlx2x64(xp + 512); mbar_wait(wbar, 1); }
#pragma unroll
        for (int j = 0; j < 4; j++) {
            const uint32_t a = sb + 2 * REG + w * 2048 + (((lane & 7) >> 1) + (lane & 1) * 4 + j * 8 + (lane >> 4) * 32) * 32 + ((lch ^ (lane & 1)) << 4);
            ldsm_t(wg[j], a); ldsm_t(wu[j], a + 16384);
        }
        {
            float cg[4] = {}, cu[4] = {}, sg[4] = {}, su[4] = {};
#pragma unroll
            for (int j = 0; j < 4; j++) {
                const float4 a = c1[j & 1], b = sv[j & 1];
                const uint32_t a0 = __float_as_uint(j >> 1 ? a.z : a.x), a1 = __float_as_uint(j >> 1 ? a.w : a.y), b0 = __float_as_uint(j >> 1 ? b.z : b.x), b1 = __float_as_uint(j >> 1 ? b.w : b.y);
                mma(cg, wg[j], a0, a1); mma(cu, wu[j], a0, a1); mma(sg, wg[j], b0, b1); mma(su, wu[j], b0, b1);
            }
            const uint32_t d = s0 + REG + g * 144 + t * 32;
            sts128f(d, cg[0], cg[2], cu[0], cu[2]); sts128f(d + 16, cg[1], cg[3], cu[1], cu[3]);
            sts128f(d + 1152, sg[0], sg[2], su[0], su[2]); sts128f(d + 1168, sg[1], sg[3], su[1], su[3]);
            bar_arrive<B_PRE, NALL>();
        }
        if (!early) { mbar_wait(sb + SM_BG, 0); spin(clock(), (7 - w) * XDW); x0 = ldg_rlx2x64(xp); x1 = ldg_rlx2x64(xp + 512); }
        int n = 0;
        while (true) {
            const bool b0 = max(x0.x, x0.z) == SENT, b1 = max(x1.x, x1.z) == SENT;
            if (!__any_sync(~0u, b0 | b1)) break;
            if (b0) x0 = ldg_rlx2x64(xp);
            if (b1) x1 = ldg_rlx2x64(xp + 512);
            if (++n > SPIN_MAX) __trap();
        }
        float q0[4] = {}, q1[4] = {}, ag[2][4] = {}, au[2][4] = {};
        {
            mma(q0, x0.x, ONE2, x0.y, ONE2, x0.x, x0.y); mma(q1, x0.z, ONE2, x0.w, ONE2, x0.z, x0.w);
            mma(q0, x1.x, ONE2, x1.y, ONE2, x1.x, x1.y); mma(q1, x1.z, ONE2, x1.w, ONE2, x1.z, x1.w);
#pragma unroll
            for (int j = 0; j < 4; j++) {
                const uint4 xv = (j & 1) ? x1 : x0; const float4 a = c1[j & 1];
                const uint32_t h0 = mul2(j >> 1 ? xv.z : xv.x, __float_as_uint(j >> 1 ? a.z : a.x)), h1 = mul2(j >> 1 ? xv.w : xv.y, __float_as_uint(j >> 1 ? a.w : a.y));
                mma(ag[j & 1], wg[j], h0, h1); mma(au[j & 1], wu[j], h0, h1);
            }
        }
        sts64(so, odd ? q0[3] + q1[3] : q0[2] + q1[2], odd ? q0[1] + q1[1] : q0[0] + q1[0]);
        sts128f(po, ag[0][0] + ag[1][0], ag[0][2] + ag[1][2], au[0][0] + au[1][0], au[0][2] + au[1][2]);
        sts128f(po + 16, ag[0][1] + ag[1][1], ag[0][3] + ag[1][3], au[0][1] + au[1][1], au[0][3] + au[1][3]);
        bar_arrive<B_FIN, NALL>();
    } else if (rid >= DN0) {
        const int f = rid - DN0;
        uint32_t wd[12][4];
        const char* const hp0 = pin(X + blk(X_HM, 0, side) + w * 512 + lane * 16);
        const char* const hp1 = pin(X + blk(X_HM, 1, side) + w * 512 + lane * 16);
        auto hm = [&](int j) { return ldg_rlx128((j & 1 ? hp1 : hp0) + (j >> 1) * 16384); };
        __nv_bfloat16* const op = pin(P.out + ((tid >> 4) & 7) * DM + f * 16 + (tid & 15));
        const uint32_t po = pin(myscr + SC_DN + t * 160 + g * 16), pi = pin(scr + SC_DN + (w & 3) * 160 + (tid & 7) * 16 + (tid & 8) + ((tid >> 4) & 1) * 4), gi = pin(sb + SM_MN + tid * 2), first = pin(w < 4);
        uint4 hv[6]; int n = 0;
        auto first_poll = [&]() {
            spin(clock(), w * HDW);
#pragma unroll
            for (int j = 0; j < 6; j++) hv[j] = (j < 5 || w < 3) ? hm(j) : make_uint4(0, 0, 0, 0);
        };
        const bool early = go_first(sb + SM_BT, 0);
        if (early) { first_poll(); mbar_wait(sb + SM_BT, 0); }
#pragma unroll
        for (int j = 0; j < 12; j++)
            if (j < 10 || w < 3) ldsm_t(wd[j], sb + 2 * REG + 16384 + (w + (j >> 1) * 8) * 1024 + (j & 1) * 512 + (((lane >> 1) & 1) + (lane & 1) * 2 + (lane & 4) + (lane >> 4) * 8) * 32 + ((lch ^ ((lane >> 2) & 1)) << 4));
            else wd[j][0] = wd[j][1] = wd[j][2] = wd[j][3] = 0;
        if (!early) { mbar_wait(sb + SM_BG, 0); first_poll(); }
        while (true) {
            unsigned m[6];
#pragma unroll
            for (int j = 0; j < 6; j++) m[j] = max(max(hv[j].x, hv[j].y), max(hv[j].z, hv[j].w));
            if (__all_sync(~0u, max(max(max(m[0], m[1]), m[2]), max(max(m[3], m[4]), m[5])) != SENT)) break;
#pragma unroll
            for (int j = 0; j < 6; j++) if (m[j] == SENT) hv[j] = hm(j);
            if (++n > SPIN_MAX) __trap();
        }
        float d[4][4] = {};
#pragma unroll
        for (int j = 0; j < 6; j++) { mma(d[(2 * j) & 3], wd[2 * j], hv[j].x, hv[j].y); mma(d[(2 * j + 1) & 3], wd[2 * j + 1], hv[j].z, hv[j].w); }
        sts128f(po, (d[0][0] + d[1][0]) + (d[2][0] + d[3][0]), (d[0][1] + d[1][1]) + (d[2][1] + d[3][1]), (d[0][2] + d[1][2]) + (d[2][2] + d[3][2]), (d[0][3] + d[1][3]) + (d[2][3] + d[3][3]));
        bar_sync<B_DN, NTHR>();
        if (first) {
            float v[8];
#pragma unroll
            for (int i = 0; i < 8; i++) v[i] = lds32(pi + i * SCR);
            unsigned gw, res;
            asm volatile("ld.shared.u16 %0, [%1];" : "=r"(gw) : "r"(gi) : "memory"); asm volatile("ld.shared.u16 %0, [%1];" : "=r"(res) : "r"(gi + 256) : "memory");
            asm volatile("st.global.u16 [%0], %1;" :: "l"(op), "h"((unsigned short)add2(res, mul2(gw, pack2(((v[0] + v[1]) + (v[2] + v[3])) + ((v[4] + v[5]) + (v[6] + v[7])), 0.f)))) : "memory");
        }
    }
}

typedef CUresult (*EncodeFn)(CUtensorMap*, CUtensorMapDataType, cuuint32_t, void*, const cuuint64_t*, const cuuint64_t*, const cuuint32_t*,
                             const cuuint32_t*, CUtensorMapInterleave, CUtensorMapSwizzle, CUtensorMapL2promotion, CUtensorMapFloatOOBfill);

void make2d(EncodeFn enc, CUtensorMap* m, const void* p, int rows, int cols, int brows, int bcols, CUtensorMapSwizzle sw) {
    cuuint64_t dims[2] = {(cuuint64_t)cols, (cuuint64_t)rows}, strides[1] = {(cuuint64_t)cols * 2};
    cuuint32_t box[2] = {(cuuint32_t)bcols, (cuuint32_t)brows}, es[2] = {1, 1};
    enc(m, CU_TENSOR_MAP_DATA_TYPE_BFLOAT16, 2, (void*)p, dims, strides, box, es, CU_TENSOR_MAP_INTERLEAVE_NONE, sw,
        CU_TENSOR_MAP_L2_PROMOTION_L2_128B, CU_TENSOR_MAP_FLOAT_OOB_FILL_NONE);
}
void make5d(EncodeFn enc, CUtensorMap* m, const void* p, int cols, const unsigned (&n)[4], const unsigned (&s)[4], unsigned nb) {
    const cuuint64_t rs = (cuuint64_t)cols * 2;
    cuuint64_t dims[5] = {(cuuint64_t)cols, n[0], n[1], n[2], n[3]}, strides[4] = {rs * s[0], rs * s[1], rs * s[2], rs * s[3]};
    cuuint32_t box[5] = {16, n[0], n[1], n[2], nb}, es[5] = {1, 1, 1, 1, 1};
    enc(m, CU_TENSOR_MAP_DATA_TYPE_BFLOAT16, 5, (void*)p, dims, strides, box, es, CU_TENSOR_MAP_INTERLEAVE_NONE, CU_TENSOR_MAP_SWIZZLE_32B,
        CU_TENSOR_MAP_L2_PROMOTION_L2_128B, CU_TENSOR_MAP_FLOAT_OOB_FILL_NONE);
}
void makekv(EncodeFn enc, CUtensorMap* m, const void* p) {
    cuuint64_t dims[3] = {64, (cuuint64_t)NB * NH * SK, 2}, strides[2] = {256, 128};
    cuuint32_t box[3] = {64, 16, 2}, es[3] = {1, 1, 1};
    enc(m, CU_TENSOR_MAP_DATA_TYPE_BFLOAT16, 3, (void*)p, dims, strides, box, es, CU_TENSOR_MAP_INTERLEAVE_NONE, CU_TENSOR_MAP_SWIZZLE_128B,
        CU_TENSOR_MAP_L2_PROMOTION_NONE, CU_TENSOR_MAP_FLOAT_OOB_FILL_NONE);
}

}

extern "C" void kernel_launch(void* const* d_in, const int* in_sizes, int n_in, void* d_out, int out_size) {
    (void)in_sizes; (void)n_in; (void)out_size;
    static EncodeFn enc = nullptr;
    static void* raw = nullptr;
    if (!enc) {
        void* fn = nullptr; cudaDriverEntryPointQueryResult qr;
        cudaGetDriverEntryPoint("cuTensorMapEncodeTiled", &fn, cudaEnableDefault, &qr);
        enc = (EncodeFn)fn;
        cudaFuncSetAttribute(fused_kernel, cudaFuncAttributeMaxDynamicSharedMemorySize, SM_TOTAL);
        cudaGetSymbolAddress(&raw, g_raw);
    }
    Params P;
    makekv(enc, &P.k, d_in[1]);
    makekv(enc, &P.v, d_in[2]);
    make2d(enc, &P.wq, d_in[3], DM, NH * DH, 64, 32, CU_TENSOR_MAP_SWIZZLE_64B);
    make2d(enc, &P.wo, d_in[4], NH * DH, DM, 32, 64, CU_TENSOR_MAP_SWIZZLE_128B);
    make2d(enc, &P.wm, d_in[10], DM, 6 * DM, 256, 8, CU_TENSOR_MAP_SWIZZLE_NONE);
    make2d(enc, &P.wn, d_in[10], DM, 6 * DM, 256, 16, CU_TENSOR_MAP_SWIZZLE_32B);
    make5d(enc, &P.wg, d_in[6], FF, {4, 2, 4, 16}, {1, 16, 4, 32}, 4);
    make5d(enc, &P.wu, d_in[7], FF, {4, 2, 4, 16}, {1, 16, 4, 32}, 4);
    make5d(enc, &P.wd, d_in[8], DM, {8, 4, 1, 43}, {4, 1, 1, 32}, 43);
    P.out = (__nv_bfloat16*)d_out;
    typedef const __nv_bfloat16* W;
    fused_kernel<<<NCTA, NALL, SM_TOTAL>>>((W)d_in[0], (W)d_in[9], (W)d_in[1], (W)d_in[10], (W)d_in[3], (char*)(((size_t)raw + X_ALIGN - 1) & ~(size_t)(X_ALIGN - 1)), P);
}
```

```cpp
#include <cuda_runtime.h>
#include <cuda_bf16.h>
#include <cuda.h>
#include <stdint.h>

namespace {

constexpr int NB = 8, DM = 512, NH = 32, DH = 128, SK = 4096, WIN = 1024, FF = 1376;
constexpr int NCTA = 128, NTHR = 288, NALL = 320;
constexpr int NT = 16;
constexpr int NF1 = 86, DN0 = 96;
constexpr unsigned SENT = 0xFFFFFFFFu;
constexpr int SPIN_MAX = 1 << 20;

constexpr int PWIN0 = 12;
constexpr int PWIN = 16;
constexpr int PSW = 22;
constexpr int NTRK = 8;
constexpr int PFK = 2;
constexpr int QN = 7;
constexpr int TAU = 166;
constexpr int ANCH0 = 176;
constexpr int LEAD = 1600;
constexpr int PACE0 = 7000;
constexpr int PNAP = 200;
constexpr int WOA_ISSUE = 3;
constexpr int WO_GAP = 2;
constexpr int WOA_READ = 8;
constexpr int WK = 3;
constexpr int WJ = 5;
constexpr int WO0 = 500;
constexpr int WOS = 30;
constexpr int WOG = 350;
constexpr int W0 = 1210;
constexpr int WS = 200;
constexpr int WD0 = 1950;
constexpr int RT0 = 2150;
constexpr int HD0 = 1250;
constexpr int XDW = 30;
constexpr int HDW = 45;
constexpr int XC = 2;

constexpr int UNIT = 4096, REG = 8 * UNIT;
constexpr int SM_SCR = 6 * REG;
constexpr int SCR = 2048;
constexpr int SM_MN = SM_SCR + 8 * SCR;
constexpr int SM_SC = SM_MN + 8192;
constexpr int SM_BAR = SM_SC + 8192;
constexpr int SM_BM = SM_BAR + 512, SM_BT = SM_BM + 8, SM_BN = SM_BM + 16, SM_BG = SM_BM + 24;
constexpr int SM_AN = SM_BM + 32, SM_SIDE = SM_BM + 36, SM_TAG = SM_BM + 40, SM_MASK = SM_BM + 44;
constexpr int SM_ST = SM_BAR + 576;
constexpr int SM_ML = SM_ST + 512;
constexpr int SM_PR = SM_ML + 96;
constexpr int SM_TOTAL = SM_PR + 512;
constexpr int SC_M = 0, SC_Q = 256;
constexpr int SC_F1 = 0, SC_DN = 0, SC_RX = 1536;
constexpr int B_INIT = 0, B_ALL = 2, B_MOD = 3, B_WQ = 4, B_LAST = 5, B_RDY = 6, B_DN = 7, B_PRE = 8, B_FIN = 9, B_STG = 10, B_SIDE = 11, B_Q = 12, B_ML = 13;

constexpr unsigned HOME = 0xB3000;
constexpr int X_PART = 0;
constexpr int X_Q = 0x100000;
constexpr int X_M1 = 0x140000;
constexpr int X_X1 = 0x150000;
constexpr int X_HM = 0x160000;
constexpr int X_MOD = 0x170000;
constexpr int X_SIDE = 0x176000;
constexpr int X_EPOCH = 0x176400;
constexpr int X_READY = 0x176480;
constexpr int X_LAG = 0x178000;
constexpr int X_ANC = 0x158000;
constexpr int X_PRB = 0x180000;
constexpr int X_ALIGN = 0x200000;
static_assert(XC == 2, "one store writes all copies of x1");
__device__ uint4 g_raw[2 * X_ALIGN / 16];
__device__ __forceinline__ unsigned blk(unsigned base, unsigned k, unsigned s) { const unsigned o = base + k * 8192; return o + ((__popc(o & HOME) ^ s) & 1) * 4096; }

struct Params {
    CUtensorMap wm, wq, k, v, wn, wo, wg, wu, wd;
    __nv_bfloat16* out;
};

__device__ __forceinline__ int tile_key(int i) { return (i & 1) * 128 + (i & 2) * 32 + (i & 12) * 64; }

__device__ __forceinline__ uint32_t smem_u32(const void* p) { return (uint32_t)__cvta_generic_to_shared(p); }
__device__ __forceinline__ void mbar_init(uint32_t a, uint32_t c) { asm volatile("mbarrier.init.shared::cta.b64 [%0], %1;" :: "r"(a), "r"(c) : "memory"); }
__device__ __forceinline__ void mbar_expect(uint32_t a, uint32_t b) { asm volatile("mbarrier.arrive.expect_tx.shared::cta.b64 _, [%0], %1;" :: "r"(a), "r"(b) : "memory"); }
__device__ __forceinline__ void mbar_wait(uint32_t a, uint32_t par) {
    uint32_t ok; int n = 0;
    do {
        asm volatile("{\n.reg .pred p;\nmbarrier.try_wait.parity.shared::cta.b64 p, [%1], %2, 2000;\nselp.u32 %0, 1, 0, p;\n}" : "=r"(ok) : "r"(a), "r"(par) : "memory");
        if (++n > SPIN_MAX) __trap();
    } while (!ok);
}
__device__ __forceinline__ bool mbar_test(uint32_t a, uint32_t par) {
    uint32_t ok; asm volatile("{\n.reg .pred p;\nmbarrier.test_wait.parity.shared::cta.b64 p, [%1], %2;\nselp.u32 %0, 1, 0, p;\n}" : "=r"(ok) : "r"(a), "r"(par) : "memory"); return ok;
}
__device__ __forceinline__ void tma2d(uint32_t dst, const CUtensorMap* m, int x, int y, uint32_t bar) {
    asm volatile("cp.async.bulk.tensor.2d.shared::cluster.global.mbarrier::complete_tx::bytes [%0], [%1, {%3, %4}], [%2];"
                 :: "r"(dst), "l"(m), "r"(bar), "r"(x), "r"(y) : "memory");
}
__device__ __forceinline__ void tma5d(uint32_t dst, const CUtensorMap* m, int x, int y, uint32_t bar) {
    asm volatile("cp.async.bulk.tensor.5d.shared::cluster.global.mbarrier::complete_tx::bytes [%0], [%1, {%3, 0, 0, 0, %4}], [%2];"
                 :: "r"(dst), "l"(m), "r"(bar), "r"(x), "r"(y) : "memory");
}
__device__ __forceinline__ void tma_kv(uint32_t dst, const CUtensorMap* m, int row, uint32_t bar, uint64_t pol) {
    asm volatile("cp.async.bulk.tensor.3d.shared::cluster.global.mbarrier::complete_tx::bytes.L2::cache_hint [%0], [%1, {0, %3, 0}], [%2], %4;"
                 :: "r"(dst), "l"(m), "r"(bar), "r"(row), "l"(pol) : "memory");
}
__device__ __forceinline__ void pf_bulk(const void* p, uint32_t n) { asm volatile("cp.async.bulk.prefetch.L2.global [%0], %1;" :: "l"(p), "r"(n) : "memory"); }
__device__ __forceinline__ void pf_if(const void* p, unsigned i, unsigned n) { asm volatile("{\n.reg .pred p;\nsetp.lt.u32 p, %1, %2;\n@p prefetch.global.L2 [%0];\n}" :: "l"(p), "r"(i), "r"(n) : "memory"); }
__device__ __forceinline__ uint4 ldg_nc(const void* p) { uint4 v; asm volatile("ld.global.nc.v4.u32 {%0,%1,%2,%3}, [%4];" : "=r"(v.x), "=r"(v.y), "=r"(v.z), "=r"(v.w) : "l"(p)); return v; }
__device__ __forceinline__ bool elect() { uint32_t p; asm volatile("{\n.reg .pred p;\nelect.sync _|p, -1;\nselp.u32 %0, 1, 0, p;\n}" : "=r"(p)); return p; }
__device__ __forceinline__ void pf_map(const CUtensorMap* m) { asm volatile("prefetch.tensormap [%0];" :: "l"(m) : "memory"); }
__device__ __forceinline__ void ldsm(uint32_t (&r)[4], uint32_t a) {
    asm volatile("ldmatrix.sync.aligned.m8n8.x4.shared.b16 {%0,%1,%2,%3}, [%4];" : "=r"(r[0]), "=r"(r[1]), "=r"(r[2]), "=r"(r[3]) : "r"(a) : "memory");
}
__device__ __forceinline__ void ldsm_t(uint32_t (&r)[4], uint32_t a) {
    asm volatile("ldmatrix.sync.aligned.m8n8.x4.trans.shared.b16 {%0,%1,%2,%3}, [%4];" : "=r"(r[0]), "=r"(r[1]), "=r"(r[2]), "=r"(r[3]) : "r"(a) : "memory");
}
__device__ __forceinline__ void mma(float (&c)[4], uint32_t a0, uint32_t a1, uint32_t a2, uint32_t a3, uint32_t b0, uint32_t b1) {
    asm("mma.sync.aligned.m16n8k16.row.col.f32.bf16.bf16.f32 {%0,%1,%2,%3}, {%4,%5,%6,%7}, {%8,%9}, {%0,%1,%2,%3};"
        : "+f"(c[0]), "+f"(c[1]), "+f"(c[2]), "+f"(c[3]) : "r"(a0), "r"(a1), "r"(a2), "r"(a3), "r"(b0), "r"(b1));
}
__device__ __forceinline__ void mma(float (&c)[4], const uint32_t (&a)[4], uint32_t b0, uint32_t b1) { mma(c, a[0], a[1], a[2], a[3], b0, b1); }
__device__ __forceinline__ uint32_t pin(uint32_t v) { asm volatile("shfl.sync.bfly.b32 %0, %0, 0, 31, -1;" : "+r"(v)); return v; }
template <class T> __device__ __forceinline__ T* pin(T* p) { const size_t a = (size_t)p; return (T*)(pin((uint32_t)a) | (size_t)pin((uint32_t)(a >> 32)) << 32); }
__device__ __forceinline__ void mmav(float (&c)[4], const uint32_t (&a)[4], uint32_t b0, uint32_t b1) {
    asm volatile("mma.sync.aligned.m16n8k16.row.col.f32.bf16.bf16.f32 {%0,%1,%2,%3}, {%4,%5,%6,%7}, {%8,%9}, {%0,%1,%2,%3};"
        : "+f"(c[0]), "+f"(c[1]), "+f"(c[2]), "+f"(c[3]) : "r"(a[0]), "r"(a[1]), "r"(a[2]), "r"(a[3]), "r"(b0), "r"(b1));
}
__device__ __forceinline__ uint32_t movm(uint32_t a) { uint32_t r; asm volatile("movmatrix.sync.aligned.m8n8.trans.b16 %0, %1;" : "=r"(r) : "r"(a)); return r; }
__device__ __forceinline__ uint32_t pack2(float lo, float hi) { uint32_t r; asm("cvt.rn.bf16x2.f32 %0, %1, %2;" : "=r"(r) : "f"(hi), "f"(lo)); return r; }
__device__ __forceinline__ float blo(uint32_t w) { return __uint_as_float(w << 16); }
__device__ __forceinline__ float bhi(uint32_t w) { return __uint_as_float(w & 0xFFFF0000u); }
__device__ __forceinline__ float rbf(float x) { return blo(pack2(x, 0.f)); }
__device__ __forceinline__ uint32_t add2(uint32_t a, uint32_t b) { uint32_t r; asm("add.rn.bf16x2 %0, %1, %2;" : "=r"(r) : "r"(a), "r"(b)); return r; }
__device__ __forceinline__ uint32_t sub2(uint32_t a, uint32_t b) { uint32_t r; asm("sub.rn.bf16x2 %0, %1, %2;" : "=r"(r) : "r"(a), "r"(b)); return r; }
__device__ __forceinline__ uint32_t mul2(uint32_t a, uint32_t b) { uint32_t r; asm("mul.rn.bf16x2 %0, %1, %2;" : "=r"(r) : "r"(a), "r"(b)); return r; }
constexpr uint32_t ONE2 = 0x3F803F80u;
constexpr float LOG2E = 1.4426950408889634f, SCALE = 0.08838834764831845f;
__device__ __forceinline__ float ex2(float x) { float y; asm("ex2.approx.ftz.f32 %0, %1;" : "=f"(y) : "f"(x)); return y; }
__device__ __forceinline__ uint4 ldg_rlx128(const void* p) {
    uint4 v; asm volatile("ld.relaxed.gpu.global.v4.u32 {%0,%1,%2,%3}, [%4];" : "=r"(v.x), "=r"(v.y), "=r"(v.z), "=r"(v.w) : "l"(p) : "memory"); return v;
}
__device__ __forceinline__ uint4 ldg_rlx2x64(const void* p) {
    unsigned long long a, b; asm volatile("ld.relaxed.gpu.global.v2.u64 {%0,%1}, [%2];" : "=l"(a), "=l"(b) : "l"(p) : "memory");
    return make_uint4((unsigned)a, (unsigned)(a >> 32), (unsigned)b, (unsigned)(b >> 32));
}
__device__ __forceinline__ uint2 ldg_rlx64(const void* p) {
    unsigned long long a; asm volatile("ld.relaxed.gpu.global.u64 %0, [%1];" : "=l"(a) : "l"(p) : "memory"); return make_uint2((unsigned)a, (unsigned)(a >> 32));
}
__device__ __forceinline__ unsigned ldg_acq32(const void* p) { unsigned v; asm volatile("ld.acquire.gpu.global.u32 %0, [%1];" : "=r"(v) : "l"(p) : "memory"); return v; }
__device__ __forceinline__ void red_add(void* p, unsigned v) { asm volatile("red.relaxed.gpu.global.add.u32 [%0], %1;" :: "l"(p), "r"(v) : "memory"); }
__device__ __forceinline__ unsigned now_ns() { unsigned t; asm volatile("mov.u32 %0, %%globaltimer_lo;" : "=r"(t)); return t; }
__device__ __forceinline__ void nap(unsigned ns) { asm volatile("nanosleep.u32 %0;" :: "r"(ns)); }
__device__ __forceinline__ unsigned ldg_rlx32(const void* p) { unsigned v; asm volatile("ld.relaxed.gpu.global.u32 %0, [%1];" : "=r"(v) : "l"(p) : "memory"); return v; }
__device__ __forceinline__ void stg_rlx32(void* p, unsigned v) { asm volatile("st.relaxed.gpu.global.u32 [%0], %1;" :: "l"(p), "r"(v) : "memory"); }
__device__ __forceinline__ void stg_rlx16(void* p, unsigned v) { asm volatile("st.relaxed.gpu.global.u16 [%0], %1;" :: "l"(p), "h"((unsigned short)v) : "memory"); }
__device__ __forceinline__ uint4 ldg_b128(const void* p) {
    unsigned long long a, b; asm volatile("{\n.reg .b128 x;\nld.relaxed.gpu.global.b128 x, [%2];\nmov.b128 {%0,%1}, x;\n}" : "=l"(a), "=l"(b) : "l"(p) : "memory");
    return make_uint4((unsigned)a, (unsigned)(a >> 32), (unsigned)b, (unsigned)(b >> 32));
}
__device__ __forceinline__ void stg_b128(void* p, uint4 v) {
    asm volatile("{\n.reg .b128 x;\nmov.b128 x, {%1,%2};\nst.relaxed.gpu.global.b128 [%0], x;\n}" :: "l"(p), "l"(v.x | ((unsigned long long)v.y << 32)), "l"(v.z | ((unsigned long long)v.w << 32)) : "memory");
}
__device__ __forceinline__ int rowoff(int b, int c) { return ((c >> 6) * 2 + ((c >> 2) & 1)) * 512 + b * 64 + (c & 3) * 16 + ((c >> 3) & 1) * 8 + ((c >> 5) & 1) * 4 + ((c >> 4) & 1) * 2; }
__device__ __forceinline__ void stg_rlx64(void* p, unsigned lo, unsigned hi) {
    unsigned long long a = lo | ((unsigned long long)hi << 32); asm volatile("st.relaxed.gpu.global.u64 [%0], %1;" :: "l"(p), "l"(a) : "memory");
}
__device__ __forceinline__ void stg_rlx128(void* p, uint4 v) { asm volatile("st.relaxed.gpu.global.v4.u32 [%0], {%1,%2,%3,%4};" :: "l"(p), "r"(v.x), "r"(v.y), "r"(v.z), "r"(v.w) : "memory"); }
__device__ __forceinline__ void sts32u(uint32_t a, unsigned x) { asm volatile("st.volatile.shared.u32 [%0], %1;" :: "r"(a), "r"(x) : "memory"); }
__device__ __forceinline__ unsigned lds32u(uint32_t a) { unsigned v; asm volatile("ld.volatile.shared.u32 %0, [%1];" : "=r"(v) : "r"(a) : "memory"); return v; }
__device__ __forceinline__ void spin(unsigned c0, unsigned d) { if (d) while ((unsigned)clock() - c0 < d) {} }
__device__ __forceinline__ void fence_gpu() { asm volatile("fence.acq_rel.gpu;" ::: "memory"); }
template <int ID, int N> __device__ __forceinline__ void bar_sync() { asm volatile("bar.sync %0, %1;" :: "n"(ID), "n"(N) : "memory"); }
template <int ID, int N> __device__ __forceinline__ void bar_arrive() { asm volatile("bar.arrive %0, %1;" :: "n"(ID), "n"(N) : "memory"); }
__device__ __forceinline__ void sts64(uint32_t a, float x, float y) { asm volatile("st.shared.v2.f32 [%0], {%1,%2};" :: "r"(a), "f"(x), "f"(y) : "memory"); }
__device__ __forceinline__ void sts128(uint32_t a, uint4 v) { asm volatile("st.volatile.shared.v4.u32 [%0], {%1,%2,%3,%4};" :: "r"(a), "r"(v.x), "r"(v.y), "r"(v.z), "r"(v.w) : "memory"); }
__device__ __forceinline__ void sts128f(uint32_t a, float x, float y, float z, float w) { asm volatile("st.volatile.shared.v4.f32 [%0], {%1,%2,%3,%4};" :: "r"(a), "f"(x), "f"(y), "f"(z), "f"(w) : "memory"); }
__device__ __forceinline__ void sts32(uint32_t a, float x) { asm volatile("st.shared.f32 [%0], %1;" :: "r"(a), "f"(x) : "memory"); }
__device__ __forceinline__ float2 lds64(uint32_t a) { float2 v; asm volatile("ld.shared.v2.f32 {%0,%1}, [%2];" : "=f"(v.x), "=f"(v.y) : "r"(a) : "memory"); return v; }
__device__ __forceinline__ float lds32(uint32_t a) { float v; asm volatile("ld.shared.f32 %0, [%1];" : "=f"(v) : "r"(a) : "memory"); return v; }
__device__ __forceinline__ float4 lds128(uint32_t a) { float4 v; asm volatile("ld.shared.v4.f32 {%0,%1,%2,%3}, [%4];" : "=f"(v.x), "=f"(v.y), "=f"(v.z), "=f"(v.w) : "r"(a) : "memory"); return v; }
__device__ __forceinline__ float2 sum8(uint32_t a) {
    float2 v[8];
#pragma unroll
    for (int i = 0; i < 8; i++) v[i] = lds64(a + i * SCR);
    return make_float2(((v[0].x + v[1].x) + (v[2].x + v[3].x)) + ((v[4].x + v[5].x) + (v[6].x + v[7].x)),
                       ((v[0].y + v[1].y) + (v[2].y + v[3].y)) + ((v[4].y + v[5].y) + (v[6].y + v[7].y)));
}
template <int STRIDE> __device__ __forceinline__ float4 sum8x4(uint32_t a) {
    float4 v[8];
#pragma unroll
    for (int i = 0; i < 8; i++) v[i] = lds128(a + i * STRIDE);
    return make_float4(((v[0].x + v[1].x) + (v[2].x + v[3].x)) + ((v[4].x + v[5].x) + (v[6].x + v[7].x)), ((v[0].y + v[1].y) + (v[2].y + v[3].y)) + ((v[4].y + v[5].y) + (v[6].y + v[7].y)),
                       ((v[0].z + v[1].z) + (v[2].z + v[3].z)) + ((v[4].z + v[5].z) + (v[6].z + v[7].z)), ((v[0].w + v[1].w) + (v[2].w + v[3].w)) + ((v[4].w + v[5].w) + (v[6].w + v[7].w)));
}
__device__ __forceinline__ float rcp(float x) { float y; asm("rcp.approx.ftz.f32 %0, %1;" : "=f"(y) : "f"(x)); return y; }
__device__ __forceinline__ float sigmoid_f(float x) { return rcp(1.0f + ex2(x * -LOG2E)); }
__device__ __forceinline__ uint32_t silu2(uint32_t c) { const float a = blo(c), b = bhi(c); return pack2(a * sigmoid_f(a), b * sigmoid_f(b)); }
__device__ __forceinline__ void ln_consts(float mean, float var, uint32_t& mu2, float& rs) {
    mu2 = pack2(mean, mean);
    float sd; asm("sqrt.approx.ftz.f32 %0, %1;" : "=f"(sd) : "f"(rbf(rbf(var) + 1e-5f)));
    rs = rcp(rbf(sd));
}
__device__ __forceinline__ uint32_t ln_norm(uint32_t x2, uint32_t mu2, float rs) { const uint32_t d = sub2(x2, mu2); return pack2(blo(d) * rs, bhi(d) * rs); }

__global__ void __launch_bounds__(NALL, 1) fused_kernel(const __nv_bfloat16* const px, const __nv_bfloat16* const pc, const __nv_bfloat16* const pk, const __nv_bfloat16* const pwm,
                                                        const __nv_bfloat16* const pwq, char* const X, const __grid_constant__ Params P) {
    extern __shared__ __align__(1024) unsigned char smem[];
    const uint32_t sb = smem_u32(smem);
    const int tid = threadIdx.x, w = tid >> 5, lane = tid & 31, g = lane >> 2, t = lane & 3;
    const int cta = blockIdx.x, head = cta >> 2, bat = (cta & 3) * 2 + (w >> 2);
    const uint32_t s0 = sb + w * UNIT, s2 = s0 + 4 * REG;
    const uint32_t bar0 = sb + SM_BAR + w * 64;
    const uint32_t barC = bar0 + 32;
    const uint32_t scr = sb + SM_SCR, myscr = scr + w * SCR;
    pf_if((const char*)pwm + ((cta * 4 + (lane >> 3)) * (6 * DM * 2) + w * 1024 + (lane & 7) * 128), w, 5);
    pf_if((const char*)pk + (unsigned)(((((cta & 3) * 2 + (w & 1)) * NH + head) * SK + (SK - WIN - 48) + tile_key(2) + (w >> 1) * 16) * (DH * 2) + lane * 128), w - 6, PFK);
    const int rid = !(cta & 1) ? cta >> 1 : (cta >> 2) + (cta & 2 ? 64 : 96);
    const unsigned t_start = now_ns();
    uint64_t pol;
    asm volatile("createpolicy.fractional.L2::evict_first.b64 %0, 1.0;" : "=l"(pol));
    auto go_first = [&](uint32_t wbar, uint32_t par) {
        for (int n = 0;; n++) {
            if (__all_sync(~0u, mbar_test(wbar, par))) return false;
            if (__all_sync(~0u, mbar_test(sb + SM_BG, 0))) return true;
            if (n > SPIN_MAX * 4) __trap();
            nap(20);
        }
    };
    if (w == 9) {
        const uint32_t sl = sb + SM_PR + lane * 16;
        char* const pl = X + blk(X_PRB, cta >> 1, lane & 1) + (lane >> 1) * 256 + (cta & 1) * 128;
        {
            char* const ps = X + X_PRB + (cta >> 1) * 8192 + g * 256 + (cta & 1) * 128 + t * 16;
            sts32u(sl, 0);
#pragma unroll
            for (int i = 0; i < 4; i++) stg_rlx128(ps + i * 2048, make_uint4(1, 1, 1, 1));
            __syncwarp();
        }
        unsigned v; asm volatile("atom.relaxed.gpu.global.add.u32 %0, [%1], 1;" : "=r"(v) : "l"(pl) : "memory");
        unsigned tag = ldg_rlx32(X + X_EPOCH);
        if (lane == 0) pf_bulk(pwq + (size_t)cta * QN * 1024, QN * 2048);
        if (lane == 0) sts32u(sb + SM_AN, t_start + ANCH0);
        if (lane < 8) sts32u(sb + SM_BAR + lane * 64 + 56, 0);
        unsigned side;
        {
            int d, n = 0;
#pragma unroll 1
            for (int r = 0; r < 4; r++) {
                if (v == SENT) __trap();
                asm volatile("cp.async.cg.shared.global [%0], [%1], 16;" :: "r"(sl), "l"(pl) : "memory");
                unsigned m;
                do {
                    m = __ballot_sync(~0u, lds32u(sl));
                    d = __popc(m & 0xAAAAAAAAu) - __popc(m & 0x55555555u);
                    if (++n > SPIN_MAX) __trap();
                } while (abs(d) < 6 && m != ~0u);
                if (abs(d) >= 6) break;
                asm volatile("cp.async.wait_all;" ::: "memory");
                sts32u(sl, 0);
                asm volatile("atom.relaxed.gpu.global.add.u32 %0, [%1], 1;" : "=r"(v) : "l"(pl) : "memory");
            }
            side = d > 0;
            tag++;
            if (lane == 0) { sts32u(sb + SM_SIDE, side); sts32u(sb + SM_TAG, tag); }
            bar_arrive<B_SIDE, NTHR>();
        }
        asm volatile("cp.async.wait_all;" ::: "memory");
        while (now_ns() - t_start < PACE0) nap(200);
        for (int n = 0; n < SPIN_MAX; n++) {
            const uint32_t wb = sb + SM_BAR + (lane & 7) * 64;
            const unsigned seen = lds32u(wb + 56), u = seen + ((lane >> 3) & 1), t1 = now_ns();
            const unsigned more = seen && mbar_test(wb + (u < 6 ? u : (~u & 2) + (u & 1)) * 8, u < 6 ? 0 : ((u - 2) >> 2) & 1);
            const unsigned lo = __reduce_min_sync(~0u, seen), sum = __reduce_add_sync(~0u, lane < 8 ? seen + more : lane < 16 ? more : 0);
            if (lo == 30) break;
            if (lo && lane < 2) stg_rlx64(X + X_LAG + (cta >> 5) * 8192 + lane * 4096 + (cta & 31) * 128, t1 - sum * TAU, tag);
            uint2 a = make_uint2(0, 0);
            if (cta == 0) {
                uint2 u[4];
#pragma unroll
                for (int i = 0; i < 4; i++) u[i] = ldg_rlx64(X + blk(X_LAG, i, side) + lane * 128);
                const int s = __reduce_add_sync(~0u, (int)(u[0].x + u[1].x + u[2].x + u[3].x - 4 * t_start));
                if (__all_sync(~0u, (u[0].y == tag) & (u[1].y == tag) & (u[2].y == tag) & (u[3].y == tag)) && lane < 2) {
                    a = make_uint2(t_start + s / NCTA, tag);
                    stg_rlx64(X + X_ANC + lane * 4096, a.x, tag);
                }
            } else if (lane == 0) a = ldg_rlx64(X + blk(X_ANC, 0, side));
            if (lane == 0 && a.y == tag) sts32u(sb + SM_AN, a.x - LEAD);
            __syncwarp();
            nap(PNAP);
        }
        {
            bar_sync<B_ML, NTHR>();
            const float2 ml = lds64(sb + SM_ML + (lane & 7) * 8);
            float M = fmaxf(ml.x, __shfl_xor_sync(~0u, ml.x, 1)); M = fmaxf(M, __shfl_xor_sync(~0u, M, 2));
            const float e = ex2((ml.x - M) * LOG2E);
            float L = e * ml.y; L += __shfl_xor_sync(~0u, L, 1); L += __shfl_xor_sync(~0u, L, 2);
            if (lane < 8) sts32(sb + SM_ML + 64 + lane * 4, e * rcp(L));
        }
        bar_arrive<B_RDY, NALL>();
        bar_sync<B_STG, 64>();
        {
            const char* const pp = pin(X + blk(X_PART, cta, side) + lane * 16);
            char* const xo = pin(X + (lane >> 4) * 16384 + blk(X_X1, (cta >> 3) & 1, lane >> 3) + (cta & 7) * 512 + (cta >> 4) * 64 + (lane & 7) * 8);
            const float4 gx = lds128(scr + SC_RX + (lane & 7) * 16);
            const unsigned t0 = lds32u(sb + SM_AN) + 256 * TAU + RT0 + (cta & 7) * (TAU / 8);
            while ((int)(now_ns() - t0) < 0) nap(20);
            uint4 v[8]; int n = 0;
            float a[4];
#pragma unroll
            for (int j = 0; j < 8; j++) v[j] = ldg_b128(pp + j * 512);
            while (true) {
#define RSUM(f) (((__uint_as_float(v[0].f) + __uint_as_float(v[1].f)) + (__uint_as_float(v[2].f) + __uint_as_float(v[3].f))) + ((__uint_as_float(v[4].f) + __uint_as_float(v[5].f)) + (__uint_as_float(v[6].f) + __uint_as_float(v[7].f))))
                const bool ok = __all_sync(~0u, max(max(max(v[0].x, v[1].x), max(v[2].x, v[3].x)), max(max(v[4].x, v[5].x), max(v[6].x, v[7].x))) != SENT);
                a[0] = RSUM(x); a[1] = RSUM(y); a[2] = RSUM(z); a[3] = RSUM(w);
                asm volatile("" : "+f"(a[0]), "+f"(a[1]), "+f"(a[2]), "+f"(a[3]));
                if (ok) break;
#pragma unroll
                for (int j = 0; j < 8; j++) if (v[j].x == SENT) v[j] = ldg_b128(pp + j * 512);
                if (++n > SPIN_MAX) __trap();
            }
#pragma unroll
            for (int i = 0; i < 4; i++) a[i] += __shfl_xor_sync(~0u, a[i], 8);
#pragma unroll
            for (int i = 0; i < 4; i++) a[i] += __shfl_xor_sync(~0u, a[i], 16);
            stg_rlx64(xo, add2(__float_as_uint(gx.z), mul2(__float_as_uint(gx.x), pack2(a[0], a[1]))), add2(__float_as_uint(gx.w), mul2(__float_as_uint(gx.y), pack2(a[2], a[3]))));
        }
        if (rid >= DN0) {
            const unsigned c1 = clock();
            const int f = rid - DN0;
            const char* const rp = X + (rid & (XC - 1)) * 16384 + blk(X_X1, f >> 4, side) + (rowoff(g, f * 16 + t * 4) & 4092);
            unsigned r[4]; int n = 0;
            spin(c1, HD0 - 450);
            do {
#pragma unroll
                for (int i = 0; i < 4; i++) r[i] = ldg_rlx32(rp + i * 16);
                if (++n > SPIN_MAX) __trap();
            } while (max(max(r[0], r[1]), max(r[2], r[3])) == SENT);
            const unsigned sel = (f & 1) ? 0x7632 : 0x5410;
            sts64(sb + SM_MN + 256 + lane * 8, __uint_as_float(__byte_perm(r[0], r[1], sel)), __uint_as_float(__byte_perm(r[2], r[3], sel)));
            __syncwarp();
            spin(c1, HD0);
        }
        if (lane == 0) asm volatile("mbarrier.arrive.shared::cta.b64 _, [%0];" :: "r"(sb + SM_BG) : "memory");
    } else if (w == 8) {
        const int row0 = ((cta & 3) * 2 * NH + head) * SK + (SK - WIN);
        auto kv_unit = [&](int u) {
            const uint32_t b = sb + SM_BAR + (u & 7) * 64 + (u >> 3) * 8;
            mbar_expect(b, UNIT);
            tma_kv(sb + (u >> 3) * REG + (u & 7) * UNIT, (u & 8) ? &P.v : &P.k, row0 + ((u >> 2) & 1) * NH * SK + (u & 3) * 16 + tile_key(u >> 4), b, pol);
        };
        if (elect()) {
            mbar_init(sb + SM_BM, 1);
#pragma unroll
            for (int i = 0; i < 8; i++) mbar_init(sb + SM_BAR + i * 64 + 48, 1);
            asm volatile("fence.mbarrier_init.release.cluster;" ::: "memory");
            mbar_expect(sb + SM_BM, 512 * 16);
            tma2d(sb + 4 * REG, &P.wm, cta * 8, 0, sb + SM_BM); tma2d(sb + 4 * REG + 256 * 16, &P.wm, cta * 8, 256, sb + SM_BM);
#pragma unroll
            for (int i = 0; i < 8; i++) { const uint32_t b = sb + SM_BAR + i * 64 + 48; mbar_expect(b, UNIT); tma2d(sb + 5 * REG + i * UNIT, &P.wq, cta * 32, i * 64, b); }
            mbar_init(sb + SM_BN, 1); mbar_init(sb + SM_BT, 1); mbar_init(sb + SM_BG, 1);
#pragma unroll
            for (int i = 0; i < 48; i++) mbar_init(sb + SM_BAR + (i & 7) * 64 + (i >> 3) * 8, 1);
            asm volatile("fence.mbarrier_init.release.cluster;" ::: "memory");
        }
        __syncwarp();
        bar_arrive<B_INIT, NTHR>();
        {
            uint32_t mine = lane >= NTRK ? 0 : lane < 8 ? sb + SM_BAR + lane * 64 + 48 : sb + SM_BM;
            int next = 0, lim = 32, n = 0;
            while (next < 48) {
                const bool idle = lane < (next < PSW ? PWIN0 : PWIN) && (mine == 0 || mbar_test(mine, 0));
                const unsigned m = __ballot_sync(~0u, idle);
                const int u = next + __popc(m & ((1u << lane) - 1));
                if (idle) {
                    mine = 0;
                    if (u < lim) { kv_unit(u); mine = sb + SM_BAR + (u & 7) * 64 + (u >> 3) * 8; }
                }
                next = min(next + __popc(m), lim);
                if (next == lim) {
                    if (lim == 32) { bar_sync<B_MOD, NTHR>(); } else if (lim == 40) { bar_sync<B_WQ, NTHR>(); }
                    lim += 8;
                }
                if (!m) nap(30);
                if (++n > SPIN_MAX) __trap();
            }
        }
        if (lane < 5) pf_map(&P.wn + lane);
        float m[4][4] = {};
        auto late_mod = [&](uint32_t a, int h) {
            const int lrow = (lane & 7) + ((lane >> 4) << 3), lch = (lane >> 3) & 1;
            const uint32_t a0 = a + lrow * 32 + ((lch ^ ((lrow >> 2) & 1)) << 4);
            const uint32_t c0 = sb + SM_SC + h * 4096 + (lane & 7) * 128 + (((lane >> 3) ^ (lane & 7)) << 4);
#pragma unroll
            for (int j = 0; j < 8; j++) {
                uint32_t c[4], r[4], u[4];
                ldsm(c, (c0 + (j >> 1) * 1024) ^ ((j & 1) << 6)); ldsm_t(r, a0 + j * 1024); ldsm_t(u, a0 + j * 1024 + 512);
                mma(m[(j & 1) * 2], r, c[0], c[1]); mma(m[(j & 1) * 2 + 1], u, c[2], c[3]);
            }
        };
        if (rid < 96) {
#pragma unroll 1
            for (int h = 0; h < 2; h++) {
                if (lane == 0) { mbar_expect(sb + SM_BN, 8192); tma2d(sb + SM_MN, &P.wn, 2 * DM + rid * 16, h * 256, sb + SM_BN); }
                mbar_wait(sb + SM_BN, h);
                late_mod(sb + SM_MN, h);
                asm volatile("" :: "f"(m[0][0]), "f"(m[1][0]), "f"(m[2][0]), "f"(m[3][0]) : "memory");
                __syncwarp();
            }
#pragma unroll
            for (int e = 0; e < 4; e++) {
                float v = rbf((m[0][e] + m[1][e]) + (m[2][e] + m[3][e]));
                if (rid >= 64) v += 1.0f;
                stg_rlx16(X + X_MOD + (rid >> 5) * 8192 + rowoff(2 * t + (e & 1), (rid & 31) * 16 + g + (e >> 1) * 8), pack2(v, 0.f));
            }
        }
        {
            const unsigned side = lds32u(sb + SM_SIDE);
#pragma unroll
            for (int i = 0; i < 8; i++) stg_rlx128(X + blk(X_PART, cta, side) + i * 512 + lane * 16, make_uint4(SENT, SENT, SENT, SENT));
            if (lane == 0) stg_rlx32(X + X_SIDE + cta * 4, side);
        }
        bar_sync<B_Q, NTHR>();
        if (lane == 0) {
            const unsigned tag = lds32u(sb + SM_TAG);
            fence_gpu();
            red_add(X + X_READY, 1);
            int n = 0;
            while ((int)(ldg_acq32(X + X_READY) - tag * NCTA) < 0) { nap(1000); if (++n > SPIN_MAX) __trap(); }
            if (cta == 0) stg_rlx32(X + X_EPOCH, tag);
        }
        __syncwarp();
        {
            stg_rlx128(X + blk(X_Q, head >> 1, 0) + (head & 1) * 2048 + g * 256 + (cta & 3) * 64 + t * 16, make_uint4(0, 0, 0, 0));
            stg_rlx128(X + blk(X_Q, head >> 1, 1) + (head & 1) * 2048 + g * 256 + (cta & 3) * 64 + t * 16, make_uint4(0, 0, 0, 0));
            stg_rlx64(X + blk(X_M1, cta >> 5, lane >> 4) + (cta & 31) * 128 + (lane & 15) * 8, 0, 0);
            const int wt = (cta & 3) * 32 + lane;
            const unsigned mask = __ballot_sync(~0u, blk(X_PART, wt, ldg_rlx32(X + X_SIDE + wt * 4)) & 4096);
            if (lane == 0) sts32u(sb + SM_MASK, mask);
            if (lane < 8) {
                const int rb = cta >> 4, c = ((cta & 15) >> 1) * 64 + (cta & 1) * 4 + (lane >> 1) + (lane & 1) * 8;
                const uint2 ga = ldg_rlx64(X + X_MOD + rowoff(rb, c));
                const unsigned short* const xp = (const unsigned short*)px + rb * DM + c;
                sts128(scr + SC_RX + lane * 16, make_uint4(ga.x, ga.y, xp[0] | (xp[16] << 16), xp[32] | (xp[48] << 16)));
            }
            if (rid < NF1) {
#pragma unroll 1
                for (int i = 0; i < 4; i++) {
                    uint4 v[8];
#pragma unroll
                    for (int j = 0; j < 8; j++) v[j] = ldg_rlx128(X + X_MOD + 8192 + (i * 8 + j) * 512 + lane * 16);
#pragma unroll
                    for (int j = 0; j < 8; j++) sts128(sb + SM_MN + (i * 8 + j) * 512 + lane * 16, v[j]);
                }
            }
        }
        bar_arrive<B_RDY, NALL>();
        bar_arrive<B_STG, 64>();
        for (int n = 0; __any_sync(~0u, lds32u(sb + SM_BAR + (lane & 7) * 64 + 56) < 30); n++) { nap(100); if (n > SPIN_MAX) __trap(); }
        const unsigned t_ref = lds32u(sb + SM_AN) + 256 * TAU + (cta & 7) * (TAU / 8);
        auto until = [&](int x) { while ((int)(now_ns() - t_ref) < x) nap(20); };
        if (lane < 16) mbar_expect(sb + SM_BAR + (lane & 7) * 64 + 32 + (lane & 8), UNIT);
        else if (lane < 20 && rid < NF1) mbar_expect(sb + SM_BAR + (lane & 7) * 64 + 48, 2 * UNIT);
        __syncwarp();
        if (elect()) {
#pragma unroll 1
            for (int i = 0; i < 16; i += 2) {
                until(WO0 + (i & 7) * WOS + (i >> 3) * WOG);
#pragma unroll
                for (int j = i; j < i + 2; j++) tma2d(sb + 4 * REG + j * UNIT, &P.wo, (j & 7) * 64, head * 128 + 64 + (j & 8) * 4, sb + SM_BAR + (j & 7) * 64 + 32 + (j & 8));
            }
            if (rid < NF1) {
#pragma unroll 1
                for (int i = 0; i < 4; i++) {
                    const uint32_t b = sb + SM_BAR + i * 64 + 48;
                    until(W0 + i * WS);
                    tma5d(sb + 2 * REG + i * UNIT, &P.wg, rid * 16, i * 4, b); tma5d(sb + 2 * REG + 16384 + i * UNIT, &P.wu, rid * 16, i * 4, b);
                }
            }
        }
        if (rid >= DN0) {
            bar_sync<B_LAST, NTHR>();
            if (elect()) {
                mbar_expect(sb + SM_BN, 16384); mbar_expect(sb + SM_BT, FF * 32);
                until(WD0);
                tma5d(sb + 2 * REG + 16384, &P.wd, (rid - DN0) * 16, 0, sb + SM_BT);
                tma2d(sb + 2 * REG, &P.wn, 2 * DM + rid * 16, 0, sb + SM_BN); tma2d(sb + 2 * REG + 8192, &P.wn, 2 * DM + rid * 16, 256, sb + SM_BN);
            }
        }
        __syncwarp();
        if (rid >= DN0) {
            mbar_wait(sb + SM_BN, 0);
            late_mod(sb + 2 * REG, 0); late_mod(sb + 2 * REG + 8192, 1);
#pragma unroll
            for (int e = 0; e < 2; e++)
                sts32u(sb + SM_MN + g * 32 + e * 16 + t * 4, movm(pack2((m[0][2 * e] + m[1][2 * e]) + (m[2][2 * e] + m[3][2 * e]), (m[0][2 * e + 1] + m[1][2 * e + 1]) + (m[2][2 * e + 1] + m[3][2 * e + 1]))));
            bar_arrive<B_DN, NTHR>();
        }
    }
    if (w >= 8) {
        if (rid < NF1) {
            const int b = (tid - 256) >> 3, c = tid & 7;
            char* const ho = pin(X + X_HM + (rid >> 4) * 8192 + ((rid >> 1) & 7) * 512 + b * 64 + (rid & 1) * 32 + c * 4);
            const uint32_t pi = pin(scr + SC_F1 + c * 144 + b * 16), si = pin(sb + SM_ST + b * 64);
            bar_sync<B_PRE, NALL>();
            float4 C = sum8x4<UNIT>(sb + REG + c * 144 + b * 16), S = sum8x4<UNIT>(sb + REG + 1152 + c * 144 + b * 16);
            S.x *= -LOG2E; S.y *= -LOG2E; C.x *= LOG2E; C.y *= LOG2E;
            sts128f(sb + SM_PR + lane * 16, C.x, C.y, C.z, C.w); sts128f(sb + SM_PR + lane * 16, S.x, S.y, S.z, S.w);
            sts128(sb + SM_PR + lane * 16, make_uint4(pi, si, (uint32_t)(size_t)ho, (uint32_t)((size_t)ho >> 32)));
            bar_sync<B_FIN, NALL>();
            const float4 s0_ = lds128(si), s1_ = lds128(si + 16), s2_ = lds128(si + 32), s3_ = lds128(si + 48);
            const float4 p = sum8x4<SCR>(pi);
            const float mean = (((s0_.x + s0_.z) + (s1_.x + s1_.z)) + ((s2_.x + s2_.z) + (s3_.x + s3_.z))) * (1.0f / DM);
            const float sq = (((s0_.y + s0_.w) + (s1_.y + s1_.w)) + ((s2_.y + s2_.w) + (s3_.y + s3_.w))) * (1.0f / DM);
            float rs; asm("rsqrt.approx.ftz.f32 %0, %1;" : "=f"(rs) : "f"(fmaxf(sq - mean * mean, 0.f) + 1e-5f));
            const float e0 = rs * (mean * C.x - LOG2E * p.x) + S.x, e1 = rs * (mean * C.y - LOG2E * p.y) + S.y;
            const float u0 = rs * (p.z - mean * C.z) + S.z, u1 = rs * (p.w - mean * C.w) + S.w;
            const unsigned hw = pack2(rcp(1.0f + ex2(e0)) * u0, rcp(1.0f + ex2(e1)) * u1);
            stg_rlx32(ho, hw); stg_rlx32(ho + 4096, hw);
        }
        return;
    }
    const unsigned ce = (lane >> 3) * (DM * 2) + w * 128 + (lane & 7) * 16;
    const uint4 ca = ldg_nc((const char*)pc + ce), cb = ldg_nc((const char*)pc + ce + 4 * DM * 2);
    const uint4 xa = ldg_nc((const char*)px + w * (DM * 2) + lane * 16), xb = ldg_nc((const char*)px + w * (DM * 2) + lane * 16 + 512);
    const uint4 xc = ldg_nc((const char*)px + ce), xd = ldg_nc((const char*)px + ce + 4 * DM * 2);
    if (w >= 4) pf_map(&P.wm + (w & 3));
    char* const qout = X + blk(X_Q, head >> 1, tid >> 7) + (head & 1) * 2048 + ((tid >> 4) & 7) * 256 + (cta & 3) * 64 + (tid & 3) * 16 + ((tid >> 2) & 3) * 4;
    char* const mout = X + blk(X_M1, cta >> 5, w) + (cta & 31) * 128 + lane * 4;
    stg_rlx32(qout, 0);
    if (w < 2) stg_rlx32(mout, 0);
    uint32_t sc[8], xf[8];
    {
        const uint32_t a = (lane >> 3) * 128 + (((lane & 7) ^ (lane >> 3)) << 4), b = (lane & 7) * 128 + (((lane >> 3) ^ (lane & 7)) << 4);
        const uint32_t cs = sb + SM_SC + w * 1024;
        sts128(cs + a, make_uint4(silu2(ca.x), silu2(ca.y), silu2(ca.z), silu2(ca.w)));
        sts128(cs + 512 + (a ^ 64), make_uint4(silu2(cb.x), silu2(cb.y), silu2(cb.z), silu2(cb.w)));
        sts128(myscr + a, xc); sts128(myscr + 512 + (a ^ 64), xd);
        __syncwarp();
        ldsm(*(uint32_t(*)[4])&sc[0], cs + b); ldsm(*(uint32_t(*)[4])&sc[4], cs + (b ^ 64));
        ldsm(*(uint32_t(*)[4])&xf[0], myscr + b); ldsm(*(uint32_t(*)[4])&xf[4], myscr + (b ^ 64));
        __syncwarp();
    }
    {
        float v[16] = {blo(xa.x), bhi(xa.x), blo(xa.y), bhi(xa.y), blo(xa.z), bhi(xa.z), blo(xa.w), bhi(xa.w),
                       blo(xb.x), bhi(xb.x), blo(xb.y), bhi(xb.y), blo(xb.z), bhi(xb.z), blo(xb.w), bhi(xb.w)};
        float s = 0;
#pragma unroll
        for (int i = 0; i < 16; i++) s += v[i];
#pragma unroll
        for (int o = 16; o; o >>= 1) s += __shfl_xor_sync(~0u, s, o);
        s *= (1.0f / DM);
        float q2 = 0;
#pragma unroll
        for (int i = 0; i < 16; i++) q2 += (v[i] - s) * (v[i] - s);
#pragma unroll
        for (int o = 16; o; o >>= 1) q2 += __shfl_xor_sync(~0u, q2, o);
        uint32_t mu2; float rs; ln_consts(s, q2 * (1.0f / DM), mu2, rs);
        if (lane == 0) sts64(sb + SM_ST + w * 8, __uint_as_float(mu2), rs);
    }
    const int lrow = (lane & 7) + ((lane >> 4) << 3), lch = (lane >> 3) & 1;
    const uint32_t off64 = lrow * 64 + ((lch ^ ((lrow >> 1) & 3)) << 4);
    const uint32_t off128 = lrow * 128 + ((lch ^ (lane & 7)) << 4);
    bar_sync<B_INIT, NTHR>();
    mbar_wait(sb + SM_BM, 0);
    {
        float a[4] = {0, 0, 0, 0}, b[4] = {0, 0, 0, 0};
        uint32_t r[4], u[4];
        ldsm_t(r, sb + 4 * REG + (w * 64 + lane) * 16); ldsm_t(u, sb + 4 * REG + (w * 64 + 32 + lane) * 16);
        mma(a, sc[0], 0, sc[1], 0, r[0], r[1]); mma(b, sc[4], 0, sc[5], 0, u[0], u[1]);
        mma(a, sc[2], 0, sc[3], 0, r[2], r[3]); mma(b, sc[6], 0, sc[7], 0, u[2], u[3]);
        sts64(myscr + SC_M + lane * 8, a[0] + b[0], a[1] + b[1]);
    }
    bar_arrive<B_MOD, NTHR>();
    bar_sync<B_ALL, 256>();
    if (w < 2) {
        const float2 m = sum8(scr + SC_M + lane * 8);
        stg_rlx32(mout, ~pack2(m.x, m.y));
    }
    if (tid < 8 * XC) stg_rlx128(X + X_X1 + (cta * 8 * XC + tid) * 16, make_uint4(SENT, SENT, SENT, SENT));
    else if (tid >= 232) stg_rlx128(X + X_HM + (cta * 24 + tid - 232) * 16, make_uint4(SENT, SENT, SENT, SENT));
    {
        const float2 st = lds64(sb + SM_ST + g * 8);
#pragma unroll
        for (int i = 0; i < 8; i++) xf[i] = ln_norm(xf[i], __float_as_uint(st.x), st.y);
    }
    {
        unsigned sv[8], cv[8]; int n = 0;
        bar_sync<B_SIDE, NTHR>();
        const char* const mp = X + blk(X_M1, w >> 2, lds32u(sb + SM_SIDE)) + (w & 3) * 1024 + lane * 4;
        if (lane == 0) while (!ldg_rlx32(mp + 16384 + 7 * 128)) { nap(40); if (++n > SPIN_MAX) __trap(); }
        __syncwarp();
#pragma unroll
        for (int j = 0; j < 8; j++) { sv[j] = ldg_rlx32(mp + j * 128); cv[j] = ldg_rlx32(mp + 16384 + j * 128); }
        while (true) {
            unsigned m = ~0u;
#pragma unroll
            for (int j = 0; j < 8; j++) m = min(m, min(sv[j], cv[j]));
            if (__all_sync(~0u, m)) break;
#pragma unroll
            for (int j = 0; j < 8; j++) { if (!sv[j]) sv[j] = ldg_rlx32(mp + j * 128); if (!cv[j]) cv[j] = ldg_rlx32(mp + 16384 + j * 128); }
            if (++n > SPIN_MAX) __trap();
        }
#pragma unroll
        for (int j = 0; j < 8; j++) xf[j] = add2(mul2(xf[j], add2(~cv[j], ONE2)), ~sv[j]);
        mbar_wait(bar0 + 48, 0);
        float acc[4][4] = {};
#pragma unroll
        for (int j = 0; j < 4; j++) {
            uint32_t r[4], u[4];
            ldsm_t(r, s2 + REG + j * 1024 + off64); ldsm_t(u, s2 + REG + j * 1024 + (off64 ^ 32));
            mma(acc[0], xf[2 * j], 0, xf[2 * j + 1], 0, r[0], r[2]); mma(acc[1], xf[2 * j], 0, xf[2 * j + 1], 0, r[1], r[3]);
            mma(acc[2], xf[2 * j], 0, xf[2 * j + 1], 0, u[0], u[2]); mma(acc[3], xf[2 * j], 0, xf[2 * j + 1], 0, u[1], u[3]);
        }
#pragma unroll
        for (int n2 = 0; n2 < 4; n2++) sts64(myscr + SC_Q + g * 160 + n2 * 32 + t * 8, acc[n2][0], acc[n2][1]);
    }
    bar_arrive<B_WQ, NTHR>();
    bar_sync<B_ALL, 256>();
    {
        const float2 s = sum8(scr + SC_Q + ((tid >> 4) & 7) * 160 + (tid & 15) * 8);
        stg_rlx32(qout, ~pack2(s.x, s.y));
    }
    uint32_t q[16];
    {
        int n = 0;
        const char* const qp = X + blk(X_Q, head >> 1, lds32u(sb + SM_SIDE)) + (head & 1) * 2048 + bat * 256 + t * 16;
        uint4 v[4];
#pragma unroll
        for (int j = 0; j < 4; j++) v[j] = ldg_rlx128(qp + j * 64);
        while (true) {
            bool bad[4];
#pragma unroll
            for (int j = 0; j < 4; j++) bad[j] = !min(min(v[j].x, v[j].y), min(v[j].z, v[j].w));
            if (!__any_sync(~0u, bad[0] | bad[1] | bad[2] | bad[3])) break;
#pragma unroll
            for (int j = 0; j < 4; j++) if (bad[j]) v[j] = ldg_rlx128(qp + j * 64);
            if (++n > SPIN_MAX) __trap();
        }
#pragma unroll
        for (int j = 0; j < 4; j++) { q[4 * j] = ~v[j].x; q[4 * j + 1] = ~v[j].y; q[4 * j + 2] = ~v[j].z; q[4 * j + 3] = ~v[j].w; }
    }
    bar_arrive<B_Q, NTHR>();

    float o[2][4] = {};
    float mrun = -3.0e38f, lrun = 0.f;
    uint32_t wa[16][4], pb[2];
#pragma unroll
    for (int i = 0; i < 16; i++) wa[i][0] = wa[i][1] = wa[i][2] = wa[i][3] = 0;
    const uint32_t offk = (lane & 15) * 128 + (((lane >> 4) ^ (lane & 7)) << 4);
    float p0, p1;
    auto scores = [&](uint32_t a0) {
        uint32_t kf[8][4];
#pragma unroll
        for (int j = 0; j < 8; j++) ldsm(kf[j], ((a0 + offk) ^ ((j & 3) << 5)) + (j >> 2) * 2048);
        float sa[4] = {0, 0, 0, 0}, sb2[4] = {0, 0, 0, 0};
#pragma unroll
        for (int j = 0; j < 8; j += 2) { mma(sa, kf[j], q[2 * j], q[2 * j + 1]); mma(sb2, kf[j + 1], q[2 * j + 2], q[2 * j + 3]); }
        uint32_t u = pack2(sa[0] + sb2[0], sa[2] + sb2[2]);
        u = pack2(blo(u) * SCALE, bhi(u) * SCALE);
        const float z0 = blo(u), z1 = bhi(u);
        float mx = fmaxf(z0, z1);
        mx = fmaxf(mx, __shfl_xor_sync(~0u, mx, 4)); mx = fmaxf(mx, __shfl_xor_sync(~0u, mx, 8)); mx = fmaxf(mx, __shfl_xor_sync(~0u, mx, 16));
        mx = fmaxf(mx, mrun);
        const float f = ex2((mrun - mx) * LOG2E);
        p0 = ex2((z0 - mx) * LOG2E); p1 = ex2((z1 - mx) * LOG2E);
        mrun = mx; lrun = lrun * f + (p0 + p1);
#pragma unroll
        for (int j = 0; j < 4; j++) { o[0][j] *= f; o[1][j] *= f; }
    };
    const int kvrow = (bat * NH + head) * SK + (SK - WIN) + (w & 3) * 16;
    const int wofs = (w * 8 + (cta & 7)) * TAU / 8;
    auto request = [&](int u) {
        sts32u(bar0 + 56, u - 1);
        while ((int)(now_ns() - lds32u(sb + SM_AN) - u * 8 * TAU - wofs) < 0) nap(20);
        const int sl = (~u & 2) + (u & 1);
        mbar_expect(bar0 + sl * 8, UNIT); tma_kv(s0 + sl * REG, &P.k + (u & 1), kvrow + tile_key(u >> 1), bar0 + sl * 8, pol);
    };
#pragma unroll 1
    for (int it = 0; it < NT - 1; it++) {
        const int si = it < 3 ? it : (it + 1) & 1;
        const uint32_t bar = bar0 + si * 16, a0 = s0 + si * 2 * REG;
        const uint32_t par = it < 3 ? 0 : ((it - 1) >> 1) & 1;
        const bool refill = lane == 0 && it >= 2;
        mbar_wait(bar, par);
        if (refill) {
            request(2 * it + 2);
            const int e = it - WOA_ISSUE;
            if (e == 0) mbar_expect(barC, 2 * UNIT);
            if (e == 0 || e == WO_GAP) tma2d(s2 + (e ? REG : 0), &P.wo, w * 64, head * 128 + (e ? 32 : 0), barC);
        }
        __syncwarp();
        if (it == WOA_READ) {
            mbar_wait(barC, 1);
#pragma unroll
            for (int j = 0; j < 16; j++) ldsm_t(wa[j], s2 + (j >> 3) * REG + ((j >> 2) & 1) * 2048 + (off128 ^ ((j & 3) << 5)));
        }
        scores(a0);
        pb[0] = movm(pack2(p0, p0)); pb[1] = movm(pack2(p1, p1));
        mbar_wait(bar + 8, par);
        if (refill) request(2 * it + 3);
        __syncwarp();
        uint32_t vf[8][4];
#pragma unroll
        for (int j = 0; j < 8; j++) ldsm_t(vf[j], ((a0 + off128) ^ ((j & 3) << 5)) + (j >> 2) * 2048 + REG);
#pragma unroll
        for (int j = 0; j < 8; j++) { const bool on = (g >> 1) == (j >> 1); mma(o[j & 1], vf[j], on ? pb[0] : 0, on ? pb[1] : 0); }
    }
    {
        uint32_t wb[16][4];
        mbar_wait(bar0, 1);
        if (rid >= DN0) bar_arrive<B_LAST, NTHR>();
        scores(s0);
        lrun += __shfl_xor_sync(~0u, lrun, 4); lrun += __shfl_xor_sync(~0u, lrun, 8); lrun += __shfl_xor_sync(~0u, lrun, 16);
        if (lane == 0) sts64(sb + SM_ML + w * 8, mrun, lrun);
        bar_arrive<B_ML, NTHR>();
        pb[0] = movm(pack2(p0, p0)); pb[1] = movm(pack2(p1, p1));
        const uint32_t va = pin(s0 + REG + off128);
        auto load_wb = [&](int j) { ldsm_t(wb[j], (va ^ ((j & 3) << 5)) + (3 + (j >> 3)) * REG + ((j >> 2) & 1) * 2048); };
        const uint32_t ho = pin(s0 + w * 16 + ((lane & 7) >> 1) * 64 + ((lane >> 3) & 1) * 32 + (lane & 1) * 16), oa = pin(sb + (lane & 7) * (UNIT + 16) + (lane >> 3) * 16);
        const uint32_t rd = pin((t >> 1) * 16 + w * 2 + (g >> 2));
        char* const pp = pin(X + X_PART + ((cta & 3) * 32 + rd) * 8192 + head * 128 + (g & 3) * 32 + (t & 1) * 16);
        const uint32_t ln = pin(lane), wbar = pin(barC + 8);
        mbar_wait(bar0 + 8, 1);
        {
            uint32_t vf[8][4];
            float o2[2][4] = {};
#pragma unroll
            for (int j = 0; j < 8; j++) ldsm_t(vf[j], (va ^ ((j & 3) << 5)) + (j >> 2) * 2048);
#pragma unroll
            for (int j = 0; j < 8; j++) { const bool on = (ln >> 3) == (j >> 1); mma((j & 2) ? o2[j & 1] : o[j & 1], vf[j], on ? pb[0] : 0, on ? pb[1] : 0); }
            asm volatile("stmatrix.sync.aligned.m8n8.x2.trans.shared.b16 [%0], {%1,%2};" :: "r"(ho), "r"(pack2(o[0][0] + o2[0][0], o[0][2] + o2[0][2])), "r"(pack2(o[1][0] + o2[1][0], o[1][2] + o2[1][2])) : "memory");
        }
        bar_sync<B_RDY, NALL>();
        float y[4][4] = {};
        uint32_t ob[4][4];
#pragma unroll
        for (int i2 = 0; i2 < 4; i2++) ldsm(ob[i2], oa + i2 * 64);
        const float2 f = lds64(sb + SM_ML + 64 + (ln & 3) * 8);
        const unsigned half = (lds32u(sb + SM_MASK) >> rd & 1) * 4096;
#pragma unroll
        for (int j = 0; j < 8; j++) {
            if (j == WK) {
                if (!mbar_test(wbar - 8, 0)) mbar_wait(wbar - 8, 0);
#pragma unroll
                for (int k = 0; k < 8; k++) load_wb(k);
            }
            if (j == WJ) {
                if (!mbar_test(wbar, 1)) mbar_wait(wbar, 1);
#pragma unroll
                for (int k = 8; k < 16; k++) load_wb(k);
            }
#pragma unroll
            for (int i = 0; i < 4; i++) mmav(y[i], j < 4 ? wa[j * 4 + i] : wb[(j - 4) * 4 + i], ob[j >> 1][2 * (j & 1)], ob[j >> 1][2 * (j & 1) + 1]);
        }
        uint32_t r[4];
#pragma unroll
        for (int i = 0; i < 4; i++) {
            const float lo = f.x * y[i][0] + f.y * y[i][1], hi = f.x * y[i][2] + f.y * y[i][3];
            r[i] = __float_as_uint(((ln & 1) ? hi : lo) + __shfl_xor_sync(~0u, (ln & 1) ? lo : hi, 1));
        }
        asm("min.u32 %0, %0, 0xFFFFFFFE;" : "+r"(r[0]));
        stg_b128(pp + half, make_uint4(r[0], r[1], r[2], r[3]));
    }
    const unsigned side = lds32u(sb + SM_SIDE);
    const char* const x1p = X + (rid & (XC - 1)) * 16384;
    if (rid < NF1) {
        uint32_t wg[4][4], wu[4][4];
        const char* const xp = pin(x1p + blk(X_X1, w >> 2, side) + (w & 3) * 1024 + lane * 16);
        float4 c1[2], sv[2];
#pragma unroll
        for (int h = 0; h < 2; h++) { sv[h] = lds128(sb + SM_MN + (w * 2 + h) * 512 + lane * 16); c1[h] = lds128(sb + SM_MN + 8192 + (w * 2 + h) * 512 + lane * 16); }
        const uint32_t po = pin(myscr + SC_F1 + g * 144 + t * 32), so = pin(t == (g >> 1) ? sb + SM_ST + g * 64 + w * 8 : myscr + 1792 + lane * 8), odd = pin(g & 1);
        const uint32_t wbar = sb + SM_BAR + (w >> 1) * 64 + 48;
        uint4 x0, x1;
        const bool early = go_first(wbar, 1);
        if (early) { spin(clock(), (7 - w) * XDW); x0 = ldg_rlx2x64(xp); x1 = ldg_rlx2x64(xp + 512); mbar_wait(wbar, 1); }
#pragma unroll
        for (int j = 0; j < 4; j++) {
            const uint32_t a = sb + 2 * REG + w * 2048 + (((lane & 7) >> 1) + (lane & 1) * 4 + j * 8 + (lane >> 4) * 32) * 32 + ((lch ^ (lane & 1)) << 4);
            ldsm_t(wg[j], a); ldsm_t(wu[j], a + 16384);
        }
        {
            float cg[4] = {}, cu[4] = {}, sg[4] = {}, su[4] = {};
#pragma unroll
            for (int j = 0; j < 4; j++) {
                const float4 a = c1[j & 1], b = sv[j & 1];
                const uint32_t a0 = __float_as_uint(j >> 1 ? a.z : a.x), a1 = __float_as_uint(j >> 1 ? a.w : a.y), b0 = __float_as_uint(j >> 1 ? b.z : b.x), b1 = __float_as_uint(j >> 1 ? b.w : b.y);
                mma(cg, wg[j], a0, a1); mma(cu, wu[j], a0, a1); mma(sg, wg[j], b0, b1); mma(su, wu[j], b0, b1);
            }
            const uint32_t d = s0 + REG + g * 144 + t * 32;
            sts128f(d, cg[0], cg[2], cu[0], cu[2]); sts128f(d + 16, cg[1], cg[3], cu[1], cu[3]);
            sts128f(d + 1152, sg[0], sg[2], su[0], su[2]); sts128f(d + 1168, sg[1], sg[3], su[1], su[3]);
            bar_arrive<B_PRE, NALL>();
        }
        if (!early) { mbar_wait(sb + SM_BG, 0); spin(clock(), (7 - w) * XDW); x0 = ldg_rlx2x64(xp); x1 = ldg_rlx2x64(xp + 512); }
        int n = 0;
        while (true) {
            const bool b0 = max(x0.x, x0.z) == SENT, b1 = max(x1.x, x1.z) == SENT;
            if (!__any_sync(~0u, b0 | b1)) break;
            if (b0) x0 = ldg_rlx2x64(xp);
            if (b1) x1 = ldg_rlx2x64(xp + 512);
            if (++n > SPIN_MAX) __trap();
        }
        float q0[4] = {}, q1[4] = {}, ag[2][4] = {}, au[2][4] = {};
        {
            mma(q0, x0.x, ONE2, x0.y, ONE2, x0.x, x0.y); mma(q1, x0.z, ONE2, x0.w, ONE2, x0.z, x0.w);
            mma(q0, x1.x, ONE2, x1.y, ONE2, x1.x, x1.y); mma(q1, x1.z, ONE2, x1.w, ONE2, x1.z, x1.w);
#pragma unroll
            for (int j = 0; j < 4; j++) {
                const uint4 xv = (j & 1) ? x1 : x0; const float4 a = c1[j & 1];
                const uint32_t h0 = mul2(j >> 1 ? xv.z : xv.x, __float_as_uint(j >> 1 ? a.z : a.x)), h1 = mul2(j >> 1 ? xv.w : xv.y, __float_as_uint(j >> 1 ? a.w : a.y));
                mma(ag[j & 1], wg[j], h0, h1); mma(au[j & 1], wu[j], h0, h1);
            }
        }
        sts64(so, odd ? q0[3] + q1[3] : q0[2] + q1[2], odd ? q0[1] + q1[1] : q0[0] + q1[0]);
        sts128f(po, ag[0][0] + ag[1][0], ag[0][2] + ag[1][2], au[0][0] + au[1][0], au[0][2] + au[1][2]);
        sts128f(po + 16, ag[0][1] + ag[1][1], ag[0][3] + ag[1][3], au[0][1] + au[1][1], au[0][3] + au[1][3]);
        bar_arrive<B_FIN, NALL>();
    } else if (rid >= DN0) {
        const int f = rid - DN0;
        uint32_t wd[12][4];
        const char* const hp0 = pin(X + blk(X_HM, 0, side) + w * 512 + lane * 16);
        const char* const hp1 = pin(X + blk(X_HM, 1, side) + w * 512 + lane * 16);
        auto hm = [&](int j) { return ldg_rlx128((j & 1 ? hp1 : hp0) + (j >> 1) * 16384); };
        __nv_bfloat16* const op = pin(P.out + ((tid >> 4) & 7) * DM + f * 16 + (tid & 15));
        const uint32_t po = pin(myscr + SC_DN + t * 160 + g * 16), pi = pin(scr + SC_DN + (w & 3) * 160 + (tid & 7) * 16 + (tid & 8) + ((tid >> 4) & 1) * 4), gi = pin(sb + SM_MN + tid * 2), first = pin(w < 4);
        uint4 hv[6]; int n = 0;
        auto first_poll = [&]() {
            spin(clock(), w * HDW);
#pragma unroll
            for (int j = 0; j < 6; j++) hv[j] = (j < 5 || w < 3) ? hm(j) : make_uint4(0, 0, 0, 0);
        };
        const bool early = go_first(sb + SM_BT, 0);
        if (early) { first_poll(); mbar_wait(sb + SM_BT, 0); }
#pragma unroll
        for (int j = 0; j < 12; j++)
            if (j < 10 || w < 3) ldsm_t(wd[j], sb + 2 * REG + 16384 + (w + (j >> 1) * 8) * 1024 + (j & 1) * 512 + (((lane >> 1) & 1) + (lane & 1) * 2 + (lane & 4) + (lane >> 4) * 8) * 32 + ((lch ^ ((lane >> 2) & 1)) << 4));
            else wd[j][0] = wd[j][1] = wd[j][2] = wd[j][3] = 0;
        if (!early) { mbar_wait(sb + SM_BG, 0); first_poll(); }
        while (true) {
            unsigned m[6];
#pragma unroll
            for (int j = 0; j < 6; j++) m[j] = max(max(hv[j].x, hv[j].y), max(hv[j].z, hv[j].w));
            if (__all_sync(~0u, max(max(max(m[0], m[1]), m[2]), max(max(m[3], m[4]), m[5])) != SENT)) break;
#pragma unroll
            for (int j = 0; j < 6; j++) if (m[j] == SENT) hv[j] = hm(j);
            if (++n > SPIN_MAX) __trap();
        }
        float d[4][4] = {};
#pragma unroll
        for (int j = 0; j < 6; j++) { mma(d[(2 * j) & 3], wd[2 * j], hv[j].x, hv[j].y); mma(d[(2 * j + 1) & 3], wd[2 * j + 1], hv[j].z, hv[j].w); }
        sts128f(po, (d[0][0] + d[1][0]) + (d[2][0] + d[3][0]), (d[0][1] + d[1][1]) + (d[2][1] + d[3][1]), (d[0][2] + d[1][2]) + (d[2][2] + d[3][2]), (d[0][3] + d[1][3]) + (d[2][3] + d[3][3]));
        bar_sync<B_DN, NTHR>();
        if (first) {
            float v[8];
#pragma unroll
            for (int i = 0; i < 8; i++) v[i] = lds32(pi + i * SCR);
            unsigned gw, res;
            asm volatile("ld.shared.u16 %0, [%1];" : "=r"(gw) : "r"(gi) : "memory"); asm volatile("ld.shared.u16 %0, [%1];" : "=r"(res) : "r"(gi + 256) : "memory");
            asm volatile("st.global.u16 [%0], %1;" :: "l"(op), "h"((unsigned short)add2(res, mul2(gw, pack2(((v[0] + v[1]) + (v[2] + v[3])) + ((v[4] + v[5]) + (v[6] + v[7])), 0.f)))) : "memory");
        }
    }
}

typedef CUresult (*EncodeFn)(CUtensorMap*, CUtensorMapDataType, cuuint32_t, void*, const cuuint64_t*, const cuuint64_t*, const cuuint32_t*,
                             const cuuint32_t*, CUtensorMapInterleave, CUtensorMapSwizzle, CUtensorMapL2promotion, CUtensorMapFloatOOBfill);

void make2d(EncodeFn enc, CUtensorMap* m, const void* p, int rows, int cols, int brows, int bcols, CUtensorMapSwizzle sw) {
    cuuint64_t dims[2] = {(cuuint64_t)cols, (cuuint64_t)rows}, strides[1] = {(cuuint64_t)cols * 2};
    cuuint32_t box[2] = {(cuuint32_t)bcols, (cuuint32_t)brows}, es[2] = {1, 1};
    enc(m, CU_TENSOR_MAP_DATA_TYPE_BFLOAT16, 2, (void*)p, dims, strides, box, es, CU_TENSOR_MAP_INTERLEAVE_NONE, sw,
        CU_TENSOR_MAP_L2_PROMOTION_L2_128B, CU_TENSOR_MAP_FLOAT_OOB_FILL_NONE);
}
void make5d(EncodeFn enc, CUtensorMap* m, const void* p, int cols, const unsigned (&n)[4], const unsigned (&s)[4], unsigned nb) {
    const cuuint64_t rs = (cuuint64_t)cols * 2;
    cuuint64_t dims[5] = {(cuuint64_t)cols, n[0], n[1], n[2], n[3]}, strides[4] = {rs * s[0], rs * s[1], rs * s[2], rs * s[3]};
    cuuint32_t box[5] = {16, n[0], n[1], n[2], nb}, es[5] = {1, 1, 1, 1, 1};
    enc(m, CU_TENSOR_MAP_DATA_TYPE_BFLOAT16, 5, (void*)p, dims, strides, box, es, CU_TENSOR_MAP_INTERLEAVE_NONE, CU_TENSOR_MAP_SWIZZLE_32B,
        CU_TENSOR_MAP_L2_PROMOTION_L2_128B, CU_TENSOR_MAP_FLOAT_OOB_FILL_NONE);
}
void makekv(EncodeFn enc, CUtensorMap* m, const void* p) {
    cuuint64_t dims[3] = {64, (cuuint64_t)NB * NH * SK, 2}, strides[2] = {256, 128};
    cuuint32_t box[3] = {64, 16, 2}, es[3] = {1, 1, 1};
    enc(m, CU_TENSOR_MAP_DATA_TYPE_BFLOAT16, 3, (void*)p, dims, strides, box, es, CU_TENSOR_MAP_INTERLEAVE_NONE, CU_TENSOR_MAP_SWIZZLE_128B,
        CU_TENSOR_MAP_L2_PROMOTION_NONE, CU_TENSOR_MAP_FLOAT_OOB_FILL_NONE);
}

}

extern "C" void kernel_launch(void* const* d_in, const int* in_sizes, int n_in, void* d_out, int out_size) {
    (void)in_sizes; (void)n_in; (void)out_size;
    static EncodeFn enc = nullptr;
    static void* raw = nullptr;
    if (!enc) {
        void* fn = nullptr; cudaDriverEntryPointQueryResult qr;
        cudaGetDriverEntryPoint("cuTensorMapEncodeTiled", &fn, cudaEnableDefault, &qr);
        enc = (EncodeFn)fn;
        cudaFuncSetAttribute(fused_kernel, cudaFuncAttributeMaxDynamicSharedMemorySize, SM_TOTAL);
        cudaGetSymbolAddress(&raw, g_raw);
    }
    Params P;
    makekv(enc, &P.k, d_in[1]);
    makekv(enc, &P.v, d_in[2]);
    make2d(enc, &P.wq, d_in[3], DM, NH * DH, 64, 32, CU_TENSOR_MAP_SWIZZLE_64B);
    make2d(enc, &P.wo, d_in[4], NH * DH, DM, 32, 64, CU_TENSOR_MAP_SWIZZLE_128B);
    make2d(enc, &P.wm, d_in[10], DM, 6 * DM, 256, 8, CU_TENSOR_MAP_SWIZZLE_NONE);
    make2d(enc, &P.wn, d_in[10], DM, 6 * DM, 256, 16, CU_TENSOR_MAP_SWIZZLE_32B);
    make5d(enc, &P.wg, d_in[6], FF, {4, 2, 4, 16}, {1, 16, 4, 32}, 4);
    make5d(enc, &P.wu, d_in[7], FF, {4, 2, 4, 16}, {1, 16, 4, 32}, 4);
    make5d(enc, &P.wd, d_in[8], DM, {8, 4, 1, 43}, {4, 1, 1, 32}, 43);
    P.out = (__nv_bfloat16*)d_out;
    typedef const __nv_bfloat16* W;
    fused_kernel<<<NCTA, NALL, SM_TOTAL>>>((W)d_in[0], (W)d_in[9], (W)d_in[1], (W)d_in[10], (W)d_in[3], (char*)(((size_t)raw + X_ALIGN - 1) & ~(size_t)(X_ALIGN - 1)), P);
}
```

```cpp
#include <cuda_runtime.h>
#include <cuda_bf16.h>
#include <cuda.h>
#include <stdint.h>

namespace {

constexpr int NB = 8, DM = 512, NH = 32, DH = 128, SK = 4096, WIN = 1024, FF = 1376;
constexpr int NCTA = 128, NTHR = 288, NALL = 320;
constexpr int NT = 16;
constexpr int NF1 = 86, DN0 = 96;
constexpr unsigned SENT = 0xFFFFFFFFu;
constexpr int SPIN_MAX = 1 << 20;

constexpr int PWIN0 = 12;
constexpr int PWIN = 16;
constexpr int PSW = 22;
constexpr int NTRK = 8;
constexpr int PFK = 2;
constexpr int QN = 7;
constexpr int TAU = 166;
constexpr int ANCH0 = 176;
constexpr int LEAD = 1600;
constexpr int PACE0 = 7000;
constexpr int PNAP = 200;
constexpr int WOA_ISSUE = 3;
constexpr int WO_GAP = 2;
constexpr int WOA_READ = 8;
constexpr int WK = 3;
constexpr int WJ = 5;
constexpr int WO0 = 530;
constexpr int WOS = 30;
constexpr int WOG = 350;
constexpr int W0 = 1240;
constexpr int WS = 200;
constexpr int WD0 = 1980;
constexpr int RT0 = 2180;
constexpr int HD0 = 1250;
constexpr int XDW = 30;
constexpr int HDW = 45;
constexpr int XC = 2;

constexpr int UNIT = 4096, REG = 8 * UNIT;
constexpr int SM_SCR = 6 * REG;
constexpr int SCR = 2048;
constexpr int SM_MN = SM_SCR + 8 * SCR;
constexpr int SM_SC = SM_MN + 8192;
constexpr int SM_BAR = SM_SC + 8192;
constexpr int SM_BM = SM_BAR + 512, SM_BT = SM_BM + 8, SM_BN = SM_BM + 16, SM_BG = SM_BM + 24;
constexpr int SM_AN = SM_BM + 32, SM_SIDE = SM_BM + 36, SM_TAG = SM_BM + 40, SM_MASK = SM_BM + 44;
constexpr int SM_ST = SM_BAR + 576;
constexpr int SM_ML = SM_ST + 512;
constexpr int SM_PR = SM_ML + 96;
constexpr int SM_TOTAL = SM_PR + 512;
constexpr int SC_M = 0, SC_Q = 256;
constexpr int SC_F1 = 0, SC_DN = 0, SC_RX = 1536;
constexpr int B_INIT = 0, B_ALL = 2, B_MOD = 3, B_WQ = 4, B_LAST = 5, B_RDY = 6, B_DN = 7, B_PRE = 8, B_FIN = 9, B_STG = 10, B_SIDE = 11, B_Q = 12, B_ML = 13;

constexpr unsigned HOME = 0xB3000;
constexpr int X_PART = 0;
constexpr int X_Q = 0x100000;
constexpr int X_M1 = 0x140000;
constexpr int X_X1 = 0x150000;
constexpr int X_HM = 0x160000;
constexpr int X_MOD = 0x170000;
constexpr int X_SIDE = 0x176000;
constexpr int X_EPOCH = 0x176400;
constexpr int X_READY = 0x176480;
constexpr int X_LAG = 0x178000;
constexpr int X_ANC = 0x158000;
constexpr int X_PRB = 0x180000;
constexpr int X_ALIGN = 0x200000;
static_assert(XC == 2, "one store writes all copies of x1");
__device__ uint4 g_raw[2 * X_ALIGN / 16];
__device__ __forceinline__ unsigned blk(unsigned base, unsigned k, unsigned s) { const unsigned o = base + k * 8192; return o + ((__popc(o & HOME) ^ s) & 1) * 4096; }

struct Params {
    CUtensorMap wm, wq, k, v, wn, wo, wg, wu, wd;
    __nv_bfloat16* out;
};

__device__ __forceinline__ int tile_key(int i) { return (i & 1) * 128 + (i & 2) * 32 + (i & 12) * 64; }

__device__ __forceinline__ uint32_t smem_u32(const void* p) { return (uint32_t)__cvta_generic_to_shared(p); }
__device__ __forceinline__ void mbar_init(uint32_t a, uint32_t c) { asm volatile("mbarrier.init.shared::cta.b64 [%0], %1;" :: "r"(a), "r"(c) : "memory"); }
__device__ __forceinline__ void mbar_expect(uint32_t a, uint32_t b) { asm volatile("mbarrier.arrive.expect_tx.shared::cta.b64 _, [%0], %1;" :: "r"(a), "r"(b) : "memory"); }
__device__ __forceinline__ void mbar_wait(uint32_t a, uint32_t par) {
    uint32_t ok; int n = 0;
    do {
        asm volatile("{\n.reg .pred p;\nmbarrier.try_wait.parity.shared::cta.b64 p, [%1], %2, 2000;\nselp.u32 %0, 1, 0, p;\n}" : "=r"(ok) : "r"(a), "r"(par) : "memory");
        if (++n > SPIN_MAX) __trap();
    } while (!ok);
}
__device__ __forceinline__ bool mbar_test(uint32_t a, uint32_t par) {
    uint32_t ok; asm volatile("{\n.reg .pred p;\nmbarrier.test_wait.parity.shared::cta.b64 p, [%1], %2;\nselp.u32 %0, 1, 0, p;\n}" : "=r"(ok) : "r"(a), "r"(par) : "memory"); return ok;
}
__device__ __forceinline__ void tma2d(uint32_t dst, const CUtensorMap* m, int x, int y, uint32_t bar) {
    asm volatile("cp.async.bulk.tensor.2d.shared::cluster.global.mbarrier::complete_tx::bytes [%0], [%1, {%3, %4}], [%2];"
                 :: "r"(dst), "l"(m), "r"(bar), "r"(x), "r"(y) : "memory");
}
__device__ __forceinline__ void tma5d(uint32_t dst, const CUtensorMap* m, int x, int y, uint32_t bar) {
    asm volatile("cp.async.bulk.tensor.5d.shared::cluster.global.mbarrier::complete_tx::bytes [%0], [%1, {%3, 0, 0, 0, %4}], [%2];"
                 :: "r"(dst), "l"(m), "r"(bar), "r"(x), "r"(y) : "memory");
}
__device__ __forceinline__ void tma_kv(uint32_t dst, const CUtensorMap* m, int row, uint32_t bar, uint64_t pol) {
    asm volatile("cp.async.bulk.tensor.3d.shared::cluster.global.mbarrier::complete_tx::bytes.L2::cache_hint [%0], [%1, {0, %3, 0}], [%2], %4;"
                 :: "r"(dst), "l"(m), "r"(bar), "r"(row), "l"(pol) : "memory");
}
__device__ __forceinline__ void pf_bulk(const void* p, uint32_t n) { asm volatile("cp.async.bulk.prefetch.L2.global [%0], %1;" :: "l"(p), "r"(n) : "memory"); }
__device__ __forceinline__ void pf_if(const void* p, unsigned i, unsigned n) { asm volatile("{\n.reg .pred p;\nsetp.lt.u32 p, %1, %2;\n@p prefetch.global.L2 [%0];\n}" :: "l"(p), "r"(i), "r"(n) : "memory"); }
__device__ __forceinline__ uint4 ldg_nc(const void* p) { uint4 v; asm volatile("ld.global.nc.v4.u32 {%0,%1,%2,%3}, [%4];" : "=r"(v.x), "=r"(v.y), "=r"(v.z), "=r"(v.w) : "l"(p)); return v; }
__device__ __forceinline__ bool elect() { uint32_t p; asm volatile("{\n.reg .pred p;\nelect.sync _|p, -1;\nselp.u32 %0, 1, 0, p;\n}" : "=r"(p)); return p; }
__device__ __forceinline__ void pf_map(const CUtensorMap* m) { asm volatile("prefetch.tensormap [%0];" :: "l"(m) : "memory"); }
__device__ __forceinline__ void ldsm(uint32_t (&r)[4], uint32_t a) {
    asm volatile("ldmatrix.sync.aligned.m8n8.x4.shared.b16 {%0,%1,%2,%3}, [%4];" : "=r"(r[0]), "=r"(r[1]), "=r"(r[2]), "=r"(r[3]) : "r"(a) : "memory");
}
__device__ __forceinline__ void ldsm_t(uint32_t (&r)[4], uint32_t a) {
    asm volatile("ldmatrix.sync.aligned.m8n8.x4.trans.shared.b16 {%0,%1,%2,%3}, [%4];" : "=r"(r[0]), "=r"(r[1]), "=r"(r[2]), "=r"(r[3]) : "r"(a) : "memory");
}
__device__ __forceinline__ void mma(float (&c)[4], uint32_t a0, uint32_t a1, uint32_t a2, uint32_t a3, uint32_t b0, uint32_t b1) {
    asm("mma.sync.aligned.m16n8k16.row.col.f32.bf16.bf16.f32 {%0,%1,%2,%3}, {%4,%5,%6,%7}, {%8,%9}, {%0,%1,%2,%3};"
        : "+f"(c[0]), "+f"(c[1]), "+f"(c[2]), "+f"(c[3]) : "r"(a0), "r"(a1), "r"(a2), "r"(a3), "r"(b0), "r"(b1));
}
__device__ __forceinline__ void mma(float (&c)[4], const uint32_t (&a)[4], uint32_t b0, uint32_t b1) { mma(c, a[0], a[1], a[2], a[3], b0, b1); }
__device__ __forceinline__ uint32_t pin(uint32_t v) { asm volatile("shfl.sync.bfly.b32 %0, %0, 0, 31, -1;" : "+r"(v)); return v; }
template <class T> __device__ __forceinline__ T* pin(T* p) { const size_t a = (size_t)p; return (T*)(pin((uint32_t)a) | (size_t)pin((uint32_t)(a >> 32)) << 32); }
__device__ __forceinline__ void mmav(float (&c)[4], const uint32_t (&a)[4], uint32_t b0, uint32_t b1) {
    asm volatile("mma.sync.aligned.m16n8k16.row.col.f32.bf16.bf16.f32 {%0,%1,%2,%3}, {%4,%5,%6,%7}, {%8,%9}, {%0,%1,%2,%3};"
        : "+f"(c[0]), "+f"(c[1]), "+f"(c[2]), "+f"(c[3]) : "r"(a[0]), "r"(a[1]), "r"(a[2]), "r"(a[3]), "r"(b0), "r"(b1));
}
__device__ __forceinline__ uint32_t movm(uint32_t a) { uint32_t r; asm volatile("movmatrix.sync.aligned.m8n8.trans.b16 %0, %1;" : "=r"(r) : "r"(a)); return r; }
__device__ __forceinline__ uint32_t pack2(float lo, float hi) { uint32_t r; asm("cvt.rn.bf16x2.f32 %0, %1, %2;" : "=r"(r) : "f"(hi), "f"(lo)); return r; }
__device__ __forceinline__ float blo(uint32_t w) { return __uint_as_float(w << 16); }
__device__ __forceinline__ float bhi(uint32_t w) { return __uint_as_float(w & 0xFFFF0000u); }
__device__ __forceinline__ float rbf(float x) { return blo(pack2(x, 0.f)); }
__device__ __forceinline__ uint32_t add2(uint32_t a, uint32_t b) { uint32_t r; asm("add.rn.bf16x2 %0, %1, %2;" : "=r"(r) : "r"(a), "r"(b)); return r; }
__device__ __forceinline__ uint32_t sub2(uint32_t a, uint32_t b) { uint32_t r; asm("sub.rn.bf16x2 %0, %1, %2;" : "=r"(r) : "r"(a), "r"(b)); return r; }
__device__ __forceinline__ uint32_t mul2(uint32_t a, uint32_t b) { uint32_t r; asm("mul.rn.bf16x2 %0, %1, %2;" : "=r"(r) : "r"(a), "r"(b)); return r; }
constexpr uint32_t ONE2 = 0x3F803F80u;
constexpr float LOG2E = 1.4426950408889634f, SCALE = 0.08838834764831845f;
__device__ __forceinline__ float ex2(float x) { float y; asm("ex2.approx.ftz.f32 %0, %1;" : "=f"(y) : "f"(x)); return y; }
__device__ __forceinline__ uint4 ldg_rlx128(const void* p) {
    uint4 v; asm volatile("ld.relaxed.gpu.global.v4.u32 {%0,%1,%2,%3}, [%4];" : "=r"(v.x), "=r"(v.y), "=r"(v.z), "=r"(v.w) : "l"(p) : "memory"); return v;
}
__device__ __forceinline__ uint4 ldg_rlx2x64(const void* p) {
    unsigned long long a, b; asm volatile("ld.relaxed.gpu.global.v2.u64 {%0,%1}, [%2];" : "=l"(a), "=l"(b) : "l"(p) : "memory");
    return make_uint4((unsigned)a, (unsigned)(a >> 32), (unsigned)b, (unsigned)(b >> 32));
}
__device__ __forceinline__ uint2 ldg_rlx64(const void* p) {
    unsigned long long a; asm volatile("ld.relaxed.gpu.global.u64 %0, [%1];" : "=l"(a) : "l"(p) : "memory"); return make_uint2((unsigned)a, (unsigned)(a >> 32));
}
__device__ __forceinline__ unsigned ldg_acq32(const void* p) { unsigned v; asm volatile("ld.acquire.gpu.global.u32 %0, [%1];" : "=r"(v) : "l"(p) : "memory"); return v; }
__device__ __forceinline__ void red_add(void* p, unsigned v) { asm volatile("red.relaxed.gpu.global.add.u32 [%0], %1;" :: "l"(p), "r"(v) : "memory"); }
__device__ __forceinline__ unsigned now_ns() { unsigned t; asm volatile("mov.u32 %0, %%globaltimer_lo;" : "=r"(t)); return t; }
__device__ __forceinline__ void nap(unsigned ns) { asm volatile("nanosleep.u32 %0;" :: "r"(ns)); }
__device__ __forceinline__ unsigned ldg_rlx32(const void* p) { unsigned v; asm volatile("ld.relaxed.gpu.global.u32 %0, [%1];" : "=r"(v) : "l"(p) : "memory"); return v; }
__device__ __forceinline__ void stg_rlx32(void* p, unsigned v) { asm volatile("st.relaxed.gpu.global.u32 [%0], %1;" :: "l"(p), "r"(v) : "memory"); }
__device__ __forceinline__ void stg_rlx16(void* p, unsigned v) { asm volatile("st.relaxed.gpu.global.u16 [%0], %1;" :: "l"(p), "h"((unsigned short)v) : "memory"); }
__device__ __forceinline__ uint4 ldg_b128(const void* p) {
    unsigned long long a, b; asm volatile("{\n.reg .b128 x;\nld.relaxed.gpu.global.b128 x, [%2];\nmov.b128 {%0,%1}, x;\n}" : "=l"(a), "=l"(b) : "l"(p) : "memory");
    return make_uint4((unsigned)a, (unsigned)(a >> 32), (unsigned)b, (unsigned)(b >> 32));
}
__device__ __forceinline__ void stg_b128(void* p, uint4 v) {
    asm volatile("{\n.reg .b128 x;\nmov.b128 x, {%1,%2};\nst.relaxed.gpu.global.b128 [%0], x;\n}" :: "l"(p), "l"(v.x | ((unsigned long long)v.y << 32)), "l"(v.z | ((unsigned long long)v.w << 32)) : "memory");
}
__device__ __forceinline__ int rowoff(int b, int c) { return ((c >> 6) * 2 + ((c >> 2) & 1)) * 512 + b * 64 + (c & 3) * 16 + ((c >> 3) & 1) * 8 + ((c >> 5) & 1) * 4 + ((c >> 4) & 1) * 2; }
__device__ __forceinline__ void stg_rlx64(void* p, unsigned lo, unsigned hi) {
    unsigned long long a = lo | ((unsigned long long)hi << 32); asm volatile("st.relaxed.gpu.global.u64 [%0], %1;" :: "l"(p), "l"(a) : "memory");
}
__device__ __forceinline__ void stg_rlx128(void* p, uint4 v) { asm volatile("st.relaxed.gpu.global.v4.u32 [%0], {%1,%2,%3,%4};" :: "l"(p), "r"(v.x), "r"(v.y), "r"(v.z), "r"(v.w) : "memory"); }
__device__ __forceinline__ void sts32u(uint32_t a, unsigned x) { asm volatile("st.volatile.shared.u32 [%0], %1;" :: "r"(a), "r"(x) : "memory"); }
__device__ __forceinline__ unsigned lds32u(uint32_t a) { unsigned v; asm volatile("ld.volatile.shared.u32 %0, [%1];" : "=r"(v) : "r"(a) : "memory"); return v; }
__device__ __forceinline__ void spin(unsigned c0, unsigned d) { if (d) while ((unsigned)clock() - c0 < d) {} }
__device__ __forceinline__ void fence_gpu() { asm volatile("fence.acq_rel.gpu;" ::: "memory"); }
template <int ID, int N> __device__ __forceinline__ void bar_sync() { asm volatile("bar.sync %0, %1;" :: "n"(ID), "n"(N) : "memory"); }
template <int ID, int N> __device__ __forceinline__ void bar_arrive() { asm volatile("bar.arrive %0, %1;" :: "n"(ID), "n"(N) : "memory"); }
__device__ __forceinline__ void sts64(uint32_t a, float x, float y) { asm volatile("st.shared.v2.f32 [%0], {%1,%2};" :: "r"(a), "f"(x), "f"(y) : "memory"); }
__device__ __forceinline__ void sts128(uint32_t a, uint4 v) { asm volatile("st.volatile.shared.v4.u32 [%0], {%1,%2,%3,%4};" :: "r"(a), "r"(v.x), "r"(v.y), "r"(v.z), "r"(v.w) : "memory"); }
__device__ __forceinline__ void sts128f(uint32_t a, float x, float y, float z, float w) { asm volatile("st.volatile.shared.v4.f32 [%0], {%1,%2,%3,%4};" :: "r"(a), "f"(x), "f"(y), "f"(z), "f"(w) : "memory"); }
__device__ __forceinline__ void sts32(uint32_t a, float x) { asm volatile("st.shared.f32 [%0], %1;" :: "r"(a), "f"(x) : "memory"); }
__device__ __forceinline__ float2 lds64(uint32_t a) { float2 v; asm volatile("ld.shared.v2.f32 {%0,%1}, [%2];" : "=f"(v.x), "=f"(v.y) : "r"(a) : "memory"); return v; }
__device__ __forceinline__ float lds32(uint32_t a) { float v; asm volatile("ld.shared.f32 %0, [%1];" : "=f"(v) : "r"(a) : "memory"); return v; }
__device__ __forceinline__ float4 lds128(uint32_t a) { float4 v; asm volatile("ld.shared.v4.f32 {%0,%1,%2,%3}, [%4];" : "=f"(v.x), "=f"(v.y), "=f"(v.z), "=f"(v.w) : "r"(a) : "memory"); return v; }
__device__ __forceinline__ float2 sum8(uint32_t a) {
    float2 v[8];
#pragma unroll
    for (int i = 0; i < 8; i++) v[i] = lds64(a + i * SCR);
    return make_float2(((v[0].x + v[1].x) + (v[2].x + v[3].x)) + ((v[4].x + v[5].x) + (v[6].x + v[7].x)),
                       ((v[0].y + v[1].y) + (v[2].y + v[3].y)) + ((v[4].y + v[5].y) + (v[6].y + v[7].y)));
}
template <int STRIDE> __device__ __forceinline__ float4 sum8x4(uint32_t a) {
    float4 v[8];
#pragma unroll
    for (int i = 0; i < 8; i++) v[i] = lds128(a + i * STRIDE);
    return make_float4(((v[0].x + v[1].x) + (v[2].x + v[3].x)) + ((v[4].x + v[5].x) + (v[6].x + v[7].x)), ((v[0].y + v[1].y) + (v[2].y + v[3].y)) + ((v[4].y + v[5].y) + (v[6].y + v[7].y)),
                       ((v[0].z + v[1].z) + (v[2].z + v[3].z)) + ((v[4].z + v[5].z) + (v[6].z + v[7].z)), ((v[0].w + v[1].w) + (v[2].w + v[3].w)) + ((v[4].w + v[5].w) + (v[6].w + v[7].w)));
}
__device__ __forceinline__ float rcp(float x) { float y; asm("rcp.approx.ftz.f32 %0, %1;" : "=f"(y) : "f"(x)); return y; }
__device__ __forceinline__ float sigmoid_f(float x) { return rcp(1.0f + ex2(x * -LOG2E)); }
__device__ __forceinline__ uint32_t silu2(uint32_t c) { const float a = blo(c), b = bhi(c); return pack2(a * sigmoid_f(a), b * sigmoid_f(b)); }
__device__ __forceinline__ void ln_consts(float mean, float var, uint32_t& mu2, float& rs) {
    mu2 = pack2(mean, mean);
    float sd; asm("sqrt.approx.ftz.f32 %0, %1;" : "=f"(sd) : "f"(rbf(rbf(var) + 1e-5f)));
    rs = rcp(rbf(sd));
}
__device__ __forceinline__ uint32_t ln_norm(uint32_t x2, uint32_t mu2, float rs) { const uint32_t d = sub2(x2, mu2); return pack2(blo(d) * rs, bhi(d) * rs); }

__global__ void __launch_bounds__(NALL, 1) fused_kernel(const __nv_bfloat16* const px, const __nv_bfloat16* const pc, const __nv_bfloat16* const pk, const __nv_bfloat16* const pwm,
                                                        const __nv_bfloat16* const pwq, char* const X, const __grid_constant__ Params P) {
    extern __shared__ __align__(1024) unsigned char smem[];
    const uint32_t sb = smem_u32(smem);
    const int tid = threadIdx.x, w = tid >> 5, lane = tid & 31, g = lane >> 2, t = lane & 3;
    const int cta = blockIdx.x, head = cta >> 2, bat = (cta & 3) * 2 + (w >> 2);
    const uint32_t s0 = sb + w * UNIT, s2 = s0 + 4 * REG;
    const uint32_t bar0 = sb + SM_BAR + w * 64;
    const uint32_t barC = bar0 + 32;
    const uint32_t scr = sb + SM_SCR, myscr = scr + w * SCR;
    pf_if((const char*)pwm + ((cta * 4 + (lane >> 3)) * (6 * DM * 2) + w * 1024 + (lane & 7) * 128), w, 5);
    pf_if((const char*)pk + (unsigned)(((((cta & 3) * 2 + (w & 1)) * NH + head) * SK + (SK - WIN - 48) + tile_key(2) + (w >> 1) * 16) * (DH * 2) + lane * 128), w - 6, PFK);
    const int rid = !(cta & 1) ? cta >> 1 : (cta >> 2) + (cta & 2 ? 64 : 96);
    const unsigned t_start = now_ns();
    uint64_t pol;
    asm volatile("createpolicy.fractional.L2::evict_first.b64 %0, 1.0;" : "=l"(pol));
    auto go_first = [&](uint32_t wbar, uint32_t par) {
        for (int n = 0;; n++) {
            if (__all_sync(~0u, mbar_test(wbar, par))) return false;
            if (__all_sync(~0u, mbar_test(sb + SM_BG, 0))) return true;
            if (n > SPIN_MAX * 4) __trap();
            nap(20);
        }
    };
    if (w == 9) {
        const uint32_t sl = sb + SM_PR + lane * 16;
        char* const pl = X + blk(X_PRB, cta >> 1, lane & 1) + (lane >> 1) * 256 + (cta & 1) * 128;
        {
            char* const ps = X + X_PRB + (cta >> 1) * 8192 + g * 256 + (cta & 1) * 128 + t * 16;
            sts32u(sl, 0);
#pragma unroll
            for (int i = 0; i < 4; i++) stg_rlx128(ps + i * 2048, make_uint4(1, 1, 1, 1));
            __syncwarp();
        }
        unsigned v; asm volatile("atom.relaxed.gpu.global.add.u32 %0, [%1], 1;" : "=r"(v) : "l"(pl) : "memory");
        unsigned tag = ldg_rlx32(X + X_EPOCH);
        if (lane == 0) pf_bulk(pwq + (size_t)cta * QN * 1024, QN * 2048);
        if (lane == 0) sts32u(sb + SM_AN, t_start + ANCH0);
        if (lane < 8) sts32u(sb + SM_BAR + lane * 64 + 56, 0);
        unsigned side;
        {
            int d, n = 0;
#pragma unroll 1
            for (int r = 0; r < 4; r++) {
                if (v == SENT) __trap();
                asm volatile("cp.async.cg.shared.global [%0], [%1], 16;" :: "r"(sl), "l"(pl) : "memory");
                unsigned m;
                do {
                    m = __ballot_sync(~0u, lds32u(sl));
                    d = __popc(m & 0xAAAAAAAAu) - __popc(m & 0x55555555u);
                    if (++n > SPIN_MAX) __trap();
                } while (abs(d) < 6 && m != ~0u);
                if (abs(d) >= 6) break;
                asm volatile("cp.async.wait_all;" ::: "memory");
                sts32u(sl, 0);
                asm volatile("atom.relaxed.gpu.global.add.u32 %0, [%1], 1;" : "=r"(v) : "l"(pl) : "memory");
            }
            side = d > 0;
            tag++;
            if (lane == 0) { sts32u(sb + SM_SIDE, side); sts32u(sb + SM_TAG, tag); }
            bar_arrive<B_SIDE, NTHR>();
        }
        asm volatile("cp.async.wait_all;" ::: "memory");
        while (now_ns() - t_start < PACE0) nap(200);
        for (int n = 0; n < SPIN_MAX; n++) {
            const uint32_t wb = sb + SM_BAR + (lane & 7) * 64;
            const unsigned seen = lds32u(wb + 56), u = seen + ((lane >> 3) & 1), t1 = now_ns();
            const unsigned more = seen && mbar_test(wb + (u < 6 ? u : (~u & 2) + (u & 1)) * 8, u < 6 ? 0 : ((u - 2) >> 2) & 1);
            const unsigned lo = __reduce_min_sync(~0u, seen), sum = __reduce_add_sync(~0u, lane < 8 ? seen + more : lane < 16 ? more : 0);
            if (lo == 30) break;
            if (lo && lane < 2) stg_rlx64(X + X_LAG + (cta >> 5) * 8192 + lane * 4096 + (cta & 31) * 128, t1 - sum * TAU, tag);
            uint2 a = make_uint2(0, 0);
            if (cta == 0) {
                uint2 u[4];
#pragma unroll
                for (int i = 0; i < 4; i++) u[i] = ldg_rlx64(X + blk(X_LAG, i, side) + lane * 128);
                const int s = __reduce_add_sync(~0u, (int)(u[0].x + u[1].x + u[2].x + u[3].x - 4 * t_start));
                if (__all_sync(~0u, (u[0].y == tag) & (u[1].y == tag) & (u[2].y == tag) & (u[3].y == tag)) && lane < 2) {
                    a = make_uint2(t_start + s / NCTA, tag);
                    stg_rlx64(X + X_ANC + lane * 4096, a.x, tag);
                }
            } else if (lane == 0) a = ldg_rlx64(X + blk(X_ANC, 0, side));
            if (lane == 0 && a.y == tag) sts32u(sb + SM_AN, a.x - LEAD);
            __syncwarp();
            nap(PNAP);
        }
        {
            bar_sync<B_ML, NTHR>();
            const float2 ml = lds64(sb + SM_ML + (lane & 7) * 8);
            float M = fmaxf(ml.x, __shfl_xor_sync(~0u, ml.x, 1)); M = fmaxf(M, __shfl_xor_sync(~0u, M, 2));
            const float e = ex2((ml.x - M) * LOG2E);
            float L = e * ml.y; L += __shfl_xor_sync(~0u, L, 1); L += __shfl_xor_sync(~0u, L, 2);
            if (lane < 8) sts32(sb + SM_ML + 64 + lane * 4, e * rcp(L));
        }
        bar_arrive<B_RDY, NALL>();
        bar_sync<B_STG, 64>();
        {
            const char* const pp = pin(X + blk(X_PART, cta, side) + lane * 16);
            char* const xo = pin(X + (lane >> 4) * 16384 + blk(X_X1, (cta >> 3) & 1, lane >> 3) + (cta & 7) * 512 + (cta >> 4) * 64 + (lane & 7) * 8);
            const float4 gx = lds128(scr + SC_RX + (lane & 7) * 16);
            const unsigned t0 = lds32u(sb + SM_AN) + 256 * TAU + RT0 + (cta & 7) * (TAU / 8);
            while ((int)(now_ns() - t0) < 0) nap(20);
            uint4 v[8]; int n = 0;
            float a[4];
#pragma unroll
            for (int j = 0; j < 8; j++) v[j] = ldg_b128(pp + j * 512);
            while (true) {
#define RSUM(f) (((__uint_as_float(v[0].f) + __uint_as_float(v[1].f)) + (__uint_as_float(v[2].f) + __uint_as_float(v[3].f))) + ((__uint_as_float(v[4].f) + __uint_as_float(v[5].f)) + (__uint_as_float(v[6].f) + __uint_as_float(v[7].f))))
                const bool ok = __all_sync(~0u, max(max(max(v[0].x, v[1].x), max(v[2].x, v[3].x)), max(max(v[4].x, v[5].x), max(v[6].x, v[7].x))) != SENT);
                a[0] = RSUM(x); a[1] = RSUM(y); a[2] = RSUM(z); a[3] = RSUM(w);
                asm volatile("" : "+f"(a[0]), "+f"(a[1]), "+f"(a[2]), "+f"(a[3]));
                if (ok) break;
#pragma unroll
                for (int j = 0; j < 8; j++) if (v[j].x == SENT) v[j] = ldg_b128(pp + j * 512);
                if (++n > SPIN_MAX) __trap();
            }
#pragma unroll
            for (int i = 0; i < 4; i++) a[i] += __shfl_xor_sync(~0u, a[i], 8);
#pragma unroll
            for (int i = 0; i < 4; i++) a[i] += __shfl_xor_sync(~0u, a[i], 16);
            stg_rlx64(xo, add2(__float_as_uint(gx.z), mul2(__float_as_uint(gx.x), pack2(a[0], a[1]))), add2(__float_as_uint(gx.w), mul2(__float_as_uint(gx.y), pack2(a[2], a[3]))));
        }
        if (rid >= DN0) {
            const unsigned c1 = clock();
            const int f = rid - DN0;
            const char* const rp = X + (rid & (XC - 1)) * 16384 + blk(X_X1, f >> 4, side) + (rowoff(g, f * 16 + t * 4) & 4092);
            unsigned r[4]; int n = 0;
            spin(c1, HD0 - 450);
            do {
#pragma unroll
                for (int i = 0; i < 4; i++) r[i] = ldg_rlx32(rp + i * 16);
                if (++n > SPIN_MAX) __trap();
            } while (max(max(r[0], r[1]), max(r[2], r[3])) == SENT);
            const unsigned sel = (f & 1) ? 0x7632 : 0x5410;
            sts64(sb + SM_MN + 256 + lane * 8, __uint_as_float(__byte_perm(r[0], r[1], sel)), __uint_as_float(__byte_perm(r[2], r[3], sel)));
            __syncwarp();
            spin(c1, HD0);
        }
        if (lane == 0) asm volatile("mbarrier.arrive.shared::cta.b64 _, [%0];" :: "r"(sb + SM_BG) : "memory");
    } else if (w == 8) {
        const int row0 = ((cta & 3) * 2 * NH + head) * SK + (SK - WIN);
        auto kv_unit = [&](int u) {
            const uint32_t b = sb + SM_BAR + (u & 7) * 64 + (u >> 3) * 8;
            mbar_expect(b, UNIT);
            tma_kv(sb + (u >> 3) * REG + (u & 7) * UNIT, (u & 8) ? &P.v : &P.k, row0 + ((u >> 2) & 1) * NH * SK + (u & 3) * 16 + tile_key(u >> 4), b, pol);
        };
        if (elect()) {
            mbar_init(sb + SM_BM, 1);
#pragma unroll
            for (int i = 0; i < 8; i++) mbar_init(sb + SM_BAR + i * 64 + 48, 1);
            asm volatile("fence.mbarrier_init.release.cluster;" ::: "memory");
            mbar_expect(sb + SM_BM, 512 * 16);
            tma2d(sb + 4 * REG, &P.wm, cta * 8, 0, sb + SM_BM); tma2d(sb + 4 * REG + 256 * 16, &P.wm, cta * 8, 256, sb + SM_BM);
#pragma unroll
            for (int i = 0; i < 8; i++) { const uint32_t b = sb + SM_BAR + i * 64 + 48; mbar_expect(b, UNIT); tma2d(sb + 5 * REG + i * UNIT, &P.wq, cta * 32, i * 64, b); }
            mbar_init(sb + SM_BN, 1); mbar_init(sb + SM_BT, 1); mbar_init(sb + SM_BG, 1);
#pragma unroll
            for (int i = 0; i < 48; i++) mbar_init(sb + SM_BAR + (i & 7) * 64 + (i >> 3) * 8, 1);
            asm volatile("fence.mbarrier_init.release.cluster;" ::: "memory");
        }
        __syncwarp();
        bar_arrive<B_INIT, NTHR>();
        {
            uint32_t mine = lane >= NTRK ? 0 : lane < 8 ? sb + SM_BAR + lane * 64 + 48 : sb + SM_BM;
            int next = 0, lim = 32, n = 0;
            while (next < 48) {
                const bool idle = lane < (next < PSW ? PWIN0 : PWIN) && (mine == 0 || mbar_test(mine, 0));
                const unsigned m = __ballot_sync(~0u, idle);
                const int u = next + __popc(m & ((1u << lane) - 1));
                if (idle) {
                    mine = 0;
                    if (u < lim) { kv_unit(u); mine = sb + SM_BAR + (u & 7) * 64 + (u >> 3) * 8; }
                }
                next = min(next + __popc(m), lim);
                if (next == lim) {
                    if (lim == 32) { bar_sync<B_MOD, NTHR>(); } else if (lim == 40) { bar_sync<B_WQ, NTHR>(); }
                    lim += 8;
                }
                if (!m) nap(30);
                if (++n > SPIN_MAX) __trap();
            }
        }
        if (lane < 5) pf_map(&P.wn + lane);
        float m[4][4] = {};
        auto late_mod = [&](uint32_t a, int h) {
            const int lrow = (lane & 7) + ((lane >> 4) << 3), lch = (lane >> 3) & 1;
            const uint32_t a0 = a + lrow * 32 + ((lch ^ ((lrow >> 2) & 1)) << 4);
            const uint32_t c0 = sb + SM_SC + h * 4096 + (lane & 7) * 128 + (((lane >> 3) ^ (lane & 7)) << 4);
#pragma unroll
            for (int j = 0; j < 8; j++) {
                uint32_t c[4], r[4], u[4];
                ldsm(c, (c0 + (j >> 1) * 1024) ^ ((j & 1) << 6)); ldsm_t(r, a0 + j * 1024); ldsm_t(u, a0 + j * 1024 + 512);
                mma(m[(j & 1) * 2], r, c[0], c[1]); mma(m[(j & 1) * 2 + 1], u, c[2], c[3]);
            }
        };
        if (rid < 96) {
#pragma unroll 1
            for (int h = 0; h < 2; h++) {
                if (lane == 0) { mbar_expect(sb + SM_BN, 8192); tma2d(sb + SM_MN, &P.wn, 2 * DM + rid * 16, h * 256, sb + SM_BN); }
                mbar_wait(sb + SM_BN, h);
                late_mod(sb + SM_MN, h);
                asm volatile("" :: "f"(m[0][0]), "f"(m[1][0]), "f"(m[2][0]), "f"(m[3][0]) : "memory");
                __syncwarp();
            }
#pragma unroll
            for (int e = 0; e < 4; e++) {
                float v = rbf((m[0][e] + m[1][e]) + (m[2][e] + m[3][e]));
                if (rid >= 64) v += 1.0f;
                stg_rlx16(X + X_MOD + (rid >> 5) * 8192 + rowoff(2 * t + (e & 1), (rid & 31) * 16 + g + (e >> 1) * 8), pack2(v, 0.f));
            }
        }
        {
            const unsigned side = lds32u(sb + SM_SIDE);
#pragma unroll
            for (int i = 0; i < 8; i++) stg_rlx128(X + blk(X_PART, cta, side) + i * 512 + lane * 16, make_uint4(SENT, SENT, SENT, SENT));
            if (lane == 0) stg_rlx32(X + X_SIDE + cta * 4, side);
        }
        bar_sync<B_Q, NTHR>();
        if (lane == 0) {
            const unsigned tag = lds32u(sb + SM_TAG);
            fence_gpu();
            red_add(X + X_READY, 1);
            int n = 0;
            while ((int)(ldg_acq32(X + X_READY) - tag * NCTA) < 0) { nap(1000); if (++n > SPIN_MAX) __trap(); }
            if (cta == 0) stg_rlx32(X + X_EPOCH, tag);
        }
        __syncwarp();
        {
            stg_rlx128(X + blk(X_Q, head >> 1, 0) + (head & 1) * 2048 + g * 256 + (cta & 3) * 64 + t * 16, make_uint4(0, 0, 0, 0));
            stg_rlx128(X + blk(X_Q, head >> 1, 1) + (head & 1) * 2048 + g * 256 + (cta & 3) * 64 + t * 16, make_uint4(0, 0, 0, 0));
            stg_rlx64(X + blk(X_M1, cta >> 5, lane >> 4) + (cta & 31) * 128 + (lane & 15) * 8, 0, 0);
            const int wt = (cta & 3) * 32 + lane;
            const unsigned mask = __ballot_sync(~0u, blk(X_PART, wt, ldg_rlx32(X + X_SIDE + wt * 4)) & 4096);
            if (lane == 0) sts32u(sb + SM_MASK, mask);
            if (lane < 8) {
                const int rb = cta >> 4, c = ((cta & 15) >> 1) * 64 + (cta & 1) * 4 + (lane >> 1) + (lane & 1) * 8;
                const uint2 ga = ldg_rlx64(X + X_MOD + rowoff(rb, c));
                const unsigned short* const xp = (const unsigned short*)px + rb * DM + c;
                sts128(scr + SC_RX + lane * 16, make_uint4(ga.x, ga.y, xp[0] | (xp[16] << 16), xp[32] | (xp[48] << 16)));
            }
            if (rid < NF1) {
#pragma unroll 1
                for (int i = 0; i < 4; i++) {
                    uint4 v[8];
#pragma unroll
                    for (int j = 0; j < 8; j++) v[j] = ldg_rlx128(X + X_MOD + 8192 + (i * 8 + j) * 512 + lane * 16);
#pragma unroll
                    for (int j = 0; j < 8; j++) sts128(sb + SM_MN + (i * 8 + j) * 512 + lane * 16, v[j]);
                }
            }
        }
        bar_arrive<B_RDY, NALL>();
        bar_arrive<B_STG, 64>();
        for (int n = 0; __any_sync(~0u, lds32u(sb + SM_BAR + (lane & 7) * 64 + 56) < 30); n++) { nap(100); if (n > SPIN_MAX) __trap(); }
        const unsigned t_ref = lds32u(sb + SM_AN) + 256 * TAU + (cta & 7) * (TAU / 8);
        auto until = [&](int x) { while ((int)(now_ns() - t_ref) < x) nap(20); };
        if (lane < 16) mbar_expect(sb + SM_BAR + (lane & 7) * 64 + 32 + (lane & 8), UNIT);
        else if (lane < 20 && rid < NF1) mbar_expect(sb + SM_BAR + (lane & 7) * 64 + 48, 2 * UNIT);
        __syncwarp();
        if (elect()) {
#pragma unroll 1
            for (int i = 0; i < 16; i += 2) {
                until(WO0 + (i & 7) * WOS + (i >> 3) * WOG);
#pragma unroll
                for (int j = i; j < i + 2; j++) tma2d(sb + 4 * REG + j * UNIT, &P.wo, (j & 7) * 64, head * 128 + 64 + (j & 8) * 4, sb + SM_BAR + (j & 7) * 64 + 32 + (j & 8));
            }
            if (rid < NF1) {
#pragma unroll 1
                for (int i = 0; i < 4; i++) {
                    const uint32_t b = sb + SM_BAR + i * 64 + 48;
                    until(W0 + i * WS);
                    tma5d(sb + 2 * REG + i * UNIT, &P.wg, rid * 16, i * 4, b); tma5d(sb + 2 * REG + 16384 + i * UNIT, &P.wu, rid * 16, i * 4, b);
                }
            }
        }
        if (rid >= DN0) {
            bar_sync<B_LAST, NTHR>();
            if (elect()) {
                mbar_expect(sb + SM_BN, 16384); mbar_expect(sb + SM_BT, FF * 32);
                until(WD0);
                tma5d(sb + 2 * REG + 16384, &P.wd, (rid - DN0) * 16, 0, sb + SM_BT);
                tma2d(sb + 2 * REG, &P.wn, 2 * DM + rid * 16, 0, sb + SM_BN); tma2d(sb + 2 * REG + 8192, &P.wn, 2 * DM + rid * 16, 256, sb + SM_BN);
            }
        }
        __syncwarp();
        if (rid >= DN0) {
            mbar_wait(sb + SM_BN, 0);
            late_mod(sb + 2 * REG, 0); late_mod(sb + 2 * REG + 8192, 1);
#pragma unroll
            for (int e = 0; e < 2; e++)
                sts32u(sb + SM_MN + g * 32 + e * 16 + t * 4, movm(pack2((m[0][2 * e] + m[1][2 * e]) + (m[2][2 * e] + m[3][2 * e]), (m[0][2 * e + 1] + m[1][2 * e + 1]) + (m[2][2 * e + 1] + m[3][2 * e + 1]))));
            bar_arrive<B_DN, NTHR>();
        }
    }
    if (w >= 8) {
        if (rid < NF1) {
            const int b = (tid - 256) >> 3, c = tid & 7;
            char* const ho = pin(X + X_HM + (rid >> 4) * 8192 + ((rid >> 1) & 7) * 512 + b * 64 + (rid & 1) * 32 + c * 4);
            const uint32_t pi = pin(scr + SC_F1 + c * 144 + b * 16), si = pin(sb + SM_ST + b * 64);
            bar_sync<B_PRE, NALL>();
            float4 C = sum8x4<UNIT>(sb + REG + c * 144 + b * 16), S = sum8x4<UNIT>(sb + REG + 1152 + c * 144 + b * 16);
            S.x *= -LOG2E; S.y *= -LOG2E; C.x *= LOG2E; C.y *= LOG2E;
            sts128f(sb + SM_PR + lane * 16, C.x, C.y, C.z, C.w); sts128f(sb + SM_PR + lane * 16, S.x, S.y, S.z, S.w);
            sts128(sb + SM_PR + lane * 16, make_uint4(pi, si, (uint32_t)(size_t)ho, (uint32_t)((size_t)ho >> 32)));
            bar_sync<B_FIN, NALL>();
            const float4 s0_ = lds128(si), s1_ = lds128(si + 16), s2_ = lds128(si + 32), s3_ = lds128(si + 48);
            const float4 p = sum8x4<SCR>(pi);
            const float mean = (((s0_.x + s0_.z) + (s1_.x + s1_.z)) + ((s2_.x + s2_.z) + (s3_.x + s3_.z))) * (1.0f / DM);
            const float sq = (((s0_.y + s0_.w) + (s1_.y + s1_.w)) + ((s2_.y + s2_.w) + (s3_.y + s3_.w))) * (1.0f / DM);
            float rs; asm("rsqrt.approx.ftz.f32 %0, %1;" : "=f"(rs) : "f"(fmaxf(sq - mean * mean, 0.f) + 1e-5f));
            const float e0 = rs * (mean * C.x - LOG2E * p.x) + S.x, e1 = rs * (mean * C.y - LOG2E * p.y) + S.y;
            const float u0 = rs * (p.z - mean * C.z) + S.z, u1 = rs * (p.w - mean * C.w) + S.w;
            const unsigned hw = pack2(rcp(1.0f + ex2(e0)) * u0, rcp(1.0f + ex2(e1)) * u1);
            stg_rlx32(ho, hw); stg_rlx32(ho + 4096, hw);
        }
        return;
    }
    const unsigned ce = (lane >> 3) * (DM * 2) + w * 128 + (lane & 7) * 16;
    const uint4 ca = ldg_nc((const char*)pc + ce), cb = ldg_nc((const char*)pc + ce + 4 * DM * 2);
    const uint4 xa = ldg_nc((const char*)px + w * (DM * 2) + lane * 16), xb = ldg_nc((const char*)px + w * (DM * 2) + lane * 16 + 512);
    const uint4 xc = ldg_nc((const char*)px + ce), xd = ldg_nc((const char*)px + ce + 4 * DM * 2);
    if (w >= 4) pf_map(&P.wm + (w & 3));
    char* const qout = X + blk(X_Q, head >> 1, tid >> 7) + (head & 1) * 2048 + ((tid >> 4) & 7) * 256 + (cta & 3) * 64 + (tid & 3) * 16 + ((tid >> 2) & 3) * 4;
    char* const mout = X + blk(X_M1, cta >> 5, w) + (cta & 31) * 128 + lane * 4;
    stg_rlx32(qout, 0);
    if (w < 2) stg_rlx32(mout, 0);
    uint32_t sc[8], xf[8];
    {
        const uint32_t a = (lane >> 3) * 128 + (((lane & 7) ^ (lane >> 3)) << 4), b = (lane & 7) * 128 + (((lane >> 3) ^ (lane & 7)) << 4);
        const uint32_t cs = sb + SM_SC + w * 1024;
        sts128(cs + a, make_uint4(silu2(ca.x), silu2(ca.y), silu2(ca.z), silu2(ca.w)));
        sts128(cs + 512 + (a ^ 64), make_uint4(silu2(cb.x), silu2(cb.y), silu2(cb.z), silu2(cb.w)));
        sts128(myscr + a, xc); sts128(myscr + 512 + (a ^ 64), xd);
        __syncwarp();
        ldsm(*(uint32_t(*)[4])&sc[0], cs + b); ldsm(*(uint32_t(*)[4])&sc[4], cs + (b ^ 64));
        ldsm(*(uint32_t(*)[4])&xf[0], myscr + b); ldsm(*(uint32_t(*)[4])&xf[4], myscr + (b ^ 64));
        __syncwarp();
    }
    {
        float v[16] = {blo(xa.x), bhi(xa.x), blo(xa.y), bhi(xa.y), blo(xa.z), bhi(xa.z), blo(xa.w), bhi(xa.w),
                       blo(xb.x), bhi(xb.x), blo(xb.y), bhi(xb.y), blo(xb.z), bhi(xb.z), blo(xb.w), bhi(xb.w)};
        float s = 0;
#pragma unroll
        for (int i = 0; i < 16; i++) s += v[i];
#pragma unroll
        for (int o = 16; o; o >>= 1) s += __shfl_xor_sync(~0u, s, o);
        s *= (1.0f / DM);
        float q2 = 0;
#pragma unroll
        for (int i = 0; i < 16; i++) q2 += (v[i] - s) * (v[i] - s);
#pragma unroll
        for (int o = 16; o; o >>= 1) q2 += __shfl_xor_sync(~0u, q2, o);
        uint32_t mu2; float rs; ln_consts(s, q2 * (1.0f / DM), mu2, rs);
        if (lane == 0) sts64(sb + SM_ST + w * 8, __uint_as_float(mu2), rs);
    }
    const int lrow = (lane & 7) + ((lane >> 4) << 3), lch = (lane >> 3) & 1;
    const uint32_t off64 = lrow * 64 + ((lch ^ ((lrow >> 1) & 3)) << 4);
    const uint32_t off128 = lrow * 128 + ((lch ^ (lane & 7)) << 4);
    bar_sync<B_INIT, NTHR>();
    mbar_wait(sb + SM_BM, 0);
    {
        float a[4] = {0, 0, 0, 0}, b[4] = {0, 0, 0, 0};
        uint32_t r[4], u[4];
        ldsm_t(r, sb + 4 * REG + (w * 64 + lane) * 16); ldsm_t(u, sb + 4 * REG + (w * 64 + 32 + lane) * 16);
        mma(a, sc[0], 0, sc[1], 0, r[0], r[1]); mma(b, sc[4], 0, sc[5], 0, u[0], u[1]);
        mma(a, sc[2], 0, sc[3], 0, r[2], r[3]); mma(b, sc[6], 0, sc[7], 0, u[2], u[3]);
        sts64(myscr + SC_M + lane * 8, a[0] + b[0], a[1] + b[1]);
    }
    bar_arrive<B_MOD, NTHR>();
    bar_sync<B_ALL, 256>();
    if (w < 2) {
        const float2 m = sum8(scr + SC_M + lane * 8);
        stg_rlx32(mout, ~pack2(m.x, m.y));
    }
    if (tid < 8 * XC) stg_rlx128(X + X_X1 + (cta * 8 * XC + tid) * 16, make_uint4(SENT, SENT, SENT, SENT));
    else if (tid >= 232) stg_rlx128(X + X_HM + (cta * 24 + tid - 232) * 16, make_uint4(SENT, SENT, SENT, SENT));
    {
        const float2 st = lds64(sb + SM_ST + g * 8);
#pragma unroll
        for (int i = 0; i < 8; i++) xf[i] = ln_norm(xf[i], __float_as_uint(st.x), st.y);
    }
    {
        unsigned sv[8], cv[8]; int n = 0;
        bar_sync<B_SIDE, NTHR>();
        const char* const mp = X + blk(X_M1, w >> 2, lds32u(sb + SM_SIDE)) + (w & 3) * 1024 + lane * 4;
        if (lane == 0) while (!ldg_rlx32(mp + 16384 + 7 * 128)) { nap(40); if (++n > SPIN_MAX) __trap(); }
        __syncwarp();
#pragma unroll
        for (int j = 0; j < 8; j++) { sv[j] = ldg_rlx32(mp + j * 128); cv[j] = ldg_rlx32(mp + 16384 + j * 128); }
        while (true) {
            unsigned m = ~0u;
#pragma unroll
            for (int j = 0; j < 8; j++) m = min(m, min(sv[j], cv[j]));
            if (__all_sync(~0u, m)) break;
#pragma unroll
            for (int j = 0; j < 8; j++) { if (!sv[j]) sv[j] = ldg_rlx32(mp + j * 128); if (!cv[j]) cv[j] = ldg_rlx32(mp + 16384 + j * 128); }
            if (++n > SPIN_MAX) __trap();
        }
#pragma unroll
        for (int j = 0; j < 8; j++) xf[j] = add2(mul2(xf[j], add2(~cv[j], ONE2)), ~sv[j]);
        mbar_wait(bar0 + 48, 0);
        float acc[4][4] = {};
#pragma unroll
        for (int j = 0; j < 4; j++) {
            uint32_t r[4], u[4];
            ldsm_t(r, s2 + REG + j * 1024 + off64); ldsm_t(u, s2 + REG + j * 1024 + (off64 ^ 32));
            mma(acc[0], xf[2 * j], 0, xf[2 * j + 1], 0, r[0], r[2]); mma(acc[1], xf[2 * j], 0, xf[2 * j + 1], 0, r[1], r[3]);
            mma(acc[2], xf[2 * j], 0, xf[2 * j + 1], 0, u[0], u[2]); mma(acc[3], xf[2 * j], 0, xf[2 * j + 1], 0, u[1], u[3]);
        }
#pragma unroll
        for (int n2 = 0; n2 < 4; n2++) sts64(myscr + SC_Q + g * 160 + n2 * 32 + t * 8, acc[n2][0], acc[n2][1]);
    }
    bar_arrive<B_WQ, NTHR>();
    bar_sync<B_ALL, 256>();
    {
        const float2 s = sum8(scr + SC_Q + ((tid >> 4) & 7) * 160 + (tid & 15) * 8);
        stg_rlx32(qout, ~pack2(s.x, s.y));
    }
    uint32_t q[16];
    {
        int n = 0;
        const char* const qp = X + blk(X_Q, head >> 1, lds32u(sb + SM_SIDE)) + (head & 1) * 2048 + bat * 256 + t * 16;
        uint4 v[4];
#pragma unroll
        for (int j = 0; j < 4; j++) v[j] = ldg_rlx128(qp + j * 64);
        while (true) {
            bool bad[4];
#pragma unroll
            for (int j = 0; j < 4; j++) bad[j] = !min(min(v[j].x, v[j].y), min(v[j].z, v[j].w));
            if (!__any_sync(~0u, bad[0] | bad[1] | bad[2] | bad[3])) break;
#pragma unroll
            for (int j = 0; j < 4; j++) if (bad[j]) v[j] = ldg_rlx128(qp + j * 64);
            if (++n > SPIN_MAX) __trap();
        }
#pragma unroll
        for (int j = 0; j < 4; j++) { q[4 * j] = ~v[j].x; q[4 * j + 1] = ~v[j].y; q[4 * j + 2] = ~v[j].z; q[4 * j + 3] = ~v[j].w; }
    }
    bar_arrive<B_Q, NTHR>();

    float o[2][4] = {};
    float mrun = -3.0e38f, lrun = 0.f;
    uint32_t wa[16][4], pb[2];
#pragma unroll
    for (int i = 0; i < 16; i++) wa[i][0] = wa[i][1] = wa[i][2] = wa[i][3] = 0;
    const uint32_t offk = (lane & 15) * 128 + (((lane >> 4) ^ (lane & 7)) << 4);
    float p0, p1;
    auto scores = [&](uint32_t a0) {
        uint32_t kf[8][4];
#pragma unroll
        for (int j = 0; j < 8; j++) ldsm(kf[j], ((a0 + offk) ^ ((j & 3) << 5)) + (j >> 2) * 2048);
        float sa[4] = {0, 0, 0, 0}, sb2[4] = {0, 0, 0, 0};
#pragma unroll
        for (int j = 0; j < 8; j += 2) { mma(sa, kf[j], q[2 * j], q[2 * j + 1]); mma(sb2, kf[j + 1], q[2 * j + 2], q[2 * j + 3]); }
        uint32_t u = pack2(sa[0] + sb2[0], sa[2] + sb2[2]);
        u = pack2(blo(u) * SCALE, bhi(u) * SCALE);
        const float z0 = blo(u), z1 = bhi(u);
        float mx = fmaxf(z0, z1);
        mx = fmaxf(mx, __shfl_xor_sync(~0u, mx, 4)); mx = fmaxf(mx, __shfl_xor_sync(~0u, mx, 8)); mx = fmaxf(mx, __shfl_xor_sync(~0u, mx, 16));
        mx = fmaxf(mx, mrun);
        const float f = ex2((mrun - mx) * LOG2E);
        p0 = ex2((z0 - mx) * LOG2E); p1 = ex2((z1 - mx) * LOG2E);
        mrun = mx; lrun = lrun * f + (p0 + p1);
#pragma unroll
        for (int j = 0; j < 4; j++) { o[0][j] *= f; o[1][j] *= f; }
    };
    const int kvrow = (bat * NH + head) * SK + (SK - WIN) + (w & 3) * 16;
    const int wofs = (w * 8 + (cta & 7)) * TAU / 8;
    auto request = [&](int u) {
        sts32u(bar0 + 56, u - 1);
        while ((int)(now_ns() - lds32u(sb + SM_AN) - u * 8 * TAU - wofs) < 0) nap(20);
        const int sl = (~u & 2) + (u & 1);
        mbar_expect(bar0 + sl * 8, UNIT); tma_kv(s0 + sl * REG, &P.k + (u & 1), kvrow + tile_key(u >> 1), bar0 + sl * 8, pol);
    };
#pragma unroll 1
    for (int it = 0; it < NT - 1; it++) {
        const int si = it < 3 ? it : (it + 1) & 1;
        const uint32_t bar = bar0 + si * 16, a0 = s0 + si * 2 * REG;
        const uint32_t par = it < 3 ? 0 : ((it - 1) >> 1) & 1;
        const bool refill = lane == 0 && it >= 2;
        mbar_wait(bar, par);
        if (refill) {
            request(2 * it + 2);
            const int e = it - WOA_ISSUE;
            if (e == 0) mbar_expect(barC, 2 * UNIT);
            if (e == 0 || e == WO_GAP) tma2d(s2 + (e ? REG : 0), &P.wo, w * 64, head * 128 + (e ? 32 : 0), barC);
        }
        __syncwarp();
        if (it == WOA_READ) {
            mbar_wait(barC, 1);
#pragma unroll
            for (int j = 0; j < 16; j++) ldsm_t(wa[j], s2 + (j >> 3) * REG + ((j >> 2) & 1) * 2048 + (off128 ^ ((j & 3) << 5)));
        }
        scores(a0);
        pb[0] = movm(pack2(p0, p0)); pb[1] = movm(pack2(p1, p1));
        mbar_wait(bar + 8, par);
        if (refill) request(2 * it + 3);
        __syncwarp();
        uint32_t vf[8][4];
#pragma unroll
        for (int j = 0; j < 8; j++) ldsm_t(vf[j], ((a0 + off128) ^ ((j & 3) << 5)) + (j >> 2) * 2048 + REG);
#pragma unroll
        for (int j = 0; j < 8; j++) { const bool on = (g >> 1) == (j >> 1); mma(o[j & 1], vf[j], on ? pb[0] : 0, on ? pb[1] : 0); }
    }
    {
        uint32_t wb[16][4];
        mbar_wait(bar0, 1);
        if (rid >= DN0) bar_arrive<B_LAST, NTHR>();
        scores(s0);
        lrun += __shfl_xor_sync(~0u, lrun, 4); lrun += __shfl_xor_sync(~0u, lrun, 8); lrun += __shfl_xor_sync(~0u, lrun, 16);
        if (lane == 0) sts64(sb + SM_ML + w * 8, mrun, lrun);
        bar_arrive<B_ML, NTHR>();
        pb[0] = movm(pack2(p0, p0)); pb[1] = movm(pack2(p1, p1));
        const uint32_t va = pin(s0 + REG + off128);
        auto load_wb = [&](int j) { ldsm_t(wb[j], (va ^ ((j & 3) << 5)) + (3 + (j >> 3)) * REG + ((j >> 2) & 1) * 2048); };
        const uint32_t ho = pin(s0 + w * 16 + ((lane & 7) >> 1) * 64 + ((lane >> 3) & 1) * 32 + (lane & 1) * 16), oa = pin(sb + (lane & 7) * (UNIT + 16) + (lane >> 3) * 16);
        const uint32_t rd = pin((t >> 1) * 16 + w * 2 + (g >> 2));
        char* const pp = pin(X + X_PART + ((cta & 3) * 32 + rd) * 8192 + head * 128 + (g & 3) * 32 + (t & 1) * 16);
        const uint32_t ln = pin(lane), wbar = pin(barC + 8);
        mbar_wait(bar0 + 8, 1);
        {
            uint32_t vf[8][4];
            float o2[2][4] = {};
#pragma unroll
            for (int j = 0; j < 8; j++) ldsm_t(vf[j], (va ^ ((j & 3) << 5)) + (j >> 2) * 2048);
#pragma unroll
            for (int j = 0; j < 8; j++) { const bool on = (ln >> 3) == (j >> 1); mma((j & 2) ? o2[j & 1] : o[j & 1], vf[j], on ? pb[0] : 0, on ? pb[1] : 0); }
            asm volatile("stmatrix.sync.aligned.m8n8.x2.trans.shared.b16 [%0], {%1,%2};" :: "r"(ho), "r"(pack2(o[0][0] + o2[0][0], o[0][2] + o2[0][2])), "r"(pack2(o[1][0] + o2[1][0], o[1][2] + o2[1][2])) : "memory");
        }
        bar_sync<B_RDY, NALL>();
        float y[4][4] = {};
        uint32_t ob[4][4];
#pragma unroll
        for (int i2 = 0; i2 < 4; i2++) ldsm(ob[i2], oa + i2 * 64);
        const float2 f = lds64(sb + SM_ML + 64 + (ln & 3) * 8);
        const unsigned half = (lds32u(sb + SM_MASK) >> rd & 1) * 4096;
#pragma unroll
        for (int j = 0; j < 8; j++) {
            if (j == WK) {
                if (!mbar_test(wbar - 8, 0)) mbar_wait(wbar - 8, 0);
#pragma unroll
                for (int k = 0; k < 8; k++) load_wb(k);
            }
            if (j == WJ) {
                if (!mbar_test(wbar, 1)) mbar_wait(wbar, 1);
#pragma unroll
                for (int k = 8; k < 16; k++) load_wb(k);
            }
#pragma unroll
            for (int i = 0; i < 4; i++) mmav(y[i], j < 4 ? wa[j * 4 + i] : wb[(j - 4) * 4 + i], ob[j >> 1][2 * (j & 1)], ob[j >> 1][2 * (j & 1) + 1]);
        }
        uint32_t r[4];
#pragma unroll
        for (int i = 0; i < 4; i++) {
            const float lo = f.x * y[i][0] + f.y * y[i][1], hi = f.x * y[i][2] + f.y * y[i][3];
            r[i] = __float_as_uint(((ln & 1) ? hi : lo) + __shfl_xor_sync(~0u, (ln & 1) ? lo : hi, 1));
        }
        asm("min.u32 %0, %0, 0xFFFFFFFE;" : "+r"(r[0]));
        stg_b128(pp + half, make_uint4(r[0], r[1], r[2], r[3]));
    }
    const unsigned side = lds32u(sb + SM_SIDE);
    const char* const x1p = X + (rid & (XC - 1)) * 16384;
    if (rid < NF1) {
        uint32_t wg[4][4], wu[4][4];
        const char* const xp = pin(x1p + blk(X_X1, w >> 2, side) + (w & 3) * 1024 + lane * 16);
        float4 c1[2], sv[2];
#pragma unroll
        for (int h = 0; h < 2; h++) { sv[h] = lds128(sb + SM_MN + (w * 2 + h) * 512 + lane * 16); c1[h] = lds128(sb + SM_MN + 8192 + (w * 2 + h) * 512 + lane * 16); }
        const uint32_t po = pin(myscr + SC_F1 + g * 144 + t * 32), so = pin(t == (g >> 1) ? sb + SM_ST + g * 64 + w * 8 : myscr + 1792 + lane * 8), odd = pin(g & 1);
        const uint32_t wbar = sb + SM_BAR + (w >> 1) * 64 + 48;
        uint4 x0, x1;
        const bool early = go_first(wbar, 1);
        if (early) { spin(clock(), (7 - w) * XDW); x0 = ldg_rlx2x64(xp); x1 = ldg_rlx2x64(xp + 512); mbar_wait(wbar, 1); }
#pragma unroll
        for (int j = 0; j < 4; j++) {
            const uint32_t a = sb + 2 * REG + w * 2048 + (((lane & 7) >> 1) + (lane & 1) * 4 + j * 8 + (lane >> 4) * 32) * 32 + ((lch ^ (lane & 1)) << 4);
            ldsm_t(wg[j], a); ldsm_t(wu[j], a + 16384);
        }
        {
            float cg[4] = {}, cu[4] = {}, sg[4] = {}, su[4] = {};
#pragma unroll
            for (int j = 0; j < 4; j++) {
                const float4 a = c1[j & 1], b = sv[j & 1];
                const uint32_t a0 = __float_as_uint(j >> 1 ? a.z : a.x), a1 = __float_as_uint(j >> 1 ? a.w : a.y), b0 = __float_as_uint(j >> 1 ? b.z : b.x), b1 = __float_as_uint(j >> 1 ? b.w : b.y);
                mma(cg, wg[j], a0, a1); mma(cu, wu[j], a0, a1); mma(sg, wg[j], b0, b1); mma(su, wu[j], b0, b1);
            }
            const uint32_t d = s0 + REG + g * 144 + t * 32;
            sts128f(d, cg[0], cg[2], cu[0], cu[2]); sts128f(d + 16, cg[1], cg[3], cu[1], cu[3]);
            sts128f(d + 1152, sg[0], sg[2], su[0], su[2]); sts128f(d + 1168, sg[1], sg[3], su[1], su[3]);
            bar_arrive<B_PRE, NALL>();
        }
        if (!early) { mbar_wait(sb + SM_BG, 0); spin(clock(), (7 - w) * XDW); x0 = ldg_rlx2x64(xp); x1 = ldg_rlx2x64(xp + 512); }
        int n = 0;
        while (true) {
            const bool b0 = max(x0.x, x0.z) == SENT, b1 = max(x1.x, x1.z) == SENT;
            if (!__any_sync(~0u, b0 | b1)) break;
            if (b0) x0 = ldg_rlx2x64(xp);
            if (b1) x1 = ldg_rlx2x64(xp + 512);
            if (++n > SPIN_MAX) __trap();
        }
        float q0[4] = {}, q1[4] = {}, ag[2][4] = {}, au[2][4] = {};
        {
            mma(q0, x0.x, ONE2, x0.y, ONE2, x0.x, x0.y); mma(q1, x0.z, ONE2, x0.w, ONE2, x0.z, x0.w);
            mma(q0, x1.x, ONE2, x1.y, ONE2, x1.x, x1.y); mma(q1, x1.z, ONE2, x1.w, ONE2, x1.z, x1.w);
#pragma unroll
            for (int j = 0; j < 4; j++) {
                const uint4 xv = (j & 1) ? x1 : x0; const float4 a = c1[j & 1];
                const uint32_t h0 = mul2(j >> 1 ? xv.z : xv.x, __float_as_uint(j >> 1 ? a.z : a.x)), h1 = mul2(j >> 1 ? xv.w : xv.y, __float_as_uint(j >> 1 ? a.w : a.y));
                mma(ag[j & 1], wg[j], h0, h1); mma(au[j & 1], wu[j], h0, h1);
            }
        }
        sts64(so, odd ? q0[3] + q1[3] : q0[2] + q1[2], odd ? q0[1] + q1[1] : q0[0] + q1[0]);
        sts128f(po, ag[0][0] + ag[1][0], ag[0][2] + ag[1][2], au[0][0] + au[1][0], au[0][2] + au[1][2]);
        sts128f(po + 16, ag[0][1] + ag[1][1], ag[0][3] + ag[1][3], au[0][1] + au[1][1], au[0][3] + au[1][3]);
        bar_arrive<B_FIN, NALL>();
    } else if (rid >= DN0) {
        const int f = rid - DN0;
        uint32_t wd[12][4];
        const char* const hp0 = pin(X + blk(X_HM, 0, side) + w * 512 + lane * 16);
        const char* const hp1 = pin(X + blk(X_HM, 1, side) + w * 512 + lane * 16);
        auto hm = [&](int j) { return ldg_rlx128((j & 1 ? hp1 : hp0) + (j >> 1) * 16384); };
        __nv_bfloat16* const op = pin(P.out + ((tid >> 4) & 7) * DM + f * 16 + (tid & 15));
        const uint32_t po = pin(myscr + SC_DN + t * 160 + g * 16), pi = pin(scr + SC_DN + (w & 3) * 160 + (tid & 7) * 16 + (tid & 8) + ((tid >> 4) & 1) * 4), gi = pin(sb + SM_MN + tid * 2), first = pin(w < 4);
        uint4 hv[6]; int n = 0;
        auto first_poll = [&]() {
            spin(clock(), w * HDW);
#pragma unroll
            for (int j = 0; j < 6; j++) hv[j] = (j < 5 || w < 3) ? hm(j) : make_uint4(0, 0, 0, 0);
        };
        const bool early = go_first(sb + SM_BT, 0);
        if (early) { first_poll(); mbar_wait(sb + SM_BT, 0); }
#pragma unroll
        for (int j = 0; j < 12; j++)
            if (j < 10 || w < 3) ldsm_t(wd[j], sb + 2 * REG + 16384 + (w + (j >> 1) * 8) * 1024 + (j & 1) * 512 + (((lane >> 1) & 1) + (lane & 1) * 2 + (lane & 4) + (lane >> 4) * 8) * 32 + ((lch ^ ((lane >> 2) & 1)) << 4));
            else wd[j][0] = wd[j][1] = wd[j][2] = wd[j][3] = 0;
        if (!early) { mbar_wait(sb + SM_BG, 0); first_poll(); }
        while (true) {
            unsigned m[6];
#pragma unroll
            for (int j = 0; j < 6; j++) m[j] = max(max(hv[j].x, hv[j].y), max(hv[j].z, hv[j].w));
            if (__all_sync(~0u, max(max(max(m[0], m[1]), m[2]), max(max(m[3], m[4]), m[5])) != SENT)) break;
#pragma unroll
            for (int j = 0; j < 6; j++) if (m[j] == SENT) hv[j] = hm(j);
            if (++n > SPIN_MAX) __trap();
        }
        float d[4][4] = {};
#pragma unroll
        for (int j = 0; j < 6; j++) { mma(d[(2 * j) & 3], wd[2 * j], hv[j].x, hv[j].y); mma(d[(2 * j + 1) & 3], wd[2 * j + 1], hv[j].z, hv[j].w); }
        sts128f(po, (d[0][0] + d[1][0]) + (d[2][0] + d[3][0]), (d[0][1] + d[1][1]) + (d[2][1] + d[3][1]), (d[0][2] + d[1][2]) + (d[2][2] + d[3][2]), (d[0][3] + d[1][3]) + (d[2][3] + d[3][3]));
        bar_sync<B_DN, NTHR>();
        if (first) {
            float v[8];
#pragma unroll
            for (int i = 0; i < 8; i++) v[i] = lds32(pi + i * SCR);
            unsigned gw, res;
            asm volatile("ld.shared.u16 %0, [%1];" : "=r"(gw) : "r"(gi) : "memory"); asm volatile("ld.shared.u16 %0, [%1];" : "=r"(res) : "r"(gi + 256) : "memory");
            asm volatile("st.global.u16 [%0], %1;" :: "l"(op), "h"((unsigned short)add2(res, mul2(gw, pack2(((v[0] + v[1]) + (v[2] + v[3])) + ((v[4] + v[5]) + (v[6] + v[7])), 0.f)))) : "memory");
        }
    }
}

typedef CUresult (*EncodeFn)(CUtensorMap*, CUtensorMapDataType, cuuint32_t, void*, const cuuint64_t*, const cuuint64_t*, const cuuint32_t*,
                             const cuuint32_t*, CUtensorMapInterleave, CUtensorMapSwizzle, CUtensorMapL2promotion, CUtensorMapFloatOOBfill);

void make2d(EncodeFn enc, CUtensorMap* m, const void* p, int rows, int cols, int brows, int bcols, CUtensorMapSwizzle sw) {
    cuuint64_t dims[2] = {(cuuint64_t)cols, (cuuint64_t)rows}, strides[1] = {(cuuint64_t)cols * 2};
    cuuint32_t box[2] = {(cuuint32_t)bcols, (cuuint32_t)brows}, es[2] = {1, 1};
    enc(m, CU_TENSOR_MAP_DATA_TYPE_BFLOAT16, 2, (void*)p, dims, strides, box, es, CU_TENSOR_MAP_INTERLEAVE_NONE, sw,
        CU_TENSOR_MAP_L2_PROMOTION_L2_128B, CU_TENSOR_MAP_FLOAT_OOB_FILL_NONE);
}
void make5d(EncodeFn enc, CUtensorMap* m, const void* p, int cols, const unsigned (&n)[4], const unsigned (&s)[4], unsigned nb) {
    const cuuint64_t rs = (cuuint64_t)cols * 2;
    cuuint64_t dims[5] = {(cuuint64_t)cols, n[0], n[1], n[2], n[3]}, strides[4] = {rs * s[0], rs * s[1], rs * s[2], rs * s[3]};
    cuuint32_t box[5] = {16, n[0], n[1], n[2], nb}, es[5] = {1, 1, 1, 1, 1};
    enc(m, CU_TENSOR_MAP_DATA_TYPE_BFLOAT16, 5, (void*)p, dims, strides, box, es, CU_TENSOR_MAP_INTERLEAVE_NONE, CU_TENSOR_MAP_SWIZZLE_32B,
        CU_TENSOR_MAP_L2_PROMOTION_L2_128B, CU_TENSOR_MAP_FLOAT_OOB_FILL_NONE);
}
void makekv(EncodeFn enc, CUtensorMap* m, const void* p) {
    cuuint64_t dims[3] = {64, (cuuint64_t)NB * NH * SK, 2}, strides[2] = {256, 128};
    cuuint32_t box[3] = {64, 16, 2}, es[3] = {1, 1, 1};
    enc(m, CU_TENSOR_MAP_DATA_TYPE_BFLOAT16, 3, (void*)p, dims, strides, box, es, CU_TENSOR_MAP_INTERLEAVE_NONE, CU_TENSOR_MAP_SWIZZLE_128B,
        CU_TENSOR_MAP_L2_PROMOTION_NONE, CU_TENSOR_MAP_FLOAT_OOB_FILL_NONE);
}

}

extern "C" void kernel_launch(void* const* d_in, const int* in_sizes, int n_in, void* d_out, int out_size) {
    (void)in_sizes; (void)n_in; (void)out_size;
    static EncodeFn enc = nullptr;
    static void* raw = nullptr;
    if (!enc) {
        void* fn = nullptr; cudaDriverEntryPointQueryResult qr;
        cudaGetDriverEntryPoint("cuTensorMapEncodeTiled", &fn, cudaEnableDefault, &qr);
        enc = (EncodeFn)fn;
        cudaFuncSetAttribute(fused_kernel, cudaFuncAttributeMaxDynamicSharedMemorySize, SM_TOTAL);
        cudaGetSymbolAddress(&raw, g_raw);
    }
    Params P;
    makekv(enc, &P.k, d_in[1]);
    makekv(enc, &P.v, d_in[2]);
    make2d(enc, &P.wq, d_in[3], DM, NH * DH, 64, 32, CU_TENSOR_MAP_SWIZZLE_64B);
    make2d(enc, &P.wo, d_in[4], NH * DH, DM, 32, 64, CU_TENSOR_MAP_SWIZZLE_128B);
    make2d(enc, &P.wm, d_in[10], DM, 6 * DM, 256, 8, CU_TENSOR_MAP_SWIZZLE_NONE);
    make2d(enc, &P.wn, d_in[10], DM, 6 * DM, 256, 16, CU_TENSOR_MAP_SWIZZLE_32B);
    make5d(enc, &P.wg, d_in[6], FF, {4, 2, 4, 16}, {1, 16, 4, 32}, 4);
    make5d(enc, &P.wu, d_in[7], FF, {4, 2, 4, 16}, {1, 16, 4, 32}, 4);
    make5d(enc, &P.wd, d_in[8], DM, {8, 4, 1, 43}, {4, 1, 1, 32}, 43);
    P.out = (__nv_bfloat16*)d_out;
    typedef const __nv_bfloat16* W;
    fused_kernel<<<NCTA, NALL, SM_TOTAL>>>((W)d_in[0], (W)d_in[9], (W)d_in[1], (W)d_in[10], (W)d_in[3], (char*)(((size_t)raw + X_ALIGN - 1) & ~(size_t)(X_ALIGN - 1)), P);
}
```
